```python
import torch

def _softmax(x, axis=-1):
    return torch.softmax(x, dim=axis)

def _gelu(x):
    return torch.nn.functional.gelu(x, approximate='tanh')

def _silu(x):
    return torch.nn.functional.silu(x)

def _sigmoid(x):
    return torch.sigmoid(x)

def _layernorm(x, axis=-1, eps=1e-05):
    m = x.mean(dim=axis, keepdim=True)
    v = x.var(dim=axis, keepdim=True, unbiased=False)
    return (x - m) / torch.sqrt(v + eps)

def _scatter_add(tgt, idx, src, axis=0):
    return tgt.clone().index_add_(axis, idx, src)

def _segment_sum(src, seg, n):
    out = torch.zeros((n,) + src.shape[1:], dtype=src.dtype)
    return out.index_add_(0, seg, src)

def _pad(x, pw):
    flat = tuple((v for pair in reversed(pw) for v in pair))
    return torch.nn.functional.pad(x, flat)
kernel_name = 'recurrent_scan__ssm_conv_h3__mixer_gmlp__prompt'

def setup_inputs():

    _w = lambda a: (lambda t: t.to(torch.bfloat16) if t.is_floating_point() else t)(torch.as_tensor(a))

    def _A_setup():
        B, S, D = (1, 2048, 640)
        ks = 4
        return {'q': _w((lambda *s: torch.randn(*s, dtype=torch.bfloat16) * 0.05)(B, S, D)), 'k': _w((lambda *s: torch.randn(*s, dtype=torch.bfloat16) * 0.2)(B, S, D)), 'v': _w((lambda *s: torch.randn(*s, dtype=torch.bfloat16) * 0.2)(B, S, D)), 'shift_k': _w((lambda *s: torch.randn(*s, dtype=torch.bfloat16) * 0.2)(D, ks) * 0.5), 'ssm_k': _w((lambda *s: torch.randn(*s, dtype=torch.bfloat16) * 0.2)(D, S) * (1.0 / S ** 0.5)), 'ssm_D': _w((lambda *s: torch.randn(*s, dtype=torch.bfloat16) * 0.2)(D))}
    _A_in = _A_setup()

    def _B_setup():
        B, S, D, F = (1, 2048, 640, 1536)
        Fh = F // 2
        return {'x': _w((lambda *s: torch.randn(*s, dtype=torch.bfloat16) * 0.05)(B, S, D)), 'w_in': _w((lambda *s: torch.randn(*s, dtype=torch.bfloat16) * 0.8)(D, 2 * Fh)), 'w_sp': _w(0.01 * (lambda *s: torch.randn(*s, dtype=torch.bfloat16) * 0.8)(S, S)), 'b_sp': _w(1.0 + 0.01 * (lambda *s: torch.randn(*s, dtype=torch.bfloat16) * 0.1)(S)), 'w_out': _w((lambda *s: torch.randn(*s, dtype=torch.bfloat16) * 0.1)(Fh, D))}
    _B_in = _B_setup()
    return {'A_q': _A_in['q'], 'A_k': _A_in['k'], 'A_v': _A_in['v'], 'A_shift_k': _A_in['shift_k'], 'A_ssm_k': _A_in['ssm_k'], 'A_ssm_D': _A_in['ssm_D'], 'B_x': _B_in['x'], 'B_w_in': _B_in['w_in'], 'B_w_sp': _B_in['w_sp'], 'B_b_sp': _B_in['b_sp'], 'B_w_out': _B_in['w_out']}

def reference(A_q, A_k, A_v, A_shift_k, A_ssm_k, A_ssm_D, B_x, B_w_in, B_w_sp, B_b_sp, B_w_out):

    def _A_ref(q, k, v, shift_k, ssm_k, ssm_D):
        B, S, D = q.shape
        ks = shift_k.shape[-1]
        k_pad = _pad(k, ((0, 0), (ks - 1, 0), (0, 0)))
        k_shift = torch.zeros_like(k)
        for t in range(ks):
            k_shift = k_shift + k_pad[:, t:t + S, :] * shift_k[:, ks - 1 - t][None, None, :]
        kv = k_shift * v
        L = 2 * S
        kv_pad = _pad(kv, ((0, 0), (0, S), (0, 0)))
        kf_pad = _pad(ssm_k, ((0, 0), (0, S)))
        kv_f = (lambda x, axes=(-2, -1): torch.fft.rfft2(x.float(), dim=axes))(kv_pad[:, None, :, :], axes=(1, 2))
        kf_f = (lambda x, axes=(-2, -1): torch.fft.rfft2(x.float(), dim=axes))(kf_pad[:, None, :], axes=(1, 2))
        kf_f = (lambda x, *d: x.permute(*d))(kf_f, 1, 2, 0)
        y_f = kv_f * kf_f[None, :, :, :]
        y = (lambda x, s, axes=(-2, -1): torch.fft.irfft2(x, s=s, dim=axes).to(torch.bfloat16))(y_f, (1, L), axes=(1, 2))[:, 0, :S, :]
        y = y + kv * ssm_D[None, None, :]
        return q * y

    def _B_ref(x, w_in, w_sp, b_sp, w_out):
        B, S, D = x.shape
        F = w_in.shape[-1]
        Fh = F // 2
        z = _gelu(torch.einsum('bsd,df->bsf', x, w_in))
        z1 = z[..., :Fh].clone()
        z2 = _layernorm(z[..., Fh:], axis=-1)
        g = torch.einsum('ts,bsf->btf', w_sp, z2) + b_sp[None, :, None]
        return torch.einsum('bsf,fd->bsd', z1 * g, w_out)
    x = A_q
    xn = _layernorm(x, axis=-1)
    s = _A_ref(xn, A_k, A_v, A_shift_k, A_ssm_k, A_ssm_D)
    g = _silu(_B_ref(xn, B_w_in, B_w_sp, B_b_sp, B_w_out))
    return x + s * g
```

```cpp
#include <cuda_runtime.h>
#include <cuda.h>
#include <cuda_bf16.h>
#include <stdint.h>

template <int N> struct WG;
template <> struct WG<16> {
  static __device__ __forceinline__ void rs(float* d, const uint32_t* a, uint64_t db) {
    asm volatile("{\n.reg .pred p;\nsetp.ne.b32 p, 1, 0;\nwgmma.mma_async.sync.aligned.m64n16k16.f32.bf16.bf16 {"
      "%0, %1, %2, %3, %4, %5, %6, %7"
      "}, {%8, %9, %10, %11}, %12, p, 1, 1, 0;\n}\n"
      :
      "+f"(d[0]), "+f"(d[1]), "+f"(d[2]), "+f"(d[3]), "+f"(d[4]), "+f"(d[5]), "+f"(d[6]), "+f"(d[7])
      : "r"(a[0]), "r"(a[1]), "r"(a[2]), "r"(a[3]), "l"(db));
  }
};
template <> struct WG<32> {
  static __device__ __forceinline__ void rs(float* d, const uint32_t* a, uint64_t db) {
    asm volatile("{\n.reg .pred p;\nsetp.ne.b32 p, 1, 0;\nwgmma.mma_async.sync.aligned.m64n32k16.f32.bf16.bf16 {"
      "%0, %1, %2, %3, %4, %5, %6, %7, %8, %9, %10, %11, %12, %13, %14, %15"
      "}, {%16, %17, %18, %19}, %20, p, 1, 1, 0;\n}\n"
      :
      "+f"(d[0]), "+f"(d[1]), "+f"(d[2]), "+f"(d[3]), "+f"(d[4]), "+f"(d[5]), "+f"(d[6]), "+f"(d[7]),
      "+f"(d[8]), "+f"(d[9]), "+f"(d[10]), "+f"(d[11]), "+f"(d[12]), "+f"(d[13]), "+f"(d[14]), "+f"(d[15])
      : "r"(a[0]), "r"(a[1]), "r"(a[2]), "r"(a[3]), "l"(db));
  }
};
template <> struct WG<48> {
  static __device__ __forceinline__ void rs(float* d, const uint32_t* a, uint64_t db) {
    asm volatile("{\n.reg .pred p;\nsetp.ne.b32 p, 1, 0;\nwgmma.mma_async.sync.aligned.m64n48k16.f32.bf16.bf16 {"
      "%0, %1, %2, %3, %4, %5, %6, %7, %8, %9, %10, %11, %12, %13, %14, %15, "
      "%16, %17, %18, %19, %20, %21, %22, %23"
      "}, {%24, %25, %26, %27}, %28, p, 1, 1, 0;\n}\n"
      :
      "+f"(d[0]), "+f"(d[1]), "+f"(d[2]), "+f"(d[3]), "+f"(d[4]), "+f"(d[5]), "+f"(d[6]), "+f"(d[7]),
      "+f"(d[8]), "+f"(d[9]), "+f"(d[10]), "+f"(d[11]), "+f"(d[12]), "+f"(d[13]), "+f"(d[14]), "+f"(d[15]),
      "+f"(d[16]), "+f"(d[17]), "+f"(d[18]), "+f"(d[19]), "+f"(d[20]), "+f"(d[21]), "+f"(d[22]), "+f"(d[23])
      : "r"(a[0]), "r"(a[1]), "r"(a[2]), "r"(a[3]), "l"(db));
  }
};
template <> struct WG<64> {
  static __device__ __forceinline__ void rs(float* d, const uint32_t* a, uint64_t db) {
    asm volatile("{\n.reg .pred p;\nsetp.ne.b32 p, 1, 0;\nwgmma.mma_async.sync.aligned.m64n64k16.f32.bf16.bf16 {"
      "%0, %1, %2, %3, %4, %5, %6, %7, %8, %9, %10, %11, %12, %13, %14, %15, "
      "%16, %17, %18, %19, %20, %21, %22, %23, %24, %25, %26, %27, %28, %29, %30, %31"
      "}, {%32, %33, %34, %35}, %36, p, 1, 1, 0;\n}\n"
      :
      "+f"(d[0]), "+f"(d[1]), "+f"(d[2]), "+f"(d[3]), "+f"(d[4]), "+f"(d[5]), "+f"(d[6]), "+f"(d[7]),
      "+f"(d[8]), "+f"(d[9]), "+f"(d[10]), "+f"(d[11]), "+f"(d[12]), "+f"(d[13]), "+f"(d[14]), "+f"(d[15]),
      "+f"(d[16]), "+f"(d[17]), "+f"(d[18]), "+f"(d[19]), "+f"(d[20]), "+f"(d[21]), "+f"(d[22]), "+f"(d[23]),
      "+f"(d[24]), "+f"(d[25]), "+f"(d[26]), "+f"(d[27]), "+f"(d[28]), "+f"(d[29]), "+f"(d[30]), "+f"(d[31])
      : "r"(a[0]), "r"(a[1]), "r"(a[2]), "r"(a[3]), "l"(db));
  }
};
template <> struct WG<80> {
  static __device__ __forceinline__ void rs(float* d, const uint32_t* a, uint64_t db) {
    asm volatile("{\n.reg .pred p;\nsetp.ne.b32 p, 1, 0;\nwgmma.mma_async.sync.aligned.m64n80k16.f32.bf16.bf16 {"
      "%0, %1, %2, %3, %4, %5, %6, %7, %8, %9, %10, %11, %12, %13, %14, %15, "
      "%16, %17, %18, %19, %20, %21, %22, %23, %24, %25, %26, %27, %28, %29, %30, %31, "
      "%32, %33, %34, %35, %36, %37, %38, %39"
      "}, {%40, %41, %42, %43}, %44, p, 1, 1, 0;\n}\n"
      :
      "+f"(d[0]), "+f"(d[1]), "+f"(d[2]), "+f"(d[3]), "+f"(d[4]), "+f"(d[5]), "+f"(d[6]), "+f"(d[7]),
      "+f"(d[8]), "+f"(d[9]), "+f"(d[10]), "+f"(d[11]), "+f"(d[12]), "+f"(d[13]), "+f"(d[14]), "+f"(d[15]),
      "+f"(d[16]), "+f"(d[17]), "+f"(d[18]), "+f"(d[19]), "+f"(d[20]), "+f"(d[21]), "+f"(d[22]), "+f"(d[23]),
      "+f"(d[24]), "+f"(d[25]), "+f"(d[26]), "+f"(d[27]), "+f"(d[28]), "+f"(d[29]), "+f"(d[30]), "+f"(d[31]),
      "+f"(d[32]), "+f"(d[33]), "+f"(d[34]), "+f"(d[35]), "+f"(d[36]), "+f"(d[37]), "+f"(d[38]), "+f"(d[39])
      : "r"(a[0]), "r"(a[1]), "r"(a[2]), "r"(a[3]), "l"(db));
  }
};
template <> struct WG<96> {
  static __device__ __forceinline__ void rs(float* d, const uint32_t* a, uint64_t db) {
    asm volatile("{\n.reg .pred p;\nsetp.ne.b32 p, 1, 0;\nwgmma.mma_async.sync.aligned.m64n96k16.f32.bf16.bf16 {"
      "%0, %1, %2, %3, %4, %5, %6, %7, %8, %9, %10, %11, %12, %13, %14, %15, "
      "%16, %17, %18, %19, %20, %21, %22, %23, %24, %25, %26, %27, %28, %29, %30, %31, "
      "%32, %33, %34, %35, %36, %37, %38, %39, %40, %41, %42, %43, %44, %45, %46, %47"
      "}, {%48, %49, %50, %51}, %52, p, 1, 1, 0;\n}\n"
      :
      "+f"(d[0]), "+f"(d[1]), "+f"(d[2]), "+f"(d[3]), "+f"(d[4]), "+f"(d[5]), "+f"(d[6]), "+f"(d[7]),
      "+f"(d[8]), "+f"(d[9]), "+f"(d[10]), "+f"(d[11]), "+f"(d[12]), "+f"(d[13]), "+f"(d[14]), "+f"(d[15]),
      "+f"(d[16]), "+f"(d[17]), "+f"(d[18]), "+f"(d[19]), "+f"(d[20]), "+f"(d[21]), "+f"(d[22]), "+f"(d[23]),
      "+f"(d[24]), "+f"(d[25]), "+f"(d[26]), "+f"(d[27]), "+f"(d[28]), "+f"(d[29]), "+f"(d[30]), "+f"(d[31]),
      "+f"(d[32]), "+f"(d[33]), "+f"(d[34]), "+f"(d[35]), "+f"(d[36]), "+f"(d[37]), "+f"(d[38]), "+f"(d[39]),
      "+f"(d[40]), "+f"(d[41]), "+f"(d[42]), "+f"(d[43]), "+f"(d[44]), "+f"(d[45]), "+f"(d[46]), "+f"(d[47])
      : "r"(a[0]), "r"(a[1]), "r"(a[2]), "r"(a[3]), "l"(db));
  }
};
template <> struct WG<112> {
  static __device__ __forceinline__ void rs(float* d, const uint32_t* a, uint64_t db) {
    asm volatile("{\n.reg .pred p;\nsetp.ne.b32 p, 1, 0;\nwgmma.mma_async.sync.aligned.m64n112k16.f32.bf16.bf16 {"
      "%0, %1, %2, %3, %4, %5, %6, %7, %8, %9, %10, %11, %12, %13, %14, %15, "
      "%16, %17, %18, %19, %20, %21, %22, %23, %24, %25, %26, %27, %28, %29, %30, %31, "
      "%32, %33, %34, %35, %36, %37, %38, %39, %40, %41, %42, %43, %44, %45, %46, %47, "
      "%48, %49, %50, %51, %52, %53, %54, %55"
      "}, {%56, %57, %58, %59}, %60, p, 1, 1, 0;\n}\n"
      :
      "+f"(d[0]), "+f"(d[1]), "+f"(d[2]), "+f"(d[3]), "+f"(d[4]), "+f"(d[5]), "+f"(d[6]), "+f"(d[7]),
      "+f"(d[8]), "+f"(d[9]), "+f"(d[10]), "+f"(d[11]), "+f"(d[12]), "+f"(d[13]), "+f"(d[14]), "+f"(d[15]),
      "+f"(d[16]), "+f"(d[17]), "+f"(d[18]), "+f"(d[19]), "+f"(d[20]), "+f"(d[21]), "+f"(d[22]), "+f"(d[23]),
      "+f"(d[24]), "+f"(d[25]), "+f"(d[26]), "+f"(d[27]), "+f"(d[28]), "+f"(d[29]), "+f"(d[30]), "+f"(d[31]),
      "+f"(d[32]), "+f"(d[33]), "+f"(d[34]), "+f"(d[35]), "+f"(d[36]), "+f"(d[37]), "+f"(d[38]), "+f"(d[39]),
      "+f"(d[40]), "+f"(d[41]), "+f"(d[42]), "+f"(d[43]), "+f"(d[44]), "+f"(d[45]), "+f"(d[46]), "+f"(d[47]),
      "+f"(d[48]), "+f"(d[49]), "+f"(d[50]), "+f"(d[51]), "+f"(d[52]), "+f"(d[53]), "+f"(d[54]), "+f"(d[55])
      : "r"(a[0]), "r"(a[1]), "r"(a[2]), "r"(a[3]), "l"(db));
  }
};
template <> struct WG<128> {
  static __device__ __forceinline__ void rs(float* d, const uint32_t* a, uint64_t db) {
    asm volatile("{\n.reg .pred p;\nsetp.ne.b32 p, 1, 0;\nwgmma.mma_async.sync.aligned.m64n128k16.f32.bf16.bf16 {"
      "%0, %1, %2, %3, %4, %5, %6, %7, %8, %9, %10, %11, %12, %13, %14, %15, "
      "%16, %17, %18, %19, %20, %21, %22, %23, %24, %25, %26, %27, %28, %29, %30, %31, "
      "%32, %33, %34, %35, %36, %37, %38, %39, %40, %41, %42, %43, %44, %45, %46, %47, "
      "%48, %49, %50, %51, %52, %53, %54, %55, %56, %57, %58, %59, %60, %61, %62, %63"
      "}, {%64, %65, %66, %67}, %68, p, 1, 1, 0;\n}\n"
      :
      "+f"(d[0]), "+f"(d[1]), "+f"(d[2]), "+f"(d[3]), "+f"(d[4]), "+f"(d[5]), "+f"(d[6]), "+f"(d[7]),
      "+f"(d[8]), "+f"(d[9]), "+f"(d[10]), "+f"(d[11]), "+f"(d[12]), "+f"(d[13]), "+f"(d[14]), "+f"(d[15]),
      "+f"(d[16]), "+f"(d[17]), "+f"(d[18]), "+f"(d[19]), "+f"(d[20]), "+f"(d[21]), "+f"(d[22]), "+f"(d[23]),
      "+f"(d[24]), "+f"(d[25]), "+f"(d[26]), "+f"(d[27]), "+f"(d[28]), "+f"(d[29]), "+f"(d[30]), "+f"(d[31]),
      "+f"(d[32]), "+f"(d[33]), "+f"(d[34]), "+f"(d[35]), "+f"(d[36]), "+f"(d[37]), "+f"(d[38]), "+f"(d[39]),
      "+f"(d[40]), "+f"(d[41]), "+f"(d[42]), "+f"(d[43]), "+f"(d[44]), "+f"(d[45]), "+f"(d[46]), "+f"(d[47]),
      "+f"(d[48]), "+f"(d[49]), "+f"(d[50]), "+f"(d[51]), "+f"(d[52]), "+f"(d[53]), "+f"(d[54]), "+f"(d[55]),
      "+f"(d[56]), "+f"(d[57]), "+f"(d[58]), "+f"(d[59]), "+f"(d[60]), "+f"(d[61]), "+f"(d[62]), "+f"(d[63])
      : "r"(a[0]), "r"(a[1]), "r"(a[2]), "r"(a[3]), "l"(db));
  }
};
template <int N> struct KB;
template <> struct KB<80> {
  template <int W, int RC, bool RA, int BSTEP, bool D1> static __device__ __forceinline__ void run(float* d, uint64_t da, uint64_t db, uint32_t rel, uint32_t rela, uint32_t doR, uint32_t fa, uint32_t pa, uint32_t fb, uint32_t pb, uint32_t acc) {
    if constexpr (W == 0 && RC == 1 && RA == 0 && D1 == 0) asm volatile(
    "{\n.reg .pred p, q, r, t;\n.reg .b64 a, b;\n.reg .u32 n;\nsetp.ne.b32 t, 1, 0;\nsetp.ne.b32 r, %49, 0;\n"
    "wgmma.mma_async.sync.aligned.m64n80k16.f32.bf16.bf16 {"
      "%0, %1, %2, %3, %4, %5, %6, %7, %8, %9, %10, %11, %12, %13, %14, %15, "
      "%16, %17, %18, %19, %20, %21, %22, %23, %24, %25, %26, %27, %28, %29, %30, %31, "
      "%32, %33, %34, %35, %36, %37, %38, %39"
      "}, %40, %41, r, 1, 1, 0, 1;\n"
    "add.u64 a, %40, 2;\nadd.u64 b, %41, %48;\n"
    "wgmma.mma_async.sync.aligned.m64n80k16.f32.bf16.bf16 {"
      "%0, %1, %2, %3, %4, %5, %6, %7, %8, %9, %10, %11, %12, %13, %14, %15, "
      "%16, %17, %18, %19, %20, %21, %22, %23, %24, %25, %26, %27, %28, %29, %30, %31, "
      "%32, %33, %34, %35, %36, %37, %38, %39"
      "}, a, b, t, 1, 1, 0, 1;\n"
    "wgmma.commit_group.sync.aligned;\nwgmma.wait_group.sync.aligned 1;\n"
    "add.u64 a, %40, 4;\nadd.u64 b, %41, 2*%48;\n"
    "wgmma.mma_async.sync.aligned.m64n80k16.f32.bf16.bf16 {"
      "%0, %1, %2, %3, %4, %5, %6, %7, %8, %9, %10, %11, %12, %13, %14, %15, "
      "%16, %17, %18, %19, %20, %21, %22, %23, %24, %25, %26, %27, %28, %29, %30, %31, "
      "%32, %33, %34, %35, %36, %37, %38, %39"
      "}, a, b, t, 1, 1, 0, 1;\n"
    "setp.ne.u32 q, %43, 0;\n@q mbarrier.arrive.shared::cta.b64 _, [%42];\n"
    "add.u64 a, %40, 6;\nadd.u64 b, %41, 3*%48;\n"
    "wgmma.mma_async.sync.aligned.m64n80k16.f32.bf16.bf16 {"
      "%0, %1, %2, %3, %4, %5, %6, %7, %8, %9, %10, %11, %12, %13, %14, %15, "
      "%16, %17, %18, %19, %20, %21, %22, %23, %24, %25, %26, %27, %28, %29, %30, %31, "
      "%32, %33, %34, %35, %36, %37, %38, %39"
      "}, a, b, t, 1, 1, 0, 1;\n"
    "wgmma.commit_group.sync.aligned;\n"
    "}\n"
      :
      "+f"(d[0]), "+f"(d[1]), "+f"(d[2]), "+f"(d[3]), "+f"(d[4]), "+f"(d[5]), "+f"(d[6]), "+f"(d[7]),
      "+f"(d[8]), "+f"(d[9]), "+f"(d[10]), "+f"(d[11]), "+f"(d[12]), "+f"(d[13]), "+f"(d[14]), "+f"(d[15]),
      "+f"(d[16]), "+f"(d[17]), "+f"(d[18]), "+f"(d[19]), "+f"(d[20]), "+f"(d[21]), "+f"(d[22]), "+f"(d[23]),
      "+f"(d[24]), "+f"(d[25]), "+f"(d[26]), "+f"(d[27]), "+f"(d[28]), "+f"(d[29]), "+f"(d[30]), "+f"(d[31]),
      "+f"(d[32]), "+f"(d[33]), "+f"(d[34]), "+f"(d[35]), "+f"(d[36]), "+f"(d[37]), "+f"(d[38]), "+f"(d[39])
      : "l"(da), "l"(db), "r"(rel), "r"(doR), "r"(fa), "r"(pa), "r"(fb), "r"(pb), "n"(BSTEP), "r"(acc), "r"(rela) : "memory");
    else if constexpr (W == 2 && RC == 1 && RA == 0 && D1 == 0) asm volatile(
    "{\n.reg .pred p, q, r, t;\n.reg .b64 a, b;\n.reg .u32 n;\nsetp.ne.b32 t, 1, 0;\nsetp.ne.b32 r, %49, 0;\n"
    "wgmma.mma_async.sync.aligned.m64n80k16.f32.bf16.bf16 {"
      "%0, %1, %2, %3, %4, %5, %6, %7, %8, %9, %10, %11, %12, %13, %14, %15, "
      "%16, %17, %18, %19, %20, %21, %22, %23, %24, %25, %26, %27, %28, %29, %30, %31, "
      "%32, %33, %34, %35, %36, %37, %38, %39"
      "}, %40, %41, r, 1, 1, 0, 1;\n"
    "add.u64 a, %40, 2;\nadd.u64 b, %41, %48;\n"
    "wgmma.mma_async.sync.aligned.m64n80k16.f32.bf16.bf16 {"
      "%0, %1, %2, %3, %4, %5, %6, %7, %8, %9, %10, %11, %12, %13, %14, %15, "
      "%16, %17, %18, %19, %20, %21, %22, %23, %24, %25, %26, %27, %28, %29, %30, %31, "
      "%32, %33, %34, %35, %36, %37, %38, %39"
      "}, a, b, t, 1, 1, 0, 1;\n"
    "wgmma.commit_group.sync.aligned;\nwgmma.wait_group.sync.aligned 1;\n"
    "add.u64 a, %40, 4;\nadd.u64 b, %41, 2*%48;\n"
    "wgmma.mma_async.sync.aligned.m64n80k16.f32.bf16.bf16 {"
      "%0, %1, %2, %3, %4, %5, %6, %7, %8, %9, %10, %11, %12, %13, %14, %15, "
      "%16, %17, %18, %19, %20, %21, %22, %23, %24, %25, %26, %27, %28, %29, %30, %31, "
      "%32, %33, %34, %35, %36, %37, %38, %39"
      "}, a, b, t, 1, 1, 0, 1;\n"
    "setp.ne.u32 q, %43, 0;\n@q mbarrier.arrive.shared::cta.b64 _, [%42];\n"
    "mbarrier.test_wait.parity.shared::cta.b64 p, [%46], %47;\n"
    "mbarrier.test_wait.parity.shared::cta.b64 r, [%44], %45;\nand.pred p, p, r;\n"
    "add.u64 a, %40, 6;\nadd.u64 b, %41, 3*%48;\n"
    "wgmma.mma_async.sync.aligned.m64n80k16.f32.bf16.bf16 {"
      "%0, %1, %2, %3, %4, %5, %6, %7, %8, %9, %10, %11, %12, %13, %14, %15, "
      "%16, %17, %18, %19, %20, %21, %22, %23, %24, %25, %26, %27, %28, %29, %30, %31, "
      "%32, %33, %34, %35, %36, %37, %38, %39"
      "}, a, b, t, 1, 1, 0, 1;\n"
    "wgmma.commit_group.sync.aligned;\n"
    "@p bra.uni DN;\nmov.u32 n, 0;\nWT: mbarrier.try_wait.parity.shared::cta.b64 p, [%46], %47;\nmbarrier.try_wait.parity.shared::cta.b64 r, [%44], %45;\nand.pred p, p, r;\n@p bra.uni DN;\nadd.u32 n, n, 1;\nsetp.lt.u32 p, n, 0x100000;\n@p bra.uni WT;\nDN:\n"
    "}\n"
      :
      "+f"(d[0]), "+f"(d[1]), "+f"(d[2]), "+f"(d[3]), "+f"(d[4]), "+f"(d[5]), "+f"(d[6]), "+f"(d[7]),
      "+f"(d[8]), "+f"(d[9]), "+f"(d[10]), "+f"(d[11]), "+f"(d[12]), "+f"(d[13]), "+f"(d[14]), "+f"(d[15]),
      "+f"(d[16]), "+f"(d[17]), "+f"(d[18]), "+f"(d[19]), "+f"(d[20]), "+f"(d[21]), "+f"(d[22]), "+f"(d[23]),
      "+f"(d[24]), "+f"(d[25]), "+f"(d[26]), "+f"(d[27]), "+f"(d[28]), "+f"(d[29]), "+f"(d[30]), "+f"(d[31]),
      "+f"(d[32]), "+f"(d[33]), "+f"(d[34]), "+f"(d[35]), "+f"(d[36]), "+f"(d[37]), "+f"(d[38]), "+f"(d[39])
      : "l"(da), "l"(db), "r"(rel), "r"(doR), "r"(fa), "r"(pa), "r"(fb), "r"(pb), "n"(BSTEP), "r"(acc), "r"(rela) : "memory");
    else static_assert(W < 0, "variant not generated");
  }
};
template <> struct KB<160> {
  template <int W, int RC, bool RA, int BSTEP, bool D1> static __device__ __forceinline__ void run(float* d, uint64_t da, uint64_t db, uint32_t rel, uint32_t rela, uint32_t doR, uint32_t fa, uint32_t pa, uint32_t fb, uint32_t pb, uint32_t acc) {
    if constexpr (W == 0 && RC == 2 && RA == 0 && D1 == 0) asm volatile(
    "{\n.reg .pred p, q, r, t;\n.reg .b64 a, b;\n.reg .u32 n;\nsetp.ne.b32 t, 1, 0;\nsetp.ne.b32 r, %89, 0;\n"
    "wgmma.mma_async.sync.aligned.m64n160k16.f32.bf16.bf16 {"
      "%0, %1, %2, %3, %4, %5, %6, %7, %8, %9, %10, %11, %12, %13, %14, %15, "
      "%16, %17, %18, %19, %20, %21, %22, %23, %24, %25, %26, %27, %28, %29, %30, %31, "
      "%32, %33, %34, %35, %36, %37, %38, %39, %40, %41, %42, %43, %44, %45, %46, %47, "
      "%48, %49, %50, %51, %52, %53, %54, %55, %56, %57, %58, %59, %60, %61, %62, %63, "
      "%64, %65, %66, %67, %68, %69, %70, %71, %72, %73, %74, %75, %76, %77, %78, %79"
      "}, %80, %81, r, 1, 1, 0, 1;\n"
    "add.u64 a, %80, 2;\nadd.u64 b, %81, %88;\n"
    "wgmma.mma_async.sync.aligned.m64n160k16.f32.bf16.bf16 {"
      "%0, %1, %2, %3, %4, %5, %6, %7, %8, %9, %10, %11, %12, %13, %14, %15, "
      "%16, %17, %18, %19, %20, %21, %22, %23, %24, %25, %26, %27, %28, %29, %30, %31, "
      "%32, %33, %34, %35, %36, %37, %38, %39, %40, %41, %42, %43, %44, %45, %46, %47, "
      "%48, %49, %50, %51, %52, %53, %54, %55, %56, %57, %58, %59, %60, %61, %62, %63, "
      "%64, %65, %66, %67, %68, %69, %70, %71, %72, %73, %74, %75, %76, %77, %78, %79"
      "}, a, b, t, 1, 1, 0, 1;\n"
    "wgmma.commit_group.sync.aligned;\nwgmma.wait_group.sync.aligned 1;\n"
    "add.u64 a, %80, 4;\nadd.u64 b, %81, 2*%88;\n"
    "wgmma.mma_async.sync.aligned.m64n160k16.f32.bf16.bf16 {"
      "%0, %1, %2, %3, %4, %5, %6, %7, %8, %9, %10, %11, %12, %13, %14, %15, "
      "%16, %17, %18, %19, %20, %21, %22, %23, %24, %25, %26, %27, %28, %29, %30, %31, "
      "%32, %33, %34, %35, %36, %37, %38, %39, %40, %41, %42, %43, %44, %45, %46, %47, "
      "%48, %49, %50, %51, %52, %53, %54, %55, %56, %57, %58, %59, %60, %61, %62, %63, "
      "%64, %65, %66, %67, %68, %69, %70, %71, %72, %73, %74, %75, %76, %77, %78, %79"
      "}, a, b, t, 1, 1, 0, 1;\n"
    "setp.ne.u32 q, %83, 0;\n@q mbarrier.arrive.shared::cta.b64 _, [%82];\n@q mbarrier.arrive.shared::cta.b64 _, [%82];\n"
    "add.u64 a, %80, 6;\nadd.u64 b, %81, 3*%88;\n"
    "wgmma.mma_async.sync.aligned.m64n160k16.f32.bf16.bf16 {"
      "%0, %1, %2, %3, %4, %5, %6, %7, %8, %9, %10, %11, %12, %13, %14, %15, "
      "%16, %17, %18, %19, %20, %21, %22, %23, %24, %25, %26, %27, %28, %29, %30, %31, "
      "%32, %33, %34, %35, %36, %37, %38, %39, %40, %41, %42, %43, %44, %45, %46, %47, "
      "%48, %49, %50, %51, %52, %53, %54, %55, %56, %57, %58, %59, %60, %61, %62, %63, "
      "%64, %65, %66, %67, %68, %69, %70, %71, %72, %73, %74, %75, %76, %77, %78, %79"
      "}, a, b, t, 1, 1, 0, 1;\n"
    "wgmma.commit_group.sync.aligned;\n"
    "}\n"
      :
      "+f"(d[0]), "+f"(d[1]), "+f"(d[2]), "+f"(d[3]), "+f"(d[4]), "+f"(d[5]), "+f"(d[6]), "+f"(d[7]),
      "+f"(d[8]), "+f"(d[9]), "+f"(d[10]), "+f"(d[11]), "+f"(d[12]), "+f"(d[13]), "+f"(d[14]), "+f"(d[15]),
      "+f"(d[16]), "+f"(d[17]), "+f"(d[18]), "+f"(d[19]), "+f"(d[20]), "+f"(d[21]), "+f"(d[22]), "+f"(d[23]),
      "+f"(d[24]), "+f"(d[25]), "+f"(d[26]), "+f"(d[27]), "+f"(d[28]), "+f"(d[29]), "+f"(d[30]), "+f"(d[31]),
      "+f"(d[32]), "+f"(d[33]), "+f"(d[34]), "+f"(d[35]), "+f"(d[36]), "+f"(d[37]), "+f"(d[38]), "+f"(d[39]),
      "+f"(d[40]), "+f"(d[41]), "+f"(d[42]), "+f"(d[43]), "+f"(d[44]), "+f"(d[45]), "+f"(d[46]), "+f"(d[47]),
      "+f"(d[48]), "+f"(d[49]), "+f"(d[50]), "+f"(d[51]), "+f"(d[52]), "+f"(d[53]), "+f"(d[54]), "+f"(d[55]),
      "+f"(d[56]), "+f"(d[57]), "+f"(d[58]), "+f"(d[59]), "+f"(d[60]), "+f"(d[61]), "+f"(d[62]), "+f"(d[63]),
      "+f"(d[64]), "+f"(d[65]), "+f"(d[66]), "+f"(d[67]), "+f"(d[68]), "+f"(d[69]), "+f"(d[70]), "+f"(d[71]),
      "+f"(d[72]), "+f"(d[73]), "+f"(d[74]), "+f"(d[75]), "+f"(d[76]), "+f"(d[77]), "+f"(d[78]), "+f"(d[79])
      : "l"(da), "l"(db), "r"(rel), "r"(doR), "r"(fa), "r"(pa), "r"(fb), "r"(pb), "n"(BSTEP), "r"(acc), "r"(rela) : "memory");
    else if constexpr (W == 1 && RC == 2 && RA == 0 && D1 == 0) asm volatile(
    "{\n.reg .pred p, q, r, t;\n.reg .b64 a, b;\n.reg .u32 n;\nsetp.ne.b32 t, 1, 0;\nsetp.ne.b32 r, %89, 0;\n"
    "wgmma.mma_async.sync.aligned.m64n160k16.f32.bf16.bf16 {"
      "%0, %1, %2, %3, %4, %5, %6, %7, %8, %9, %10, %11, %12, %13, %14, %15, "
      "%16, %17, %18, %19, %20, %21, %22, %23, %24, %25, %26, %27, %28, %29, %30, %31, "
      "%32, %33, %34, %35, %36, %37, %38, %39, %40, %41, %42, %43, %44, %45, %46, %47, "
      "%48, %49, %50, %51, %52, %53, %54, %55, %56, %57, %58, %59, %60, %61, %62, %63, "
      "%64, %65, %66, %67, %68, %69, %70, %71, %72, %73, %74, %75, %76, %77, %78, %79"
      "}, %80, %81, r, 1, 1, 0, 1;\n"
    "add.u64 a, %80, 2;\nadd.u64 b, %81, %88;\n"
    "wgmma.mma_async.sync.aligned.m64n160k16.f32.bf16.bf16 {"
      "%0, %1, %2, %3, %4, %5, %6, %7, %8, %9, %10, %11, %12, %13, %14, %15, "
      "%16, %17, %18, %19, %20, %21, %22, %23, %24, %25, %26, %27, %28, %29, %30, %31, "
      "%32, %33, %34, %35, %36, %37, %38, %39, %40, %41, %42, %43, %44, %45, %46, %47, "
      "%48, %49, %50, %51, %52, %53, %54, %55, %56, %57, %58, %59, %60, %61, %62, %63, "
      "%64, %65, %66, %67, %68, %69, %70, %71, %72, %73, %74, %75, %76, %77, %78, %79"
      "}, a, b, t, 1, 1, 0, 1;\n"
    "wgmma.commit_group.sync.aligned;\nwgmma.wait_group.sync.aligned 1;\n"
    "add.u64 a, %80, 4;\nadd.u64 b, %81, 2*%88;\n"
    "wgmma.mma_async.sync.aligned.m64n160k16.f32.bf16.bf16 {"
      "%0, %1, %2, %3, %4, %5, %6, %7, %8, %9, %10, %11, %12, %13, %14, %15, "
      "%16, %17, %18, %19, %20, %21, %22, %23, %24, %25, %26, %27, %28, %29, %30, %31, "
      "%32, %33, %34, %35, %36, %37, %38, %39, %40, %41, %42, %43, %44, %45, %46, %47, "
      "%48, %49, %50, %51, %52, %53, %54, %55, %56, %57, %58, %59, %60, %61, %62, %63, "
      "%64, %65, %66, %67, %68, %69, %70, %71, %72, %73, %74, %75, %76, %77, %78, %79"
      "}, a, b, t, 1, 1, 0, 1;\n"
    "setp.ne.u32 q, %83, 0;\n@q mbarrier.arrive.shared::cta.b64 _, [%82];\n@q mbarrier.arrive.shared::cta.b64 _, [%82];\n"
    "mbarrier.test_wait.parity.shared::cta.b64 p, [%86], %87;\n"
    "add.u64 a, %80, 6;\nadd.u64 b, %81, 3*%88;\n"
    "wgmma.mma_async.sync.aligned.m64n160k16.f32.bf16.bf16 {"
      "%0, %1, %2, %3, %4, %5, %6, %7, %8, %9, %10, %11, %12, %13, %14, %15, "
      "%16, %17, %18, %19, %20, %21, %22, %23, %24, %25, %26, %27, %28, %29, %30, %31, "
      "%32, %33, %34, %35, %36, %37, %38, %39, %40, %41, %42, %43, %44, %45, %46, %47, "
      "%48, %49, %50, %51, %52, %53, %54, %55, %56, %57, %58, %59, %60, %61, %62, %63, "
      "%64, %65, %66, %67, %68, %69, %70, %71, %72, %73, %74, %75, %76, %77, %78, %79"
      "}, a, b, t, 1, 1, 0, 1;\n"
    "wgmma.commit_group.sync.aligned;\n"
    "@p bra.uni DN;\nmov.u32 n, 0;\nWT: mbarrier.try_wait.parity.shared::cta.b64 p, [%86], %87;\n@p bra.uni DN;\nadd.u32 n, n, 1;\nsetp.lt.u32 p, n, 0x100000;\n@p bra.uni WT;\nDN:\n"
    "}\n"
      :
      "+f"(d[0]), "+f"(d[1]), "+f"(d[2]), "+f"(d[3]), "+f"(d[4]), "+f"(d[5]), "+f"(d[6]), "+f"(d[7]),
      "+f"(d[8]), "+f"(d[9]), "+f"(d[10]), "+f"(d[11]), "+f"(d[12]), "+f"(d[13]), "+f"(d[14]), "+f"(d[15]),
      "+f"(d[16]), "+f"(d[17]), "+f"(d[18]), "+f"(d[19]), "+f"(d[20]), "+f"(d[21]), "+f"(d[22]), "+f"(d[23]),
      "+f"(d[24]), "+f"(d[25]), "+f"(d[26]), "+f"(d[27]), "+f"(d[28]), "+f"(d[29]), "+f"(d[30]), "+f"(d[31]),
      "+f"(d[32]), "+f"(d[33]), "+f"(d[34]), "+f"(d[35]), "+f"(d[36]), "+f"(d[37]), "+f"(d[38]), "+f"(d[39]),
      "+f"(d[40]), "+f"(d[41]), "+f"(d[42]), "+f"(d[43]), "+f"(d[44]), "+f"(d[45]), "+f"(d[46]), "+f"(d[47]),
      "+f"(d[48]), "+f"(d[49]), "+f"(d[50]), "+f"(d[51]), "+f"(d[52]), "+f"(d[53]), "+f"(d[54]), "+f"(d[55]),
      "+f"(d[56]), "+f"(d[57]), "+f"(d[58]), "+f"(d[59]), "+f"(d[60]), "+f"(d[61]), "+f"(d[62]), "+f"(d[63]),
      "+f"(d[64]), "+f"(d[65]), "+f"(d[66]), "+f"(d[67]), "+f"(d[68]), "+f"(d[69]), "+f"(d[70]), "+f"(d[71]),
      "+f"(d[72]), "+f"(d[73]), "+f"(d[74]), "+f"(d[75]), "+f"(d[76]), "+f"(d[77]), "+f"(d[78]), "+f"(d[79])
      : "l"(da), "l"(db), "r"(rel), "r"(doR), "r"(fa), "r"(pa), "r"(fb), "r"(pb), "n"(BSTEP), "r"(acc), "r"(rela) : "memory");
    else static_assert(W < 0, "variant not generated");
  }
};
template <> struct KB<192> {
  template <int W, int RC, bool RA, int BSTEP, bool D1> static __device__ __forceinline__ void run(float* d, uint64_t da, uint64_t db, uint32_t rel, uint32_t rela, uint32_t doR, uint32_t fa, uint32_t pa, uint32_t fb, uint32_t pb, uint32_t acc) {
    if constexpr (W == 0 && RC == 2 && RA == 0 && D1 == 0) asm volatile(
    "{\n.reg .pred p, q, r, t;\n.reg .b64 a, b;\n.reg .u32 n;\nsetp.ne.b32 t, 1, 0;\nsetp.ne.b32 r, %105, 0;\n"
    "wgmma.mma_async.sync.aligned.m64n192k16.f32.bf16.bf16 {"
      "%0, %1, %2, %3, %4, %5, %6, %7, %8, %9, %10, %11, %12, %13, %14, %15, "
      "%16, %17, %18, %19, %20, %21, %22, %23, %24, %25, %26, %27, %28, %29, %30, %31, "
      "%32, %33, %34, %35, %36, %37, %38, %39, %40, %41, %42, %43, %44, %45, %46, %47, "
      "%48, %49, %50, %51, %52, %53, %54, %55, %56, %57, %58, %59, %60, %61, %62, %63, "
      "%64, %65, %66, %67, %68, %69, %70, %71, %72, %73, %74, %75, %76, %77, %78, %79, "
      "%80, %81, %82, %83, %84, %85, %86, %87, %88, %89, %90, %91, %92, %93, %94, %95"
      "}, %96, %97, r, 1, 1, 0, 1;\n"
    "add.u64 a, %96, 2;\nadd.u64 b, %97, %104;\n"
    "wgmma.mma_async.sync.aligned.m64n192k16.f32.bf16.bf16 {"
      "%0, %1, %2, %3, %4, %5, %6, %7, %8, %9, %10, %11, %12, %13, %14, %15, "
      "%16, %17, %18, %19, %20, %21, %22, %23, %24, %25, %26, %27, %28, %29, %30, %31, "
      "%32, %33, %34, %35, %36, %37, %38, %39, %40, %41, %42, %43, %44, %45, %46, %47, "
      "%48, %49, %50, %51, %52, %53, %54, %55, %56, %57, %58, %59, %60, %61, %62, %63, "
      "%64, %65, %66, %67, %68, %69, %70, %71, %72, %73, %74, %75, %76, %77, %78, %79, "
      "%80, %81, %82, %83, %84, %85, %86, %87, %88, %89, %90, %91, %92, %93, %94, %95"
      "}, a, b, t, 1, 1, 0, 1;\n"
    "wgmma.commit_group.sync.aligned;\nwgmma.wait_group.sync.aligned 1;\n"
    "add.u64 a, %96, 4;\nadd.u64 b, %97, 2*%104;\n"
    "wgmma.mma_async.sync.aligned.m64n192k16.f32.bf16.bf16 {"
      "%0, %1, %2, %3, %4, %5, %6, %7, %8, %9, %10, %11, %12, %13, %14, %15, "
      "%16, %17, %18, %19, %20, %21, %22, %23, %24, %25, %26, %27, %28, %29, %30, %31, "
      "%32, %33, %34, %35, %36, %37, %38, %39, %40, %41, %42, %43, %44, %45, %46, %47, "
      "%48, %49, %50, %51, %52, %53, %54, %55, %56, %57, %58, %59, %60, %61, %62, %63, "
      "%64, %65, %66, %67, %68, %69, %70, %71, %72, %73, %74, %75, %76, %77, %78, %79, "
      "%80, %81, %82, %83, %84, %85, %86, %87, %88, %89, %90, %91, %92, %93, %94, %95"
      "}, a, b, t, 1, 1, 0, 1;\n"
    "setp.ne.u32 q, %99, 0;\n@q mbarrier.arrive.shared::cta.b64 _, [%98];\n@q mbarrier.arrive.shared::cta.b64 _, [%98];\n"
    "add.u64 a, %96, 6;\nadd.u64 b, %97, 3*%104;\n"
    "wgmma.mma_async.sync.aligned.m64n192k16.f32.bf16.bf16 {"
      "%0, %1, %2, %3, %4, %5, %6, %7, %8, %9, %10, %11, %12, %13, %14, %15, "
      "%16, %17, %18, %19, %20, %21, %22, %23, %24, %25, %26, %27, %28, %29, %30, %31, "
      "%32, %33, %34, %35, %36, %37, %38, %39, %40, %41, %42, %43, %44, %45, %46, %47, "
      "%48, %49, %50, %51, %52, %53, %54, %55, %56, %57, %58, %59, %60, %61, %62, %63, "
      "%64, %65, %66, %67, %68, %69, %70, %71, %72, %73, %74, %75, %76, %77, %78, %79, "
      "%80, %81, %82, %83, %84, %85, %86, %87, %88, %89, %90, %91, %92, %93, %94, %95"
      "}, a, b, t, 1, 1, 0, 1;\n"
    "wgmma.commit_group.sync.aligned;\n"
    "}\n"
      :
      "+f"(d[0]), "+f"(d[1]), "+f"(d[2]), "+f"(d[3]), "+f"(d[4]), "+f"(d[5]), "+f"(d[6]), "+f"(d[7]),
      "+f"(d[8]), "+f"(d[9]), "+f"(d[10]), "+f"(d[11]), "+f"(d[12]), "+f"(d[13]), "+f"(d[14]), "+f"(d[15]),
      "+f"(d[16]), "+f"(d[17]), "+f"(d[18]), "+f"(d[19]), "+f"(d[20]), "+f"(d[21]), "+f"(d[22]), "+f"(d[23]),
      "+f"(d[24]), "+f"(d[25]), "+f"(d[26]), "+f"(d[27]), "+f"(d[28]), "+f"(d[29]), "+f"(d[30]), "+f"(d[31]),
      "+f"(d[32]), "+f"(d[33]), "+f"(d[34]), "+f"(d[35]), "+f"(d[36]), "+f"(d[37]), "+f"(d[38]), "+f"(d[39]),
      "+f"(d[40]), "+f"(d[41]), "+f"(d[42]), "+f"(d[43]), "+f"(d[44]), "+f"(d[45]), "+f"(d[46]), "+f"(d[47]),
      "+f"(d[48]), "+f"(d[49]), "+f"(d[50]), "+f"(d[51]), "+f"(d[52]), "+f"(d[53]), "+f"(d[54]), "+f"(d[55]),
      "+f"(d[56]), "+f"(d[57]), "+f"(d[58]), "+f"(d[59]), "+f"(d[60]), "+f"(d[61]), "+f"(d[62]), "+f"(d[63]),
      "+f"(d[64]), "+f"(d[65]), "+f"(d[66]), "+f"(d[67]), "+f"(d[68]), "+f"(d[69]), "+f"(d[70]), "+f"(d[71]),
      "+f"(d[72]), "+f"(d[73]), "+f"(d[74]), "+f"(d[75]), "+f"(d[76]), "+f"(d[77]), "+f"(d[78]), "+f"(d[79]),
      "+f"(d[80]), "+f"(d[81]), "+f"(d[82]), "+f"(d[83]), "+f"(d[84]), "+f"(d[85]), "+f"(d[86]), "+f"(d[87]),
      "+f"(d[88]), "+f"(d[89]), "+f"(d[90]), "+f"(d[91]), "+f"(d[92]), "+f"(d[93]), "+f"(d[94]), "+f"(d[95])
      : "l"(da), "l"(db), "r"(rel), "r"(doR), "r"(fa), "r"(pa), "r"(fb), "r"(pb), "n"(BSTEP), "r"(acc), "r"(rela) : "memory");
    else if constexpr (W == 0 && RC == 2 && RA == 1 && D1 == 0) asm volatile(
    "{\n.reg .pred p, q, r, t;\n.reg .b64 a, b;\n.reg .u32 n;\nsetp.ne.b32 t, 1, 0;\nsetp.ne.b32 r, %105, 0;\n"
    "wgmma.mma_async.sync.aligned.m64n192k16.f32.bf16.bf16 {"
      "%0, %1, %2, %3, %4, %5, %6, %7, %8, %9, %10, %11, %12, %13, %14, %15, "
      "%16, %17, %18, %19, %20, %21, %22, %23, %24, %25, %26, %27, %28, %29, %30, %31, "
      "%32, %33, %34, %35, %36, %37, %38, %39, %40, %41, %42, %43, %44, %45, %46, %47, "
      "%48, %49, %50, %51, %52, %53, %54, %55, %56, %57, %58, %59, %60, %61, %62, %63, "
      "%64, %65, %66, %67, %68, %69, %70, %71, %72, %73, %74, %75, %76, %77, %78, %79, "
      "%80, %81, %82, %83, %84, %85, %86, %87, %88, %89, %90, %91, %92, %93, %94, %95"
      "}, %96, %97, r, 1, 1, 0, 1;\n"
    "add.u64 a, %96, 2;\nadd.u64 b, %97, %104;\n"
    "wgmma.mma_async.sync.aligned.m64n192k16.f32.bf16.bf16 {"
      "%0, %1, %2, %3, %4, %5, %6, %7, %8, %9, %10, %11, %12, %13, %14, %15, "
      "%16, %17, %18, %19, %20, %21, %22, %23, %24, %25, %26, %27, %28, %29, %30, %31, "
      "%32, %33, %34, %35, %36, %37, %38, %39, %40, %41, %42, %43, %44, %45, %46, %47, "
      "%48, %49, %50, %51, %52, %53, %54, %55, %56, %57, %58, %59, %60, %61, %62, %63, "
      "%64, %65, %66, %67, %68, %69, %70, %71, %72, %73, %74, %75, %76, %77, %78, %79, "
      "%80, %81, %82, %83, %84, %85, %86, %87, %88, %89, %90, %91, %92, %93, %94, %95"
      "}, a, b, t, 1, 1, 0, 1;\n"
    "wgmma.commit_group.sync.aligned;\nwgmma.wait_group.sync.aligned 1;\n"
    "add.u64 a, %96, 4;\nadd.u64 b, %97, 2*%104;\n"
    "wgmma.mma_async.sync.aligned.m64n192k16.f32.bf16.bf16 {"
      "%0, %1, %2, %3, %4, %5, %6, %7, %8, %9, %10, %11, %12, %13, %14, %15, "
      "%16, %17, %18, %19, %20, %21, %22, %23, %24, %25, %26, %27, %28, %29, %30, %31, "
      "%32, %33, %34, %35, %36, %37, %38, %39, %40, %41, %42, %43, %44, %45, %46, %47, "
      "%48, %49, %50, %51, %52, %53, %54, %55, %56, %57, %58, %59, %60, %61, %62, %63, "
      "%64, %65, %66, %67, %68, %69, %70, %71, %72, %73, %74, %75, %76, %77, %78, %79, "
      "%80, %81, %82, %83, %84, %85, %86, %87, %88, %89, %90, %91, %92, %93, %94, %95"
      "}, a, b, t, 1, 1, 0, 1;\n"
    "setp.ne.u32 q, %99, 0;\n@q mbarrier.arrive.shared::cta.b64 _, [%98];\n@q mbarrier.arrive.shared::cta.b64 _, [%98];\n@q mbarrier.arrive.shared::cta.b64 _, [%106];\n@q mbarrier.arrive.shared::cta.b64 _, [%106];\n"
    "add.u64 a, %96, 6;\nadd.u64 b, %97, 3*%104;\n"
    "wgmma.mma_async.sync.aligned.m64n192k16.f32.bf16.bf16 {"
      "%0, %1, %2, %3, %4, %5, %6, %7, %8, %9, %10, %11, %12, %13, %14, %15, "
      "%16, %17, %18, %19, %20, %21, %22, %23, %24, %25, %26, %27, %28, %29, %30, %31, "
      "%32, %33, %34, %35, %36, %37, %38, %39, %40, %41, %42, %43, %44, %45, %46, %47, "
      "%48, %49, %50, %51, %52, %53, %54, %55, %56, %57, %58, %59, %60, %61, %62, %63, "
      "%64, %65, %66, %67, %68, %69, %70, %71, %72, %73, %74, %75, %76, %77, %78, %79, "
      "%80, %81, %82, %83, %84, %85, %86, %87, %88, %89, %90, %91, %92, %93, %94, %95"
      "}, a, b, t, 1, 1, 0, 1;\n"
    "wgmma.commit_group.sync.aligned;\n"
    "}\n"
      :
      "+f"(d[0]), "+f"(d[1]), "+f"(d[2]), "+f"(d[3]), "+f"(d[4]), "+f"(d[5]), "+f"(d[6]), "+f"(d[7]),
      "+f"(d[8]), "+f"(d[9]), "+f"(d[10]), "+f"(d[11]), "+f"(d[12]), "+f"(d[13]), "+f"(d[14]), "+f"(d[15]),
      "+f"(d[16]), "+f"(d[17]), "+f"(d[18]), "+f"(d[19]), "+f"(d[20]), "+f"(d[21]), "+f"(d[22]), "+f"(d[23]),
      "+f"(d[24]), "+f"(d[25]), "+f"(d[26]), "+f"(d[27]), "+f"(d[28]), "+f"(d[29]), "+f"(d[30]), "+f"(d[31]),
      "+f"(d[32]), "+f"(d[33]), "+f"(d[34]), "+f"(d[35]), "+f"(d[36]), "+f"(d[37]), "+f"(d[38]), "+f"(d[39]),
      "+f"(d[40]), "+f"(d[41]), "+f"(d[42]), "+f"(d[43]), "+f"(d[44]), "+f"(d[45]), "+f"(d[46]), "+f"(d[47]),
      "+f"(d[48]), "+f"(d[49]), "+f"(d[50]), "+f"(d[51]), "+f"(d[52]), "+f"(d[53]), "+f"(d[54]), "+f"(d[55]),
      "+f"(d[56]), "+f"(d[57]), "+f"(d[58]), "+f"(d[59]), "+f"(d[60]), "+f"(d[61]), "+f"(d[62]), "+f"(d[63]),
      "+f"(d[64]), "+f"(d[65]), "+f"(d[66]), "+f"(d[67]), "+f"(d[68]), "+f"(d[69]), "+f"(d[70]), "+f"(d[71]),
      "+f"(d[72]), "+f"(d[73]), "+f"(d[74]), "+f"(d[75]), "+f"(d[76]), "+f"(d[77]), "+f"(d[78]), "+f"(d[79]),
      "+f"(d[80]), "+f"(d[81]), "+f"(d[82]), "+f"(d[83]), "+f"(d[84]), "+f"(d[85]), "+f"(d[86]), "+f"(d[87]),
      "+f"(d[88]), "+f"(d[89]), "+f"(d[90]), "+f"(d[91]), "+f"(d[92]), "+f"(d[93]), "+f"(d[94]), "+f"(d[95])
      : "l"(da), "l"(db), "r"(rel), "r"(doR), "r"(fa), "r"(pa), "r"(fb), "r"(pb), "n"(BSTEP), "r"(acc), "r"(rela) : "memory");
    else if constexpr (W == 1 && RC == 2 && RA == 1 && D1 == 0) asm volatile(
    "{\n.reg .pred p, q, r, t;\n.reg .b64 a, b;\n.reg .u32 n;\nsetp.ne.b32 t, 1, 0;\nsetp.ne.b32 r, %105, 0;\n"
    "wgmma.mma_async.sync.aligned.m64n192k16.f32.bf16.bf16 {"
      "%0, %1, %2, %3, %4, %5, %6, %7, %8, %9, %10, %11, %12, %13, %14, %15, "
      "%16, %17, %18, %19, %20, %21, %22, %23, %24, %25, %26, %27, %28, %29, %30, %31, "
      "%32, %33, %34, %35, %36, %37, %38, %39, %40, %41, %42, %43, %44, %45, %46, %47, "
      "%48, %49, %50, %51, %52, %53, %54, %55, %56, %57, %58, %59, %60, %61, %62, %63, "
      "%64, %65, %66, %67, %68, %69, %70, %71, %72, %73, %74, %75, %76, %77, %78, %79, "
      "%80, %81, %82, %83, %84, %85, %86, %87, %88, %89, %90, %91, %92, %93, %94, %95"
      "}, %96, %97, r, 1, 1, 0, 1;\n"
    "add.u64 a, %96, 2;\nadd.u64 b, %97, %104;\n"
    "wgmma.mma_async.sync.aligned.m64n192k16.f32.bf16.bf16 {"
      "%0, %1, %2, %3, %4, %5, %6, %7, %8, %9, %10, %11, %12, %13, %14, %15, "
      "%16, %17, %18, %19, %20, %21, %22, %23, %24, %25, %26, %27, %28, %29, %30, %31, "
      "%32, %33, %34, %35, %36, %37, %38, %39, %40, %41, %42, %43, %44, %45, %46, %47, "
      "%48, %49, %50, %51, %52, %53, %54, %55, %56, %57, %58, %59, %60, %61, %62, %63, "
      "%64, %65, %66, %67, %68, %69, %70, %71, %72, %73, %74, %75, %76, %77, %78, %79, "
      "%80, %81, %82, %83, %84, %85, %86, %87, %88, %89, %90, %91, %92, %93, %94, %95"
      "}, a, b, t, 1, 1, 0, 1;\n"
    "wgmma.commit_group.sync.aligned;\nwgmma.wait_group.sync.aligned 1;\n"
    "add.u64 a, %96, 4;\nadd.u64 b, %97, 2*%104;\n"
    "wgmma.mma_async.sync.aligned.m64n192k16.f32.bf16.bf16 {"
      "%0, %1, %2, %3, %4, %5, %6, %7, %8, %9, %10, %11, %12, %13, %14, %15, "
      "%16, %17, %18, %19, %20, %21, %22, %23, %24, %25, %26, %27, %28, %29, %30, %31, "
      "%32, %33, %34, %35, %36, %37, %38, %39, %40, %41, %42, %43, %44, %45, %46, %47, "
      "%48, %49, %50, %51, %52, %53, %54, %55, %56, %57, %58, %59, %60, %61, %62, %63, "
      "%64, %65, %66, %67, %68, %69, %70, %71, %72, %73, %74, %75, %76, %77, %78, %79, "
      "%80, %81, %82, %83, %84, %85, %86, %87, %88, %89, %90, %91, %92, %93, %94, %95"
      "}, a, b, t, 1, 1, 0, 1;\n"
    "setp.ne.u32 q, %99, 0;\n@q mbarrier.arrive.shared::cta.b64 _, [%98];\n@q mbarrier.arrive.shared::cta.b64 _, [%98];\n@q mbarrier.arrive.shared::cta.b64 _, [%106];\n@q mbarrier.arrive.shared::cta.b64 _, [%106];\n"
    "mbarrier.test_wait.parity.shared::cta.b64 p, [%102], %103;\n"
    "add.u64 a, %96, 6;\nadd.u64 b, %97, 3*%104;\n"
    "wgmma.mma_async.sync.aligned.m64n192k16.f32.bf16.bf16 {"
      "%0, %1, %2, %3, %4, %5, %6, %7, %8, %9, %10, %11, %12, %13, %14, %15, "
      "%16, %17, %18, %19, %20, %21, %22, %23, %24, %25, %26, %27, %28, %29, %30, %31, "
      "%32, %33, %34, %35, %36, %37, %38, %39, %40, %41, %42, %43, %44, %45, %46, %47, "
      "%48, %49, %50, %51, %52, %53, %54, %55, %56, %57, %58, %59, %60, %61, %62, %63, "
      "%64, %65, %66, %67, %68, %69, %70, %71, %72, %73, %74, %75, %76, %77, %78, %79, "
      "%80, %81, %82, %83, %84, %85, %86, %87, %88, %89, %90, %91, %92, %93, %94, %95"
      "}, a, b, t, 1, 1, 0, 1;\n"
    "wgmma.commit_group.sync.aligned;\n"
    "@p bra.uni DN;\nmov.u32 n, 0;\nWT: mbarrier.try_wait.parity.shared::cta.b64 p, [%102], %103;\n@p bra.uni DN;\nadd.u32 n, n, 1;\nsetp.lt.u32 p, n, 0x100000;\n@p bra.uni WT;\nDN:\n"
    "}\n"
      :
      "+f"(d[0]), "+f"(d[1]), "+f"(d[2]), "+f"(d[3]), "+f"(d[4]), "+f"(d[5]), "+f"(d[6]), "+f"(d[7]),
      "+f"(d[8]), "+f"(d[9]), "+f"(d[10]), "+f"(d[11]), "+f"(d[12]), "+f"(d[13]), "+f"(d[14]), "+f"(d[15]),
      "+f"(d[16]), "+f"(d[17]), "+f"(d[18]), "+f"(d[19]), "+f"(d[20]), "+f"(d[21]), "+f"(d[22]), "+f"(d[23]),
      "+f"(d[24]), "+f"(d[25]), "+f"(d[26]), "+f"(d[27]), "+f"(d[28]), "+f"(d[29]), "+f"(d[30]), "+f"(d[31]),
      "+f"(d[32]), "+f"(d[33]), "+f"(d[34]), "+f"(d[35]), "+f"(d[36]), "+f"(d[37]), "+f"(d[38]), "+f"(d[39]),
      "+f"(d[40]), "+f"(d[41]), "+f"(d[42]), "+f"(d[43]), "+f"(d[44]), "+f"(d[45]), "+f"(d[46]), "+f"(d[47]),
      "+f"(d[48]), "+f"(d[49]), "+f"(d[50]), "+f"(d[51]), "+f"(d[52]), "+f"(d[53]), "+f"(d[54]), "+f"(d[55]),
      "+f"(d[56]), "+f"(d[57]), "+f"(d[58]), "+f"(d[59]), "+f"(d[60]), "+f"(d[61]), "+f"(d[62]), "+f"(d[63]),
      "+f"(d[64]), "+f"(d[65]), "+f"(d[66]), "+f"(d[67]), "+f"(d[68]), "+f"(d[69]), "+f"(d[70]), "+f"(d[71]),
      "+f"(d[72]), "+f"(d[73]), "+f"(d[74]), "+f"(d[75]), "+f"(d[76]), "+f"(d[77]), "+f"(d[78]), "+f"(d[79]),
      "+f"(d[80]), "+f"(d[81]), "+f"(d[82]), "+f"(d[83]), "+f"(d[84]), "+f"(d[85]), "+f"(d[86]), "+f"(d[87]),
      "+f"(d[88]), "+f"(d[89]), "+f"(d[90]), "+f"(d[91]), "+f"(d[92]), "+f"(d[93]), "+f"(d[94]), "+f"(d[95])
      : "l"(da), "l"(db), "r"(rel), "r"(doR), "r"(fa), "r"(pa), "r"(fb), "r"(pb), "n"(BSTEP), "r"(acc), "r"(rela) : "memory");
    else if constexpr (W == 2 && RC == 2 && RA == 0 && D1 == 0) asm volatile(
    "{\n.reg .pred p, q, r, t;\n.reg .b64 a, b;\n.reg .u32 n;\nsetp.ne.b32 t, 1, 0;\nsetp.ne.b32 r, %105, 0;\n"
    "wgmma.mma_async.sync.aligned.m64n192k16.f32.bf16.bf16 {"
      "%0, %1, %2, %3, %4, %5, %6, %7, %8, %9, %10, %11, %12, %13, %14, %15, "
      "%16, %17, %18, %19, %20, %21, %22, %23, %24, %25, %26, %27, %28, %29, %30, %31, "
      "%32, %33, %34, %35, %36, %37, %38, %39, %40, %41, %42, %43, %44, %45, %46, %47, "
      "%48, %49, %50, %51, %52, %53, %54, %55, %56, %57, %58, %59, %60, %61, %62, %63, "
      "%64, %65, %66, %67, %68, %69, %70, %71, %72, %73, %74, %75, %76, %77, %78, %79, "
      "%80, %81, %82, %83, %84, %85, %86, %87, %88, %89, %90, %91, %92, %93, %94, %95"
      "}, %96, %97, r, 1, 1, 0, 1;\n"
    "add.u64 a, %96, 2;\nadd.u64 b, %97, %104;\n"
    "wgmma.mma_async.sync.aligned.m64n192k16.f32.bf16.bf16 {"
      "%0, %1, %2, %3, %4, %5, %6, %7, %8, %9, %10, %11, %12, %13, %14, %15, "
      "%16, %17, %18, %19, %20, %21, %22, %23, %24, %25, %26, %27, %28, %29, %30, %31, "
      "%32, %33, %34, %35, %36, %37, %38, %39, %40, %41, %42, %43, %44, %45, %46, %47, "
      "%48, %49, %50, %51, %52, %53, %54, %55, %56, %57, %58, %59, %60, %61, %62, %63, "
      "%64, %65, %66, %67, %68, %69, %70, %71, %72, %73, %74, %75, %76, %77, %78, %79, "
      "%80, %81, %82, %83, %84, %85, %86, %87, %88, %89, %90, %91, %92, %93, %94, %95"
      "}, a, b, t, 1, 1, 0, 1;\n"
    "wgmma.commit_group.sync.aligned;\nwgmma.wait_group.sync.aligned 1;\n"
    "add.u64 a, %96, 4;\nadd.u64 b, %97, 2*%104;\n"
    "wgmma.mma_async.sync.aligned.m64n192k16.f32.bf16.bf16 {"
      "%0, %1, %2, %3, %4, %5, %6, %7, %8, %9, %10, %11, %12, %13, %14, %15, "
      "%16, %17, %18, %19, %20, %21, %22, %23, %24, %25, %26, %27, %28, %29, %30, %31, "
      "%32, %33, %34, %35, %36, %37, %38, %39, %40, %41, %42, %43, %44, %45, %46, %47, "
      "%48, %49, %50, %51, %52, %53, %54, %55, %56, %57, %58, %59, %60, %61, %62, %63, "
      "%64, %65, %66, %67, %68, %69, %70, %71, %72, %73, %74, %75, %76, %77, %78, %79, "
      "%80, %81, %82, %83, %84, %85, %86, %87, %88, %89, %90, %91, %92, %93, %94, %95"
      "}, a, b, t, 1, 1, 0, 1;\n"
    "setp.ne.u32 q, %99, 0;\n@q mbarrier.arrive.shared::cta.b64 _, [%98];\n@q mbarrier.arrive.shared::cta.b64 _, [%98];\n"
    "mbarrier.test_wait.parity.shared::cta.b64 p, [%102], %103;\n"
    "mbarrier.test_wait.parity.shared::cta.b64 r, [%100], %101;\nand.pred p, p, r;\n"
    "add.u64 a, %96, 6;\nadd.u64 b, %97, 3*%104;\n"
    "wgmma.mma_async.sync.aligned.m64n192k16.f32.bf16.bf16 {"
      "%0, %1, %2, %3, %4, %5, %6, %7, %8, %9, %10, %11, %12, %13, %14, %15, "
      "%16, %17, %18, %19, %20, %21, %22, %23, %24, %25, %26, %27, %28, %29, %30, %31, "
      "%32, %33, %34, %35, %36, %37, %38, %39, %40, %41, %42, %43, %44, %45, %46, %47, "
      "%48, %49, %50, %51, %52, %53, %54, %55, %56, %57, %58, %59, %60, %61, %62, %63, "
      "%64, %65, %66, %67, %68, %69, %70, %71, %72, %73, %74, %75, %76, %77, %78, %79, "
      "%80, %81, %82, %83, %84, %85, %86, %87, %88, %89, %90, %91, %92, %93, %94, %95"
      "}, a, b, t, 1, 1, 0, 1;\n"
    "wgmma.commit_group.sync.aligned;\n"
    "@p bra.uni DN;\nmov.u32 n, 0;\nWT: mbarrier.try_wait.parity.shared::cta.b64 p, [%102], %103;\nmbarrier.try_wait.parity.shared::cta.b64 r, [%100], %101;\nand.pred p, p, r;\n@p bra.uni DN;\nadd.u32 n, n, 1;\nsetp.lt.u32 p, n, 0x100000;\n@p bra.uni WT;\nDN:\n"
    "}\n"
      :
      "+f"(d[0]), "+f"(d[1]), "+f"(d[2]), "+f"(d[3]), "+f"(d[4]), "+f"(d[5]), "+f"(d[6]), "+f"(d[7]),
      "+f"(d[8]), "+f"(d[9]), "+f"(d[10]), "+f"(d[11]), "+f"(d[12]), "+f"(d[13]), "+f"(d[14]), "+f"(d[15]),
      "+f"(d[16]), "+f"(d[17]), "+f"(d[18]), "+f"(d[19]), "+f"(d[20]), "+f"(d[21]), "+f"(d[22]), "+f"(d[23]),
      "+f"(d[24]), "+f"(d[25]), "+f"(d[26]), "+f"(d[27]), "+f"(d[28]), "+f"(d[29]), "+f"(d[30]), "+f"(d[31]),
      "+f"(d[32]), "+f"(d[33]), "+f"(d[34]), "+f"(d[35]), "+f"(d[36]), "+f"(d[37]), "+f"(d[38]), "+f"(d[39]),
      "+f"(d[40]), "+f"(d[41]), "+f"(d[42]), "+f"(d[43]), "+f"(d[44]), "+f"(d[45]), "+f"(d[46]), "+f"(d[47]),
      "+f"(d[48]), "+f"(d[49]), "+f"(d[50]), "+f"(d[51]), "+f"(d[52]), "+f"(d[53]), "+f"(d[54]), "+f"(d[55]),
      "+f"(d[56]), "+f"(d[57]), "+f"(d[58]), "+f"(d[59]), "+f"(d[60]), "+f"(d[61]), "+f"(d[62]), "+f"(d[63]),
      "+f"(d[64]), "+f"(d[65]), "+f"(d[66]), "+f"(d[67]), "+f"(d[68]), "+f"(d[69]), "+f"(d[70]), "+f"(d[71]),
      "+f"(d[72]), "+f"(d[73]), "+f"(d[74]), "+f"(d[75]), "+f"(d[76]), "+f"(d[77]), "+f"(d[78]), "+f"(d[79]),
      "+f"(d[80]), "+f"(d[81]), "+f"(d[82]), "+f"(d[83]), "+f"(d[84]), "+f"(d[85]), "+f"(d[86]), "+f"(d[87]),
      "+f"(d[88]), "+f"(d[89]), "+f"(d[90]), "+f"(d[91]), "+f"(d[92]), "+f"(d[93]), "+f"(d[94]), "+f"(d[95])
      : "l"(da), "l"(db), "r"(rel), "r"(doR), "r"(fa), "r"(pa), "r"(fb), "r"(pb), "n"(BSTEP), "r"(acc), "r"(rela) : "memory");
    else if constexpr (W == 2 && RC == 2 && RA == 1 && D1 == 0) asm volatile(
    "{\n.reg .pred p, q, r, t;\n.reg .b64 a, b;\n.reg .u32 n;\nsetp.ne.b32 t, 1, 0;\nsetp.ne.b32 r, %105, 0;\n"
    "wgmma.mma_async.sync.aligned.m64n192k16.f32.bf16.bf16 {"
      "%0, %1, %2, %3, %4, %5, %6, %7, %8, %9, %10, %11, %12, %13, %14, %15, "
      "%16, %17, %18, %19, %20, %21, %22, %23, %24, %25, %26, %27, %28, %29, %30, %31, "
      "%32, %33, %34, %35, %36, %37, %38, %39, %40, %41, %42, %43, %44, %45, %46, %47, "
      "%48, %49, %50, %51, %52, %53, %54, %55, %56, %57, %58, %59, %60, %61, %62, %63, "
      "%64, %65, %66, %67, %68, %69, %70, %71, %72, %73, %74, %75, %76, %77, %78, %79, "
      "%80, %81, %82, %83, %84, %85, %86, %87, %88, %89, %90, %91, %92, %93, %94, %95"
      "}, %96, %97, r, 1, 1, 0, 1;\n"
    "add.u64 a, %96, 2;\nadd.u64 b, %97, %104;\n"
    "wgmma.mma_async.sync.aligned.m64n192k16.f32.bf16.bf16 {"
      "%0, %1, %2, %3, %4, %5, %6, %7, %8, %9, %10, %11, %12, %13, %14, %15, "
      "%16, %17, %18, %19, %20, %21, %22, %23, %24, %25, %26, %27, %28, %29, %30, %31, "
      "%32, %33, %34, %35, %36, %37, %38, %39, %40, %41, %42, %43, %44, %45, %46, %47, "
      "%48, %49, %50, %51, %52, %53, %54, %55, %56, %57, %58, %59, %60, %61, %62, %63, "
      "%64, %65, %66, %67, %68, %69, %70, %71, %72, %73, %74, %75, %76, %77, %78, %79, "
      "%80, %81, %82, %83, %84, %85, %86, %87, %88, %89, %90, %91, %92, %93, %94, %95"
      "}, a, b, t, 1, 1, 0, 1;\n"
    "wgmma.commit_group.sync.aligned;\nwgmma.wait_group.sync.aligned 1;\n"
    "add.u64 a, %96, 4;\nadd.u64 b, %97, 2*%104;\n"
    "wgmma.mma_async.sync.aligned.m64n192k16.f32.bf16.bf16 {"
      "%0, %1, %2, %3, %4, %5, %6, %7, %8, %9, %10, %11, %12, %13, %14, %15, "
      "%16, %17, %18, %19, %20, %21, %22, %23, %24, %25, %26, %27, %28, %29, %30, %31, "
      "%32, %33, %34, %35, %36, %37, %38, %39, %40, %41, %42, %43, %44, %45, %46, %47, "
      "%48, %49, %50, %51, %52, %53, %54, %55, %56, %57, %58, %59, %60, %61, %62, %63, "
      "%64, %65, %66, %67, %68, %69, %70, %71, %72, %73, %74, %75, %76, %77, %78, %79, "
      "%80, %81, %82, %83, %84, %85, %86, %87, %88, %89, %90, %91, %92, %93, %94, %95"
      "}, a, b, t, 1, 1, 0, 1;\n"
    "setp.ne.u32 q, %99, 0;\n@q mbarrier.arrive.shared::cta.b64 _, [%98];\n@q mbarrier.arrive.shared::cta.b64 _, [%98];\n@q mbarrier.arrive.shared::cta.b64 _, [%106];\n@q mbarrier.arrive.shared::cta.b64 _, [%106];\n"
    "mbarrier.test_wait.parity.shared::cta.b64 p, [%102], %103;\n"
    "mbarrier.test_wait.parity.shared::cta.b64 r, [%100], %101;\nand.pred p, p, r;\n"
    "add.u64 a, %96, 6;\nadd.u64 b, %97, 3*%104;\n"
    "wgmma.mma_async.sync.aligned.m64n192k16.f32.bf16.bf16 {"
      "%0, %1, %2, %3, %4, %5, %6, %7, %8, %9, %10, %11, %12, %13, %14, %15, "
      "%16, %17, %18, %19, %20, %21, %22, %23, %24, %25, %26, %27, %28, %29, %30, %31, "
      "%32, %33, %34, %35, %36, %37, %38, %39, %40, %41, %42, %43, %44, %45, %46, %47, "
      "%48, %49, %50, %51, %52, %53, %54, %55, %56, %57, %58, %59, %60, %61, %62, %63, "
      "%64, %65, %66, %67, %68, %69, %70, %71, %72, %73, %74, %75, %76, %77, %78, %79, "
      "%80, %81, %82, %83, %84, %85, %86, %87, %88, %89, %90, %91, %92, %93, %94, %95"
      "}, a, b, t, 1, 1, 0, 1;\n"
    "wgmma.commit_group.sync.aligned;\n"
    "@p bra.uni DN;\nmov.u32 n, 0;\nWT: mbarrier.try_wait.parity.shared::cta.b64 p, [%102], %103;\nmbarrier.try_wait.parity.shared::cta.b64 r, [%100], %101;\nand.pred p, p, r;\n@p bra.uni DN;\nadd.u32 n, n, 1;\nsetp.lt.u32 p, n, 0x100000;\n@p bra.uni WT;\nDN:\n"
    "}\n"
      :
      "+f"(d[0]), "+f"(d[1]), "+f"(d[2]), "+f"(d[3]), "+f"(d[4]), "+f"(d[5]), "+f"(d[6]), "+f"(d[7]),
      "+f"(d[8]), "+f"(d[9]), "+f"(d[10]), "+f"(d[11]), "+f"(d[12]), "+f"(d[13]), "+f"(d[14]), "+f"(d[15]),
      "+f"(d[16]), "+f"(d[17]), "+f"(d[18]), "+f"(d[19]), "+f"(d[20]), "+f"(d[21]), "+f"(d[22]), "+f"(d[23]),
      "+f"(d[24]), "+f"(d[25]), "+f"(d[26]), "+f"(d[27]), "+f"(d[28]), "+f"(d[29]), "+f"(d[30]), "+f"(d[31]),
      "+f"(d[32]), "+f"(d[33]), "+f"(d[34]), "+f"(d[35]), "+f"(d[36]), "+f"(d[37]), "+f"(d[38]), "+f"(d[39]),
      "+f"(d[40]), "+f"(d[41]), "+f"(d[42]), "+f"(d[43]), "+f"(d[44]), "+f"(d[45]), "+f"(d[46]), "+f"(d[47]),
      "+f"(d[48]), "+f"(d[49]), "+f"(d[50]), "+f"(d[51]), "+f"(d[52]), "+f"(d[53]), "+f"(d[54]), "+f"(d[55]),
      "+f"(d[56]), "+f"(d[57]), "+f"(d[58]), "+f"(d[59]), "+f"(d[60]), "+f"(d[61]), "+f"(d[62]), "+f"(d[63]),
      "+f"(d[64]), "+f"(d[65]), "+f"(d[66]), "+f"(d[67]), "+f"(d[68]), "+f"(d[69]), "+f"(d[70]), "+f"(d[71]),
      "+f"(d[72]), "+f"(d[73]), "+f"(d[74]), "+f"(d[75]), "+f"(d[76]), "+f"(d[77]), "+f"(d[78]), "+f"(d[79]),
      "+f"(d[80]), "+f"(d[81]), "+f"(d[82]), "+f"(d[83]), "+f"(d[84]), "+f"(d[85]), "+f"(d[86]), "+f"(d[87]),
      "+f"(d[88]), "+f"(d[89]), "+f"(d[90]), "+f"(d[91]), "+f"(d[92]), "+f"(d[93]), "+f"(d[94]), "+f"(d[95])
      : "l"(da), "l"(db), "r"(rel), "r"(doR), "r"(fa), "r"(pa), "r"(fb), "r"(pb), "n"(BSTEP), "r"(acc), "r"(rela) : "memory");
    else if constexpr (W == 0 && RC == 2 && RA == 1 && D1 == 1) asm volatile(
    "{\n.reg .pred p, q, r, t;\n.reg .b64 a, b;\n.reg .u32 n;\nsetp.ne.b32 t, 1, 0;\nsetp.ne.b32 r, %105, 0;\n"
    "wgmma.mma_async.sync.aligned.m64n192k16.f32.bf16.bf16 {"
      "%0, %1, %2, %3, %4, %5, %6, %7, %8, %9, %10, %11, %12, %13, %14, %15, "
      "%16, %17, %18, %19, %20, %21, %22, %23, %24, %25, %26, %27, %28, %29, %30, %31, "
      "%32, %33, %34, %35, %36, %37, %38, %39, %40, %41, %42, %43, %44, %45, %46, %47, "
      "%48, %49, %50, %51, %52, %53, %54, %55, %56, %57, %58, %59, %60, %61, %62, %63, "
      "%64, %65, %66, %67, %68, %69, %70, %71, %72, %73, %74, %75, %76, %77, %78, %79, "
      "%80, %81, %82, %83, %84, %85, %86, %87, %88, %89, %90, %91, %92, %93, %94, %95"
      "}, %96, %97, r, 1, 1, 0, 1;\n"
    "wgmma.commit_group.sync.aligned;\nwgmma.wait_group.sync.aligned 1;\n"
    "add.u64 a, %96, 2;\nadd.u64 b, %97, %104;\n"
    "wgmma.mma_async.sync.aligned.m64n192k16.f32.bf16.bf16 {"
      "%0, %1, %2, %3, %4, %5, %6, %7, %8, %9, %10, %11, %12, %13, %14, %15, "
      "%16, %17, %18, %19, %20, %21, %22, %23, %24, %25, %26, %27, %28, %29, %30, %31, "
      "%32, %33, %34, %35, %36, %37, %38, %39, %40, %41, %42, %43, %44, %45, %46, %47, "
      "%48, %49, %50, %51, %52, %53, %54, %55, %56, %57, %58, %59, %60, %61, %62, %63, "
      "%64, %65, %66, %67, %68, %69, %70, %71, %72, %73, %74, %75, %76, %77, %78, %79, "
      "%80, %81, %82, %83, %84, %85, %86, %87, %88, %89, %90, %91, %92, %93, %94, %95"
      "}, a, b, t, 1, 1, 0, 1;\n"
    "wgmma.commit_group.sync.aligned;\nwgmma.wait_group.sync.aligned 1;\n"
    "add.u64 a, %96, 4;\nadd.u64 b, %97, 2*%104;\n"
    "wgmma.mma_async.sync.aligned.m64n192k16.f32.bf16.bf16 {"
      "%0, %1, %2, %3, %4, %5, %6, %7, %8, %9, %10, %11, %12, %13, %14, %15, "
      "%16, %17, %18, %19, %20, %21, %22, %23, %24, %25, %26, %27, %28, %29, %30, %31, "
      "%32, %33, %34, %35, %36, %37, %38, %39, %40, %41, %42, %43, %44, %45, %46, %47, "
      "%48, %49, %50, %51, %52, %53, %54, %55, %56, %57, %58, %59, %60, %61, %62, %63, "
      "%64, %65, %66, %67, %68, %69, %70, %71, %72, %73, %74, %75, %76, %77, %78, %79, "
      "%80, %81, %82, %83, %84, %85, %86, %87, %88, %89, %90, %91, %92, %93, %94, %95"
      "}, a, b, t, 1, 1, 0, 1;\n"
    "wgmma.commit_group.sync.aligned;\n"
    "setp.ne.u32 q, %99, 0;\n@q mbarrier.arrive.shared::cta.b64 _, [%98];\n@q mbarrier.arrive.shared::cta.b64 _, [%98];\n@q mbarrier.arrive.shared::cta.b64 _, [%106];\n@q mbarrier.arrive.shared::cta.b64 _, [%106];\n"
    "wgmma.wait_group.sync.aligned 1;\n"
    "add.u64 a, %96, 6;\nadd.u64 b, %97, 3*%104;\n"
    "wgmma.mma_async.sync.aligned.m64n192k16.f32.bf16.bf16 {"
      "%0, %1, %2, %3, %4, %5, %6, %7, %8, %9, %10, %11, %12, %13, %14, %15, "
      "%16, %17, %18, %19, %20, %21, %22, %23, %24, %25, %26, %27, %28, %29, %30, %31, "
      "%32, %33, %34, %35, %36, %37, %38, %39, %40, %41, %42, %43, %44, %45, %46, %47, "
      "%48, %49, %50, %51, %52, %53, %54, %55, %56, %57, %58, %59, %60, %61, %62, %63, "
      "%64, %65, %66, %67, %68, %69, %70, %71, %72, %73, %74, %75, %76, %77, %78, %79, "
      "%80, %81, %82, %83, %84, %85, %86, %87, %88, %89, %90, %91, %92, %93, %94, %95"
      "}, a, b, t, 1, 1, 0, 1;\n"
    "wgmma.commit_group.sync.aligned;\n"
    "}\n"
      :
      "+f"(d[0]), "+f"(d[1]), "+f"(d[2]), "+f"(d[3]), "+f"(d[4]), "+f"(d[5]), "+f"(d[6]), "+f"(d[7]),
      "+f"(d[8]), "+f"(d[9]), "+f"(d[10]), "+f"(d[11]), "+f"(d[12]), "+f"(d[13]), "+f"(d[14]), "+f"(d[15]),
      "+f"(d[16]), "+f"(d[17]), "+f"(d[18]), "+f"(d[19]), "+f"(d[20]), "+f"(d[21]), "+f"(d[22]), "+f"(d[23]),
      "+f"(d[24]), "+f"(d[25]), "+f"(d[26]), "+f"(d[27]), "+f"(d[28]), "+f"(d[29]), "+f"(d[30]), "+f"(d[31]),
      "+f"(d[32]), "+f"(d[33]), "+f"(d[34]), "+f"(d[35]), "+f"(d[36]), "+f"(d[37]), "+f"(d[38]), "+f"(d[39]),
      "+f"(d[40]), "+f"(d[41]), "+f"(d[42]), "+f"(d[43]), "+f"(d[44]), "+f"(d[45]), "+f"(d[46]), "+f"(d[47]),
      "+f"(d[48]), "+f"(d[49]), "+f"(d[50]), "+f"(d[51]), "+f"(d[52]), "+f"(d[53]), "+f"(d[54]), "+f"(d[55]),
      "+f"(d[56]), "+f"(d[57]), "+f"(d[58]), "+f"(d[59]), "+f"(d[60]), "+f"(d[61]), "+f"(d[62]), "+f"(d[63]),
      "+f"(d[64]), "+f"(d[65]), "+f"(d[66]), "+f"(d[67]), "+f"(d[68]), "+f"(d[69]), "+f"(d[70]), "+f"(d[71]),
      "+f"(d[72]), "+f"(d[73]), "+f"(d[74]), "+f"(d[75]), "+f"(d[76]), "+f"(d[77]), "+f"(d[78]), "+f"(d[79]),
      "+f"(d[80]), "+f"(d[81]), "+f"(d[82]), "+f"(d[83]), "+f"(d[84]), "+f"(d[85]), "+f"(d[86]), "+f"(d[87]),
      "+f"(d[88]), "+f"(d[89]), "+f"(d[90]), "+f"(d[91]), "+f"(d[92]), "+f"(d[93]), "+f"(d[94]), "+f"(d[95])
      : "l"(da), "l"(db), "r"(rel), "r"(doR), "r"(fa), "r"(pa), "r"(fb), "r"(pb), "n"(BSTEP), "r"(acc), "r"(rela) : "memory");
    else if constexpr (W == 2 && RC == 2 && RA == 1 && D1 == 1) asm volatile(
    "{\n.reg .pred p, q, r, t;\n.reg .b64 a, b;\n.reg .u32 n;\nsetp.ne.b32 t, 1, 0;\nsetp.ne.b32 r, %105, 0;\n"
    "wgmma.mma_async.sync.aligned.m64n192k16.f32.bf16.bf16 {"
      "%0, %1, %2, %3, %4, %5, %6, %7, %8, %9, %10, %11, %12, %13, %14, %15, "
      "%16, %17, %18, %19, %20, %21, %22, %23, %24, %25, %26, %27, %28, %29, %30, %31, "
      "%32, %33, %34, %35, %36, %37, %38, %39, %40, %41, %42, %43, %44, %45, %46, %47, "
      "%48, %49, %50, %51, %52, %53, %54, %55, %56, %57, %58, %59, %60, %61, %62, %63, "
      "%64, %65, %66, %67, %68, %69, %70, %71, %72, %73, %74, %75, %76, %77, %78, %79, "
      "%80, %81, %82, %83, %84, %85, %86, %87, %88, %89, %90, %91, %92, %93, %94, %95"
      "}, %96, %97, r, 1, 1, 0, 1;\n"
    "wgmma.commit_group.sync.aligned;\nwgmma.wait_group.sync.aligned 1;\n"
    "add.u64 a, %96, 2;\nadd.u64 b, %97, %104;\n"
    "wgmma.mma_async.sync.aligned.m64n192k16.f32.bf16.bf16 {"
      "%0, %1, %2, %3, %4, %5, %6, %7, %8, %9, %10, %11, %12, %13, %14, %15, "
      "%16, %17, %18, %19, %20, %21, %22, %23, %24, %25, %26, %27, %28, %29, %30, %31, "
      "%32, %33, %34, %35, %36, %37, %38, %39, %40, %41, %42, %43, %44, %45, %46, %47, "
      "%48, %49, %50, %51, %52, %53, %54, %55, %56, %57, %58, %59, %60, %61, %62, %63, "
      "%64, %65, %66, %67, %68, %69, %70, %71, %72, %73, %74, %75, %76, %77, %78, %79, "
      "%80, %81, %82, %83, %84, %85, %86, %87, %88, %89, %90, %91, %92, %93, %94, %95"
      "}, a, b, t, 1, 1, 0, 1;\n"
    "wgmma.commit_group.sync.aligned;\nwgmma.wait_group.sync.aligned 1;\n"
    "add.u64 a, %96, 4;\nadd.u64 b, %97, 2*%104;\n"
    "wgmma.mma_async.sync.aligned.m64n192k16.f32.bf16.bf16 {"
      "%0, %1, %2, %3, %4, %5, %6, %7, %8, %9, %10, %11, %12, %13, %14, %15, "
      "%16, %17, %18, %19, %20, %21, %22, %23, %24, %25, %26, %27, %28, %29, %30, %31, "
      "%32, %33, %34, %35, %36, %37, %38, %39, %40, %41, %42, %43, %44, %45, %46, %47, "
      "%48, %49, %50, %51, %52, %53, %54, %55, %56, %57, %58, %59, %60, %61, %62, %63, "
      "%64, %65, %66, %67, %68, %69, %70, %71, %72, %73, %74, %75, %76, %77, %78, %79, "
      "%80, %81, %82, %83, %84, %85, %86, %87, %88, %89, %90, %91, %92, %93, %94, %95"
      "}, a, b, t, 1, 1, 0, 1;\n"
    "wgmma.commit_group.sync.aligned;\n"
    "setp.ne.u32 q, %99, 0;\n@q mbarrier.arrive.shared::cta.b64 _, [%98];\n@q mbarrier.arrive.shared::cta.b64 _, [%98];\n@q mbarrier.arrive.shared::cta.b64 _, [%106];\n@q mbarrier.arrive.shared::cta.b64 _, [%106];\n"
    "mbarrier.test_wait.parity.shared::cta.b64 p, [%102], %103;\n"
    "mbarrier.test_wait.parity.shared::cta.b64 r, [%100], %101;\nand.pred p, p, r;\n"
    "wgmma.wait_group.sync.aligned 1;\n"
    "add.u64 a, %96, 6;\nadd.u64 b, %97, 3*%104;\n"
    "wgmma.mma_async.sync.aligned.m64n192k16.f32.bf16.bf16 {"
      "%0, %1, %2, %3, %4, %5, %6, %7, %8, %9, %10, %11, %12, %13, %14, %15, "
      "%16, %17, %18, %19, %20, %21, %22, %23, %24, %25, %26, %27, %28, %29, %30, %31, "
      "%32, %33, %34, %35, %36, %37, %38, %39, %40, %41, %42, %43, %44, %45, %46, %47, "
      "%48, %49, %50, %51, %52, %53, %54, %55, %56, %57, %58, %59, %60, %61, %62, %63, "
      "%64, %65, %66, %67, %68, %69, %70, %71, %72, %73, %74, %75, %76, %77, %78, %79, "
      "%80, %81, %82, %83, %84, %85, %86, %87, %88, %89, %90, %91, %92, %93, %94, %95"
      "}, a, b, t, 1, 1, 0, 1;\n"
    "wgmma.commit_group.sync.aligned;\n"
    "@p bra.uni DN;\nmov.u32 n, 0;\nWT: mbarrier.try_wait.parity.shared::cta.b64 p, [%102], %103;\nmbarrier.try_wait.parity.shared::cta.b64 r, [%100], %101;\nand.pred p, p, r;\n@p bra.uni DN;\nadd.u32 n, n, 1;\nsetp.lt.u32 p, n, 0x100000;\n@p bra.uni WT;\nDN:\n"
    "}\n"
      :
      "+f"(d[0]), "+f"(d[1]), "+f"(d[2]), "+f"(d[3]), "+f"(d[4]), "+f"(d[5]), "+f"(d[6]), "+f"(d[7]),
      "+f"(d[8]), "+f"(d[9]), "+f"(d[10]), "+f"(d[11]), "+f"(d[12]), "+f"(d[13]), "+f"(d[14]), "+f"(d[15]),
      "+f"(d[16]), "+f"(d[17]), "+f"(d[18]), "+f"(d[19]), "+f"(d[20]), "+f"(d[21]), "+f"(d[22]), "+f"(d[23]),
      "+f"(d[24]), "+f"(d[25]), "+f"(d[26]), "+f"(d[27]), "+f"(d[28]), "+f"(d[29]), "+f"(d[30]), "+f"(d[31]),
      "+f"(d[32]), "+f"(d[33]), "+f"(d[34]), "+f"(d[35]), "+f"(d[36]), "+f"(d[37]), "+f"(d[38]), "+f"(d[39]),
      "+f"(d[40]), "+f"(d[41]), "+f"(d[42]), "+f"(d[43]), "+f"(d[44]), "+f"(d[45]), "+f"(d[46]), "+f"(d[47]),
      "+f"(d[48]), "+f"(d[49]), "+f"(d[50]), "+f"(d[51]), "+f"(d[52]), "+f"(d[53]), "+f"(d[54]), "+f"(d[55]),
      "+f"(d[56]), "+f"(d[57]), "+f"(d[58]), "+f"(d[59]), "+f"(d[60]), "+f"(d[61]), "+f"(d[62]), "+f"(d[63]),
      "+f"(d[64]), "+f"(d[65]), "+f"(d[66]), "+f"(d[67]), "+f"(d[68]), "+f"(d[69]), "+f"(d[70]), "+f"(d[71]),
      "+f"(d[72]), "+f"(d[73]), "+f"(d[74]), "+f"(d[75]), "+f"(d[76]), "+f"(d[77]), "+f"(d[78]), "+f"(d[79]),
      "+f"(d[80]), "+f"(d[81]), "+f"(d[82]), "+f"(d[83]), "+f"(d[84]), "+f"(d[85]), "+f"(d[86]), "+f"(d[87]),
      "+f"(d[88]), "+f"(d[89]), "+f"(d[90]), "+f"(d[91]), "+f"(d[92]), "+f"(d[93]), "+f"(d[94]), "+f"(d[95])
      : "l"(da), "l"(db), "r"(rel), "r"(doR), "r"(fa), "r"(pa), "r"(fb), "r"(pb), "n"(BSTEP), "r"(acc), "r"(rela) : "memory");
    else static_assert(W < 0, "variant not generated");
  }
};

#define GV 0
#define GVC 0
#define HPC 1
#define PF_W 0
#define YTAG 2
#define YD 800
#define PP 0
#define PPC 0
#define ZPD 0
#define CL 8
#define XSD 0
#define CSD 0
#define XP 0
#define KV2T 0
#define LSD 800
#define TP_T 5000
#define HVY 0
#define HE 0
#define STG 0
#define LKI 9
#define XL 0
#define XPF 1
#define KV_T0 2300
#define GATE 0
#define PAUSE 0
#define SEG1 4
#define ZW 0
#define HK1 1
#define HOLD 32
#define BPART 1
#define LEAD 2
#define HA 0
#define HD 300
#define ROT 0
#define CSI 9
#define PF_T 11000
#define PF_D 600
#define PF_N 1
#define HP0 3500
#define HPD 450
#define D2 4
#define NSLEEP 100
#define MAP 5
#define ST_YIELD 1

namespace {

constexpr int kS = 2048, kD = 640, kF = 1536;
constexpr int A_SLOT = 8192, B_SLOT = 24576, W_SLOT = 20480;
constexpr int OFF_A = 0;
constexpr int OFF_B = OFF_A + 10 * A_SLOT;
constexpr int XB_PL = 2112;
constexpr int CV_KE = 4224, CV_KO = CV_KE + 4160;
constexpr int CV_SZ = CV_KO + 4160;
constexpr int OFF_CV = OFF_B + 5 * B_SLOT;
constexpr int OFF_CS = OFF_CV + 2 * CV_SZ;
constexpr int OFF_XS = OFF_CS + 1536;
constexpr int OFF_BAR = OFF_XS + 512;
constexpr int SMEM_BYTES = OFF_BAR + 512;
static_assert(SMEM_BYTES <= 232448, "smem");
constexpr int OFF_RT = OFF_CS + 768;
constexpr int BAR_AF = OFF_BAR, BAR_BF = OFF_BAR + 8 * 10, BAR_WF = OFF_BAR + 8 * 15, BAR_ST = OFF_BAR + 8 * 21, BAR_XF = OFF_BAR + 8 * 23;
constexpr int BAR_ZP = OFF_BAR + 8 * 25, BAR_DUMMY = OFF_BAR + 8 * 27, BAR_PART = OFF_BAR + 8 * 28, BAR_WO = OFF_BAR + 8 * 29;
constexpr int BAR_YT = OFF_BAR + 8 * 30, BAR_KV2 = OFF_BAR + 8 * 31, BAR_XS = OFF_BAR + 8 * 32, BAR_HOLD = OFF_BAR + 8 * 33, BAR_ZG = OFF_BAR + 8 * 34;
constexpr int OFF_TAG = OFF_BAR + 8 * 35;
constexpr int BAR_HV = OFF_BAR + 8 * 36;
constexpr int BAR_HR = BAR_HV + 64;
constexpr int BAR_XL = OFF_CS - 16;
constexpr int BAR_AE = OFF_BAR + 8 * 45, BAR_BE = OFF_BAR + 8 * 53, BAR_WE = OFF_BAR + 8 * 58;
constexpr int NB_WG = 1, NB_G1 = 3, NB_WO = 4, NB_CD = 5, NB_Z = 6, NB_C = 7, NB_KU = 8, NB_SV = 9, NB_PC = 11, NB_KF = 12, NB_G1D = 13, NB_KU2 = 14, NB_KL = 15;

constexpr int CNT_KV = 0, CNT_WO = 4, CNT_Z = CL, CNT_Y = CL + 2;
struct Scratch {
  uint8_t kvx[kD * 4096];
  uint8_t z2[4 * 32 * 24576];
  uint8_t h[32 * 12 * 8192];
  uint8_t wo[4 * 12 * 20480];
  uint8_t y[kD * 4096];
  uint4 zstat[32 * 128];
  uint2 xstat[kS];
  uint32_t colsum[kF];
  uint32_t cnt[64];
  uint32_t hflag[32 * 32];
  uint32_t epoch[136];

};
__device__ __align__(1024) Scratch g_scr;
#define TSP
#define TSA
#define TR(i)
#define STAMP(i)
#define STAMPE(i)
#define STAMP2(i)
#define STAMPW(i)

struct Params {
  Scratch* scr;
  int by_smid;
  const __nv_bfloat16 *x, *k, *v, *shift, *ssmk, *ssmD, *wsp, *bsp, *wout;
  __nv_bfloat16* out;
  CUtensorMap tmX, tmW, tmWsp, tmY, tmKV;
};

__device__ __forceinline__ uint64_t mkdesc(uint32_t addr, uint32_t lbo, uint32_t sbo, uint32_t swz) {
  return (uint64_t)((addr & 0x3FFFF) >> 4) | ((uint64_t)(lbo >> 4) << 16) | ((uint64_t)(sbo >> 4) << 32) | ((uint64_t)swz << 62);
}
#define WG_FENCE() asm volatile("wgmma.fence.sync.aligned;" ::: "memory")
#define WG_COMMIT() asm volatile("wgmma.commit_group.sync.aligned;" ::: "memory")
#define WG_WAIT(n) asm volatile("wgmma.wait_group.sync.aligned %0;" ::"n"(n) : "memory")
template <int N> __device__ __forceinline__ void acc_fence(float* d) {
#pragma unroll
  for (int i = 0; i < N; i++) asm volatile("" : "+f"(d[i])::"memory");
}
__device__ __forceinline__ void mbar_init(uint32_t bar, int cnt) { asm volatile("mbarrier.init.shared::cta.b64 [%0], %1;" ::"r"(bar), "r"(cnt) : "memory"); }
__device__ __forceinline__ void mbar_expect(uint32_t bar, uint32_t bytes) { asm volatile("mbarrier.arrive.expect_tx.shared::cta.b64 _, [%0], %1;" ::"r"(bar), "r"(bytes) : "memory"); }
__device__ __forceinline__ void mbar_arrive(uint32_t bar) { asm volatile("mbarrier.arrive.shared::cta.b64 _, [%0];" ::"r"(bar) : "memory"); }
__device__ __forceinline__ void mbar_arrive_if(uint32_t bar, bool c) {
  asm volatile("{\n.reg .pred p;\nsetp.ne.u32 p, %1, 0;\n@p mbarrier.arrive.shared::cta.b64 _, [%0];\n}\n" ::"r"(bar), "r"((uint32_t)c) : "memory");
}
__device__ __forceinline__ bool mbar_try(uint32_t bar, uint32_t parity) {
  uint32_t ok;
  asm volatile("{\n.reg .pred p;\nmbarrier.try_wait.parity.shared::cta.b64 p, [%1], %2;\nselp.u32 %0, 1, 0, p;\n}\n" : "=r"(ok) : "r"(bar), "r"(parity) : "memory");
  return ok;
}
__device__ __forceinline__ void die() { asm volatile("st.volatile.global.u32 [%0], %1;" ::"l"(0ull), "r"(0) : "memory"); }
#define GALL 0
template <bool G = false> __device__ __forceinline__ void spin_guard(uint32_t& n, uint32_t = 0) {
  if (G || GALL == 1) { if (++n == (1u << 20)) die(); }
  else if (GALL == 2) __nanosleep(0);
  else if (GALL == 3) __syncwarp();
}
template <bool G = false> __device__ __forceinline__ void mbar_wait(uint32_t bar, uint32_t parity) {
  uint32_t t0 = 0;
#pragma unroll 1
  while (!mbar_try(bar, parity)) spin_guard<G>(t0, bar);
}
__device__ __forceinline__ void mbar_wait2(uint32_t b0, uint32_t p0, uint32_t b1, uint32_t p1) { mbar_wait(b0, p0); mbar_wait(b1, p1); }
__device__ __forceinline__ int tid_now() { int v; asm volatile("mov.u32 %0, %%tid.x;" : "=r"(v)); return v & 127; }
__device__ __forceinline__ bool elect_one() {
  uint32_t p;
  asm volatile("{\n.reg .pred P;\nelect.sync _|P, 0xffffffff;\nselp.u32 %0, 1, 0, P;\n}\n" : "=r"(p));
  return p;
}
__device__ __forceinline__ void bar_sync(int id, int n) { asm volatile("bar.sync %0, %1;" ::"r"(id), "r"(n) : "memory"); }
__device__ __forceinline__ void bar_arrive(int id, int n) { asm volatile("bar.arrive %0, %1;" ::"r"(id), "r"(n) : "memory"); }
__device__ __forceinline__ void fence_async_smem() { asm volatile("fence.proxy.async.shared::cta;" ::: "memory"); }
__device__ __forceinline__ void bulk_g2s(uint32_t dst, const void* src, uint32_t bytes, uint32_t bar) {
  asm volatile("cp.async.bulk.shared::cluster.global.mbarrier::complete_tx::bytes [%0], [%1], %2, [%3];" ::"r"(dst), "l"(src), "r"(bytes), "r"(bar) : "memory");
}
__device__ __forceinline__ void bulk_s2g(void* dst, uint32_t src, uint32_t bytes) {
  asm volatile("cp.async.bulk.global.shared::cta.bulk_group [%0], [%1], %2;" ::"l"(dst), "r"(src), "r"(bytes) : "memory");
}
__device__ __forceinline__ void tma2d(uint32_t dst, const CUtensorMap* m, int c0, int c1, uint32_t bar) {
  asm volatile("cp.async.bulk.tensor.2d.shared::cluster.global.mbarrier::complete_tx::bytes [%0], [%1, {%3, %4}], [%2];" ::"r"(dst), "l"(m), "r"(bar), "r"(c0), "r"(c1) : "memory");
}
__device__ __forceinline__ void tma3d(uint32_t dst, const CUtensorMap* m, int c0, int c1, int c2, uint32_t bar) {
  asm volatile("cp.async.bulk.tensor.3d.shared::cluster.global.mbarrier::complete_tx::bytes [%0], [%1, {%3, %4, %5}], [%2];" ::"r"(dst), "l"(m), "r"(bar), "r"(c0), "r"(c1), "r"(c2) : "memory");
}
__device__ __forceinline__ uint4 ld_ll4(const void* p) {
  uint64_t a, b;
  asm volatile("ld.relaxed.gpu.global.v2.u64 {%0,%1}, [%2];" : "=l"(a), "=l"(b) : "l"(p) : "memory");
  return make_uint4((uint32_t)a, (uint32_t)(a >> 32), (uint32_t)b, (uint32_t)(b >> 32));
}
__device__ __forceinline__ void st_ll4(void* p, uint32_t a, uint32_t b, uint32_t c, uint32_t d) {
  asm volatile("st.relaxed.gpu.global.v2.u64 [%0], {%1,%2};" ::"l"(p), "l"(a | ((uint64_t)b << 32)), "l"(c | ((uint64_t)d << 32)) : "memory");
}
__device__ __forceinline__ void st_ll2(void* p, uint32_t a, uint32_t b) { asm volatile("st.relaxed.gpu.global.u64 [%0], %1;" ::"l"(p), "l"(a | ((uint64_t)b << 32)) : "memory"); }
__device__ __forceinline__ void wgmma_colsum(float* d, uint64_t da, uint64_t db) {
  asm volatile("{\n.reg .pred p;\nsetp.ne.b32 p, 1, 0;\nwgmma.mma_async.sync.aligned.m64n8k16.f32.bf16.bf16 {%0, %1, %2, %3}, %4, %5, p, 1, 1, 1, 0;\n}\n"
               : "+f"(d[0]), "+f"(d[1]), "+f"(d[2]), "+f"(d[3]) : "l"(da), "l"(db));
}
__device__ __forceinline__ void prefetch_l2(const void* p) { asm volatile("prefetch.global.L2 [%0];" ::"l"(p)); }
template <bool SLEEP = true> __device__ __forceinline__ void pace(uint32_t& t, uint32_t dt) {
  t += dt;
  while ((int32_t)((uint32_t)clock() - t) < 0) { if (SLEEP) __nanosleep(NSLEEP); }
}
__device__ __forceinline__ void red_release(uint32_t* p) { asm volatile("red.release.gpu.global.add.u32 [%0], 1;" ::"l"(p) : "memory"); }
__device__ __forceinline__ uint4 ldg4(const void* p) { uint4 v; asm volatile("ld.global.v4.u32 {%0,%1,%2,%3}, [%4];" : "=r"(v.x), "=r"(v.y), "=r"(v.z), "=r"(v.w) : "l"(p) : "memory"); return v; }
__device__ __forceinline__ uint32_t ldg1(const void* p) { uint32_t v; asm volatile("ld.global.u32 %0, [%1];" : "=r"(v) : "l"(p) : "memory"); return v; }
__device__ __forceinline__ void stg4_if(void* p, uint32_t a, uint32_t b, uint32_t c, uint32_t d, bool on) {
  asm volatile("{\n.reg .pred p;\nsetp.ne.u32 p, %5, 0;\n@p st.global.v4.u32 [%0], {%1,%2,%3,%4};\n}\n" ::"l"(p), "r"(a), "r"(b), "r"(c), "r"(d), "r"((uint32_t)on) : "memory");
}
template <int OFF> __device__ __forceinline__ uint32_t lds32(uint32_t a) { uint32_t v; asm volatile("ld.shared.u32 %0, [%1+%2];" : "=r"(v) : "r"(a), "n"(OFF)); return v; }
__device__ __forceinline__ uint4 lds128(uint32_t a) { uint4 v; asm volatile("ld.shared.v4.u32 {%0,%1,%2,%3}, [%4];" : "=r"(v.x), "=r"(v.y), "=r"(v.z), "=r"(v.w) : "r"(a) : "memory"); return v; }
__device__ __forceinline__ float2 lds64f(uint32_t a) { float2 v; asm volatile("ld.shared.v2.f32 {%0,%1}, [%2];" : "=f"(v.x), "=f"(v.y) : "r"(a) : "memory"); return v; }
__device__ __forceinline__ void sts64f(uint32_t a, float x, float y) { asm volatile("st.shared.v2.f32 [%0], {%1,%2};" ::"r"(a), "f"(x), "f"(y) : "memory"); }
__device__ __forceinline__ void sts32(uint32_t a, uint32_t x) { asm volatile("st.shared.u32 [%0], %1;" ::"r"(a), "r"(x) : "memory"); }
__device__ __forceinline__ void sts128(uint32_t a, uint32_t x, uint32_t y, uint32_t z, uint32_t w) { asm volatile("st.shared.v4.u32 [%0], {%1,%2,%3,%4};" ::"r"(a), "r"(x), "r"(y), "r"(z), "r"(w) : "memory"); }
__device__ __forceinline__ void stsm4(uint32_t a, uint32_t r0, uint32_t r1, uint32_t r2, uint32_t r3) {
  asm volatile("stmatrix.sync.aligned.m8n8.x4.shared.b16 [%0], {%1,%2,%3,%4};" ::"r"(a), "r"(r0), "r"(r1), "r"(r2), "r"(r3) : "memory");
}
__device__ __forceinline__ void stsm4t(uint32_t a, uint32_t r0, uint32_t r1, uint32_t r2, uint32_t r3) {
  asm volatile("stmatrix.sync.aligned.m8n8.x4.trans.shared.b16 [%0], {%1,%2,%3,%4};" ::"r"(a), "r"(r0), "r"(r1), "r"(r2), "r"(r3) : "memory");
}
__device__ __forceinline__ void ldsm4t(uint32_t* r, uint32_t a) {
  asm volatile("ldmatrix.sync.aligned.m8n8.x4.trans.shared.b16 {%0,%1,%2,%3}, [%4];" : "=r"(r[0]), "=r"(r[1]), "=r"(r[2]), "=r"(r[3]) : "r"(a) : "memory");
}
__device__ __forceinline__ uint32_t pack2(float lo, float hi) { uint32_t r; asm("cvt.rn.bf16x2.f32 %0, %1, %2;" : "=r"(r) : "f"(hi), "f"(lo)); return r; }
__device__ __forceinline__ float bf_lo(uint32_t u) { return __uint_as_float(u << 16); }
__device__ __forceinline__ float bf_hi(uint32_t u) { return __uint_as_float(u & 0xffff0000u); }
__device__ __forceinline__ float tanh_fast(float x) { float y; asm("tanh.approx.f32 %0, %1;" : "=f"(y) : "f"(x)); return y; }
__device__ __forceinline__ uint32_t hmul2(uint32_t a, uint32_t b) { uint32_t r; asm("mul.rn.bf16x2 %0, %1, %2;" : "=r"(r) : "r"(a), "r"(b)); return r; }
__device__ __forceinline__ uint32_t hfma2(uint32_t a, uint32_t b, uint32_t c) { uint32_t r; asm("fma.rn.bf16x2 %0, %1, %2, %3;" : "=r"(r) : "r"(a), "r"(b), "r"(c)); return r; }
__device__ __forceinline__ uint32_t prmt(uint32_t a, uint32_t b, uint32_t s) { return __byte_perm(a, b, s); }

__device__ __forceinline__ uint32_t ld_relaxed(const uint32_t* p) { uint32_t v; asm volatile("ld.relaxed.gpu.global.u32 %0, [%1];" : "=r"(v) : "l"(p) : "memory"); return v; }
__device__ __forceinline__ void acquire_fence() { asm volatile("fence.acquire.gpu;\nfence.proxy.async.global;" ::: "memory"); }
__device__ __forceinline__ uint32_t load_epoch(const Params& p, int idx, int lane) { return ld_relaxed(&p.scr->epoch[idx + (((lane * lane) & 3) == 2 ? 1 : 0)]); }
template <bool G, int DT, class T, class L, class C>
__device__ __forceinline__ T poll3(L load, C ok) {
  uint32_t t0 = 0;
  T a = load();
#pragma unroll 1
  while (!__all_sync(0xffffffff, ok(a))) { spin_guard<G>(t0); if (DT) __nanosleep(DT); a = load(); }
  return a;
}
__device__ __forceinline__ void poll_flags4(const uint32_t* flags, uint32_t tag, int lane) {
  poll3<false, PPC, uint32_t>([&]() { return ld_relaxed(flags + (lane & 3) * 8); }, [&](uint32_t v) { return v == tag; });
  acquire_fence();
}
__device__ __forceinline__ void st_relaxed(uint32_t* p, uint32_t v) { asm volatile("st.relaxed.gpu.global.u32 [%0], %1;" ::"l"(p), "r"(v) : "memory"); }
__device__ __forceinline__ uint32_t tag8(uint32_t tag) { return (tag & 127) | 128; }
__device__ __forceinline__ uint32_t tagged(float v, uint32_t t8) { return (__float_as_uint(v) & ~255u) | t8; }
__device__ __forceinline__ void reset_sector(uint32_t* f) { st_ll4(f, 0, 0, 0, 0); st_ll4(f + 4, 0, 0, 0, 0); }
template <bool G = false> __device__ __forceinline__ void poll_counter(const uint32_t* cnt, uint32_t target) {
  poll3<G, PPC, uint32_t>([&]() { return ld_relaxed(cnt); }, [&](uint32_t v) { return v == target; });
  acquire_fence();
}

__device__ __forceinline__ uint32_t hadd2(uint32_t a, uint32_t b) { uint32_t r; asm("add.rn.bf16x2 %0, %1, %2;" : "=r"(r) : "r"(a), "r"(b)); return r; }
__device__ __forceinline__ uint32_t htanh2(uint32_t a) { uint32_t r; asm("tanh.approx.bf16x2 %0, %1;" : "=r"(r) : "r"(a)); return r; }
__device__ __forceinline__ void red_relaxed(uint32_t* p) { asm volatile("red.relaxed.gpu.global.add.u32 [%0], 1;" ::"l"(p) : "memory"); }
__device__ __forceinline__ void bulk_commit_wait() { asm volatile("cp.async.bulk.commit_group;\ncp.async.bulk.wait_group 0;" ::: "memory"); }

__device__ __forceinline__ int g3_block(int cb, int it) { return it < 3 ? cb * 3 + it : (it - 3 < cb * 3 ? it - 3 : it); }

#define GSTAMP(m, i)
struct NoHook { __device__ __forceinline__ void operator()(int = 0) const {} };
template <int N, int MODE, class F = NoHook, class F0 = NoHook>
__device__ __forceinline__ void gemm_seg(float* d, uint32_t sb, uint64_t db0, int i0, int i1, int s, uint32_t pb, uint32_t doR, uint32_t acc TSP, F hook = F(), F0 pre = F0()) {
  constexpr bool G3 = MODE == 2 || MODE == 4, RA = MODE == 1 || MODE == 3;
  constexpr int W = MODE <= 2 ? 2 : 1, RC = MODE == 2 ? 1 : 2, NS = G3 ? 6 : 5, BSTEP = G3 ? 320 : 128;
  const uint64_t da0 = mkdesc(sb + OFF_A, 16, 1024, 1);
  auto sa = [](int i) { return MODE == 1 ? (i + 3) & 7 : (G3 && i >= 9 ? i - 9 : i); };
  auto fa = [&](int i) { return sb + (MODE == 2 ? (i < 3 ? BAR_HR : BAR_HV + 8 * (i - 3)) : BAR_AF + 8 * sa(i)); };
  auto pa = [](int i) { return MODE == 1 ? ((i >> 3) & 1) ^ 1 : MODE == 2 && i >= 9; };
  auto fb = [&](int s_) { return sb + (G3 ? BAR_WF : BAR_BF) + 8 * s_; };
  auto db = [&](int s_) { return db0 + (G3 ? (s_ >= 3 ? s_ - 3 : s_ + 3) * (W_SLOT >> 4) : s_ * (B_SLOT >> 4)); };
  const uint32_t dummy = sb + BAR_DUMMY;
  auto ea = [&](int i) { return MODE == 3 && i >= 8 ? dummy : sb + BAR_AE + 8 * sa(i); };
  uint32_t rel = dummy, rela = dummy;
  acc_fence<N / 2>(d);
  pre();
  if (W == 2) mbar_wait(fa(i0), pa(i0));
  mbar_wait(fb(s), pb);
  WG_FENCE();
#pragma unroll 1
  for (int i = i0; i < i1 - 1; i++) {
    GSTAMP(MODE, i);
    const int n = s + 1 == NS ? 0 : s + 1;
    if (n == 0) pb ^= 1;
    KB<N>::template run<W, RC, RA, BSTEP, MODE == 1 && D2 == 1>(d, da0 + sa(i) * (A_SLOT >> 4), db(s), rel, rela, doR, fa(i + 1), pa(i + 1), fb(n), pb, acc);
    rel = G3 ? (i < 6 ? sb + BAR_WE + 8 * s : dummy) : sb + BAR_BE + 8 * s;
    rela = ea(i);
    s = n;
    acc = 1;
  }
  hook();
  GSTAMP(MODE, i1 - 1);
  KB<N>::template run<0, RC, RA, BSTEP, MODE == 1 && D2 == 1>(d, da0 + sa(i1 - 1) * (A_SLOT >> 4), db(s), rel, rela, doR, 0, 0, 0, 0, 1);
  WG_WAIT(0);
  GSTAMP(MODE, i1);
  acc_fence<N / 2>(d);
  if (MODE != 2) {
    rel = sb + (G3 ? BAR_WE : BAR_BE) + 8 * s;
    mbar_arrive_if(rel, doR);
    mbar_arrive_if(rel, doR);
    if (RA) { mbar_arrive_if(ea(i1 - 1), doR); mbar_arrive_if(ea(i1 - 1), doR); }
  }
}

__device__ __forceinline__ uint32_t val_off(int lane) { return lane * 32 + ((lane >> 2) & 1) * 16 + (lane >> 3) * 4; }
template <int NK, int PAD = 0, class F>
__device__ __forceinline__ void validate(uint32_t a, uint32_t par, uint32_t rt, F reload) {
  uint32_t t0 = 0;
#pragma unroll 1
  while (true) {
    uint32_t v[NK], any = 0;
#pragma unroll
    for (int i = 0; i < NK; i++) asm volatile("ld.shared.u32 %0, [%1];" : "=r"(v[i]) : "r"(a + i * 1024 + (i >> 1) * PAD) : "memory");
#pragma unroll
    for (int i = 0; i < NK; i++) any |= v[i] ^ par;
    if (!__any_sync(0xffffffff, any & 1)) break;
    spin_guard(t0);
    fence_async_smem();
    __syncwarp();
    if (elect_one()) { mbar_init(rt, 1); fence_async_smem(); mbar_expect(rt, NK * 1024); reload(); }
    __syncwarp();
    mbar_wait(rt, 0);
    __syncwarp();
    if (elect_one()) asm volatile("mbarrier.inval.shared::cta.b64 [%0];" ::"r"(rt) : "memory");
  }
}
__device__ __forceinline__ uint32_t swz_base(uint32_t img, int w, int lane) { return img + (w * 16 + (lane & 15)) * 128 + (((lane >> 4) ^ lane) & 7) * 16; }

template <int NT, bool STATS>
__device__ __forceinline__ void gelu_tile(const float* d, uint32_t* z, float* st, uint32_t cs0, float2 s0, float2 s1, uint32_t done) {
  const float kA = 0.7978845608028654f, kB = 0.7978845608028654f * 0.044715f;
  const float a1 = kA * s0.y, a3 = kB * s0.y * s0.y * s0.y, b1 = kA * s1.y, b3 = kB * s1.y * s1.y * s1.y;
  const uint32_t c1[2] = {pack2(a1, a1), pack2(b1, b1)}, c3[2] = {pack2(a3, a3), pack2(b3, b3)};
  const float m[2] = {-s0.x, -s1.x};
  uint32_t S[2][2], Q[2][2];
  float fs[4] = {0.f, 0.f, 0.f, 0.f}, fq[4] = {0.f, 0.f, 0.f, 0.f};
#pragma unroll
  for (int j = 0; j < NT; j++) {
    if (!STATS && j && j % 6 == 0) mbar_wait(done, 0);
    const float2 cs = lds64f(cs0 + j * 32);
#pragma unroll
    for (int r = 0; r < 2; r++) {
      constexpr int V = STATS ? GV : GVC;
      const float v0 = fmaf(m[r], cs.x, d[4 * j + 2 * r]), v1 = fmaf(m[r], cs.y, d[4 * j + 2 * r + 1]);
      uint32_t y;
      if (((XP & 1) && !STATS) || ((XP & 64) && STATS)) y = pack2(v0, v1);
      else if (V == 0) {
        const uint32_t v = pack2(v0, v1);
        y = hfma2(v, htanh2(hmul2(v, hfma2(hmul2(v, v), c3[r], c1[r]))), v);
      } else if (V <= 3) {
        const float f1 = r ? b1 : a1, f3 = r ? b3 : a3;
        const float t0 = tanh_fast(v0 * fmaf(v0 * v0, f3, f1)), t1 = tanh_fast(v1 * fmaf(v1 * v1, f3, f1));
        if (V == 3) { const uint32_t v = pack2(v0, v1); y = hfma2(v, pack2(t0, t1), v); }
        else {
          const float y0 = fmaf(v0, t0, v0), y1 = fmaf(v1, t1, v1);
          if (V == 2 && STATS) { fs[2 * r] += y0; fs[2 * r + 1] += y1; fq[2 * r] = fmaf(y0, y0, fq[2 * r]); fq[2 * r + 1] = fmaf(y1, y1, fq[2 * r + 1]); }
          y = pack2(y0, y1);
        }
      } else {
        const uint32_t v = pack2(v0, v1), a = hmul2(v, hfma2(hmul2(v, v), c3[r], c1[r]));
        y = pack2(fmaf(v0, tanh_fast(bf_lo(a)), v0), fmaf(v1, tanh_fast(__uint_as_float(a)), v1));
      }
      asm volatile("" : "+r"(y));
      z[2 * j + r] = y;
      if (STATS && V != 2) {
        S[r][j & 1] = j < 2 ? y : hadd2(S[r][j & 1], y);
        Q[r][j & 1] = j < 2 ? hmul2(y, y) : hfma2(y, y, Q[r][j & 1]);
      }
    }
  }
  if (STATS) {
#pragma unroll
    for (int r = 0; r < 2; r++) {
      if (GV == 2) { st[2 * r] = fs[2 * r] + fs[2 * r + 1]; st[2 * r + 1] = fq[2 * r] + fq[2 * r + 1]; continue; }
      st[2 * r] = (bf_lo(S[r][0]) + bf_hi(S[r][0])) + (bf_lo(S[r][1]) + bf_hi(S[r][1]));
      st[2 * r + 1] = (bf_lo(Q[r][0]) + bf_hi(Q[r][0])) + (bf_lo(Q[r][1]) + bf_hi(Q[r][1]));
    }
  }
}

__device__ __forceinline__ float2 quad_sum(const float* st, int t) {
  const bool o = t & 1;
  float s = (o ? st[2] : st[0]) + __shfl_xor_sync(0xffffffff, o ? st[0] : st[2], 1);
  float q = (o ? st[3] : st[1]) + __shfl_xor_sync(0xffffffff, o ? st[1] : st[3], 1);
  s += __shfl_xor_sync(0xffffffff, s, 2);
  q += __shfl_xor_sync(0xffffffff, q, 2);
  return make_float2(s, q);
}
template <int Q> __device__ __forceinline__ void conv_load(uint32_t* a, uint32_t ab) {
  a[0] = lds32<512 * Q>(ab);       a[1] = lds32<512 * Q + 256>(ab);  a[2] = lds32<512 * Q + 16>(ab);   a[3] = lds32<512 * Q + 272>(ab);
  a[4] = lds32<512 * Q + 32>(ab);  a[5] = lds32<512 * Q + 288>(ab);  a[6] = lds32<512 * Q + 48>(ab);   a[7] = lds32<512 * Q + 304>(ab);
  a[8] = lds32<512 * Q + 64>(ab);  a[9] = lds32<512 * Q + 320>(ab);  a[10] = lds32<512 * Q + 80>(ab);  a[11] = lds32<512 * Q + 336>(ab);
  a[12] = lds32<512 * Q + 96>(ab); a[13] = lds32<512 * Q + 352>(ab); a[14] = lds32<512 * Q + 112>(ab); a[15] = lds32<512 * Q + 368>(ab);
}
template <int Q, int L> __device__ __forceinline__ void conv_step(float* d, uint32_t (*a)[16], uint32_t ab, uint64_t db) {
  WG_FENCE();
#pragma unroll
  for (int s = 0; s < 4; s++) WG<128 - 16 * Q>::rs(d, a[Q] + 4 * s, db + s + 16 * Q);
  WG_COMMIT();
  WG_WAIT(1);
  if (L >= 0) conv_load<(L >= 0 ? L : 0)>(a[L >= 0 ? L : 0], ab);
  if (Q == 0) WG_WAIT(0);
}

__device__ __forceinline__ void final_load_x(uint32_t (*xw)[10], const __nv_bfloat16* x0, int t) {
#pragma unroll
  for (int r = 0; r < 2; r++) {
    const __nv_bfloat16* q = x0 + r * 8 * kD;
    const uint4 u = ldg4(q + t * 8), v = ldg4(q + 32 + t * 8);
    asm volatile("ld.global.v2.u32 {%0,%1}, [%2];" : "=r"(xw[r][8]), "=r"(xw[r][9]) : "l"(q + 64 + t * 4) : "memory");
    xw[r][0] = u.x; xw[r][1] = u.y; xw[r][2] = u.z; xw[r][3] = u.w;
    xw[r][4] = v.x; xw[r][5] = v.y; xw[r][6] = v.z; xw[r][7] = v.w;
  }
}
__device__ __forceinline__ void final_gate(const float* d, uint32_t* gt, const uint32_t (*xw)[10], float2 s0, float2 s1) {
  const uint32_t r2[2] = {pack2(s0.y, s0.y), pack2(s1.y, s1.y)};
  const float na = -s0.x * bf_lo(r2[0]), nb = -s1.x * bf_lo(r2[1]), c[2] = {0.25f * s0.y, 0.25f * s1.y};
  const uint32_t n2[2] = {pack2(na, na), pack2(nb, nb)};
#pragma unroll
  for (int i = 0; i < 20; i++) {
    const int r = i & 1;
    const uint32_t h = pack2(d[2 * i] * c[r], d[2 * i + 1] * c[r]);
    gt[i] = (XP & 4) ? h : hmul2(hfma2(h, htanh2(h), h), hfma2(xw[r][i >> 1], r2[r], n2[r]));
    asm volatile("" : "+r"(gt[i]));
  }
}
__device__ __forceinline__ void final_out(const uint32_t* gt, const uint32_t (*xw)[10], uint32_t yt, __nv_bfloat16* o0, int w, int lane) {
  const int r8 = lane & 7, mi = lane >> 3, t = lane & 3;
  const uint32_t ya = yt + ((mi >> 1) * 8 + r8) * 128 + (((2 * w + (mi & 1)) ^ r8) << 4);
  uint32_t y[20];
#pragma unroll
  for (int j = 0; j < 5; j++) ldsm4t(y + 4 * j, ya + j * 2048);
#pragma unroll
  for (int i = 0; i < 20; i++) y[i] = hfma2(gt[i], y[i], xw[i & 1][i >> 1]);
#pragma unroll
  for (int r = 0; r < 2; r++) {
    __nv_bfloat16* q = o0 + r * 8 * kD;
    stg4_if(q + t * 8, y[r], y[2 + r], y[4 + r], y[6 + r], true);
    stg4_if(q + 32 + t * 8, y[8 + r], y[10 + r], y[12 + r], y[14 + r], true);
    asm volatile("st.global.v2.u32 [%0], {%1,%2};" ::"l"(q + 64 + t * 4), "r"(y[16 + r]), "r"(y[18 + r]) : "memory");
  }
}

struct Taps { uint4 r0, r1; uint32_t n0, n1, dd; };
__device__ __forceinline__ void load_taps(Taps& k, const Params& p, int ch, int tid) {
  const uint4* kp = (const uint4*)(p.ssmk + (size_t)ch * kS);
  k.r0 = ldg4(kp + tid); k.r1 = ldg4(kp + 128 + tid);
  k.n0 = ldg1(kp + tid + 1); k.n1 = tid < 127 ? ldg1(kp + 129 + tid) : 0u;
  k.dd = __bfloat16_as_ushort(p.ssmD[ch]);
}
__device__ __forceinline__ void convx_copy(const Params& p, uint32_t cv, uint32_t bar, int ch) {
  bulk_g2s(cv, p.scr->kvx + (size_t)ch * 4096, 2048, bar);
  bulk_g2s(cv + XB_PL, p.scr->kvx + (size_t)ch * 4096 + 2048, 2048, bar);
}
__device__ __forceinline__ void convx_issue(const Params& p, uint32_t sb, int h, int ch) {
  if (elect_one()) { mbar_expect(sb + BAR_XL + 8 * h, 4096); convx_copy(p, sb + OFF_CV + (1 - h) * CV_SZ, sb + BAR_XL + 8 * h, ch); }
}
__device__ __forceinline__ void convx_finish(const Params& p, uint32_t sb, int h, int ch, int i, uint32_t par, int lane) {
  const uint32_t cv = sb + OFF_CV + (1 - h) * CV_SZ, rt = sb + BAR_XL - 16 + 8 * h;
  mbar_wait(sb + BAR_XL + 8 * h, i & 1);
  validate<4, XB_PL - 2048>(cv + lane * 32, par, rt, [&]() { convx_copy(p, cv, rt, ch); });
  if (elect_one()) mbar_arrive(sb + BAR_XF + 8 * h);
}
__device__ __forceinline__ void zero_pads(uint32_t cv, int lane) {
  if (lane < 8) sts128(cv + (lane >> 2) * XB_PL + 2048 + (lane & 3) * 16, 0, 0, 0, 0);
  else if (lane < 12) sts128(cv + ((lane & 2) ? CV_KO : CV_KE) + (lane & 1) * 16, 0, 0, 0, 0);
  fence_async_smem();
  __syncwarp();
}
__device__ __forceinline__ int y_row(int c) {
  const int cc = c % 80;
  return c - cc + (cc & 1) + (cc < 64 ? (cc & 32) + ((cc >> 1) & 3) * 8 + ((cc >> 3) & 3) * 2 : 64 + ((cc >> 1) & 1) * 8 + ((cc >> 2) & 3) * 2);
}
struct KvRegs { uint32_t k[11], v[8]; uint4 sh; };
__device__ __forceinline__ void kv_load(KvRegs& q, const __nv_bfloat16* kp, const __nv_bfloat16* vp, const __nv_bfloat16* sp, bool halo) {
  if (XP & 8) { for (int i = 0; i < 11; i++) q.k[i] = (uint32_t)(size_t)kp + i; for (int i = 0; i < 8; i++) q.v[i] = i; q.sh = make_uint4(1, 2, 3, 4); return; }
#pragma unroll
  for (int i = 0; i < 11; i++) q.k[i] = (i >= 3 || halo) ? ldg1(kp + i * kD) : 0u;
#pragma unroll
  for (int i = 0; i < 8; i++) q.v[i] = ldg1(vp + i * kD);
  q.sh = ldg4(sp);
}
__device__ __forceinline__ void kv_calc(const KvRegs& q, uint32_t* o) {
  const uint32_t w0 = prmt(q.sh.x, q.sh.z, 0x5410), w1 = prmt(q.sh.x, q.sh.z, 0x7632), w2 = prmt(q.sh.y, q.sh.w, 0x5410), w3 = prmt(q.sh.y, q.sh.w, 0x7632);
  uint32_t r[8];
#pragma unroll
  for (int i = 0; i < 8; i++) r[i] = hmul2(hfma2(q.k[i + 3], w0, hfma2(q.k[i + 2], w1, hfma2(q.k[i + 1], w2, hmul2(q.k[i], w3)))), q.v[i]);
#pragma unroll
  for (int i = 0; i < 4; i++) { o[i] = prmt(r[7 - 2 * i], r[6 - 2 * i], 0x5410); o[4 + i] = prmt(r[7 - 2 * i], r[6 - 2 * i], 0x7632); }
}
__device__ __forceinline__ void kv_put(const uint32_t* o, uint32_t oa, uint32_t tm, uint32_t tb) {
  sts128(oa, (o[0] & tm) | tb, o[1], o[2], o[3]);
  sts128(oa + 2048, (o[4] & tm) | tb, o[5], o[6], o[7]);
}

__device__ __forceinline__ void kv_store(const Params& p, uint32_t src, int tb, int unit) {
  asm volatile("cp.async.bulk.tensor.3d.global.shared::cta.bulk_group [%0, {%2, %3, %4}], [%1];" ::"l"(&p.tmKV), "r"(src), "r"((63 - tb) * 16), "r"(unit * 32), "r"(0) : "memory");
}
__device__ __forceinline__ uint32_t kv_stage_addr(int w, int lane) { return ((3 - w) & 1) * 1024 + lane * 32 + ((((3 - w) >> 1) ^ (lane >> 2)) & 1) * 16; }

template <class F>
__device__ __forceinline__ void conv_service(const Params& p, uint32_t sb, int h, int ch, uint32_t par, int lane, F mid) {
#pragma unroll 1
  for (int i = 0; i < 2 + h; i++, ch += 128) {
    bar_sync(NB_SV + h, 160);
    if (i < h) convx_issue(p, sb, h, ch + 128);
    uint8_t* dst = p.scr->y + (size_t)y_row(ch) * 4096;
    bar_sync(NB_SV + h, 160);
    if (elect_one()) {
      bulk_s2g(dst, sb + OFF_A + 9 * A_SLOT + h * 4096, 4096);
      bulk_commit_wait();
    }
    __syncwarp();
    if (i > h) break;
    if (i == h) { mid(); mbar_wait(sb + BAR_KV2, 0); convx_issue(p, sb, h, ch + 128); }
    convx_finish(p, sb, h, ch + 128, i + 1, par, lane);
  }
}
__device__ __forceinline__ void conv_worker(const Params& p, Taps& k, uint32_t sb, int h, int ch0, int w, int lane, int tid, int rb, int cb TSP) {
  const uint32_t cv = sb + OFF_CV + (1 - h) * CV_SZ, yb0 = sb + OFF_A + 9 * A_SLOT + h * 4096, xbar = sb + BAR_XF + 8 * h;
  const int n = 2 + h, nbar = NB_WG + h;
  const int g = lane >> 2, t = lane & 3, w0 = w & 1, w1 = w >> 1;
  const uint32_t ab = cv + ((g & 1) ? CV_KE : CV_KO) + 32 + 2 * (64 * w0 + 8 * w1 + ((g - 15) & ~1) + 2 * t);
  const uint32_t scA = cv + (w1 ? CV_KO : CV_KE) + 32, scB = scA + 2048;
  const int dl = (t >> 1) ^ 1, col = lane & 7, mi = lane >> 3;
  if (h == 0) mbar_wait(xbar, 0);
  TR(26);
#pragma unroll 1
  for (int i = 0; i < n; i++) {
    if (tid == 0) {
      k.r0.x = (k.r0.x & 0xffff0000u) | (pack2(bf_lo(k.r0.x) + bf_lo(k.dd), 0.f) & 0xffffu);
      sts32(cv + CV_KO + 28, k.r0.x << 16);
    }
    sts128(cv + CV_KE + 32 + tid * 16, k.r0.x, k.r0.y, k.r0.z, k.r0.w);
    sts128(cv + CV_KO + 32 + tid * 16, prmt(k.r0.x, k.r0.y, 0x5432), prmt(k.r0.y, k.r0.z, 0x5432), prmt(k.r0.z, k.r0.w, 0x5432), prmt(k.r0.w, k.n0, 0x5432));
    sts128(cv + CV_KE + 2080 + tid * 16, k.r1.x, k.r1.y, k.r1.z, k.r1.w);
    sts128(cv + CV_KO + 2080 + tid * 16, prmt(k.r1.x, k.r1.y, 0x5432), prmt(k.r1.y, k.r1.z, 0x5432), prmt(k.r1.z, k.r1.w, 0x5432), prmt(k.r1.w, k.n1, 0x5432));
    TR(30 + i * 10);
    if (i + 1 < n) load_taps(k, p, ch0 + (i + 1) * 128, tid);
    bar_sync(nbar, 128);
    TR(31 + i * 10);
    const uint64_t db = mkdesc(cv + (i & 0x1000), XB_PL, 128, 0);
    float d[64];
    uint32_t a[8][16];
    conv_load<7>(a[7], ab);
    conv_load<6>(a[6], ab);
    conv_load<5>(a[5], ab);
    conv_load<4>(a[4], ab);
#pragma unroll
    for (int j = 0; j < 64; j++) d[j] = 0.f;
    if (i == 0) STAMPW(h ? 43 : 8);
    TR(32 + i * 10);
    const uint32_t hold = sb + (i + 1 == n ? (HOLD == 32 || (STG && STG != h + 1) ? BAR_HR : BAR_HOLD) : (HK1 == 0 || i ? BAR_XS : (HK1 == 1 ? BAR_ZG : BAR_ZP)));
    if (HVY) {
      mbar_wait(xbar, i & 1);
      conv_step<7, -1>(d, a, ab, db); conv_step<6, 3>(d, a, ab, db); conv_step<5, 2>(d, a, ab, db); conv_step<4, 1>(d, a, ab, db);
      WG_WAIT(0);
      conv_load<0>(a[0], ab);
      TR(39 + i * 10);
      mbar_wait(hold, 0);
    } else {
      mbar_wait2(xbar, i & 1, hold, 0);
    }
    if (i == 0) STAMPW(h ? 51 : 7);
    TR(33 + i * 10);
    if (!((XP & 32) && i == 1 && h == 1) && !((XP & 128) && i + 1 == n) && !((XP & 256) && i == 0)) {
    if (HVY) {
      conv_step<3, -1>(d, a, ab, db); conv_step<2, -1>(d, a, ab, db); conv_step<1, -1>(d, a, ab, db); conv_step<0, -1>(d, a, ab, db);
    } else {
    conv_step<7, -1>(d, a, ab, db); conv_step<6, -1>(d, a, ab, db); conv_step<5, -1>(d, a, ab, db); conv_step<4, 3>(d, a, ab, db);
    conv_step<3, 2>(d, a, ab, db); conv_step<2, 1>(d, a, ab, db); conv_step<1, 0>(d, a, ab, db); conv_step<0, -1>(d, a, ab, db);
    }
    }
    acc_fence<64>(d);
    TR(34 + i * 10);
    if (HE && i == 0) mbar_wait(sb + BAR_ZG, 1);
    bar_sync(NB_SV + h, 160);
    TR(35 + i * 10);
    float E[16][2];
#pragma unroll
    for (int j = 0; j < 15; j++) { E[j][0] = d[4 * j] + d[4 * j + 6]; E[j][1] = d[4 * j + 1] + d[4 * j + 7]; }
    E[15][0] = d[60]; E[15][1] = d[61];
    if (w0 == 0) {
#pragma unroll
      for (int j = 8; j < 16; j++) sts64f(scA + (j - 8) * 256 + lane * 8, E[j][0], E[j][1]);
    } else {
      const uint32_t a = scB - dl * 256 + (lane ^ 2) * 8;
#pragma unroll
      for (int j = 1; j < 8; j++) sts64f(a + j * 256, E[j][0], E[j][1]);
      sts64f(scB + (dl ? 7 * 256 : 0) + (lane ^ 2) * 8, dl ? E[8][0] : E[0][0], dl ? E[8][1] : E[0][1]);
    }
    TR(36 + i * 10);
    bar_sync(nbar, 128);
    uint32_t pk[8];
    const bool tg = YTAG && w1 == 0 && g == 0;
    const uint32_t tm = tg ? ~0x10001u : ~0u, tb = tg ? (lds32<0>(sb + OFF_TAG) & 1) * 0x10001u : 0;
    if (w0 == 0) {
#pragma unroll
      for (int j = 0; j < 8; j++) { const float2 v = lds64f(scB + j * 256 + lane * 8); pk[j] = (pack2(E[j][0] + v.x, E[j][1] + v.y) & tm) | tb; }
      const uint32_t ya = yb0 + 32 * (127 - (8 * mi + col)) + 16 * w1;
      stsm4t(ya, pk[0], pk[1], pk[2], pk[3]);
      stsm4t(ya - 1024, pk[4], pk[5], pk[6], pk[7]);
    } else {
      const uint32_t a0 = scA - dl * 256 + (lane ^ 2) * 8;
#pragma unroll
      for (int j = 9; j < 16; j++) { const float2 v = lds64f(a0 + (j - 8) * 256); pk[j - 8] = (pack2(E[j][0] + v.x, E[j][1] + v.y) & tm) | tb; }
      const float2 v = lds64f(scA + (dl ? 7 * 256 : 0) + (lane ^ 2) * 8);
      pk[0] = (pack2((dl ? 0.f : E[8][0]) + v.x, (dl ? 0.f : E[8][1]) + v.y) & tm) | tb;
      const uint32_t yb = yb0 + 32 * (127 - (92 + 8 * mi + col)) + 16 * w1;
      const uint32_t ya = (mi == 0 && col < 4) ? yb0 + 32 * (3 - col) + 16 * w1 : yb + 1024;
      stsm4t(ya, pk[0], pk[1], pk[2], pk[3]);
      stsm4t(yb, pk[4], pk[5], pk[6], pk[7]);
    }
    TR(37 + i * 10);
    fence_async_smem();
    bar_sync(NB_SV + h, 160);
    TR(38 + i * 10);
    STAMPW((h ? 40 : 5) + i);
    if (i == 0 && h == 0) {
      const int tn = tid_now();
      {
        const int ln = tn & 31, t0 = (rb * 2 + (cb & 1)) * 32 + w * 8, c0 = (cb >> 1) * 320 + 192 + ln * 2;
        KvRegs q0, q1;
        uint32_t o[8];
        kv_load(q0, p.k + (size_t)(t0 - 3) * kD + c0, p.v + (size_t)t0 * kD + c0, p.shift + c0 * 4, t0 > 0);
        kv_load(q1, p.k + (size_t)(t0 - 3) * kD + c0 + 64, p.v + (size_t)t0 * kD + c0 + 64, p.shift + c0 * 4 + 256, t0 > 0);
        const uint32_t oa = sb + OFF_A + 8 * A_SLOT + kv_stage_addr(w, ln), km = w >= 2 ? ~1u : ~0u, kb = w >= 2 ? lds32<0>(sb + OFF_TAG) & 1 : 0;
        kv_calc(q0, o);
        kv_put(o, oa, km, kb);
        kv_calc(q1, o);
        kv_put(o, oa + 4096, km, kb);
        fence_async_smem();
        bar_arrive(NB_KL, 160);
      }
      STAMPW(56);
      const int u = (tn >> 3) % 5, kg = rb * 3 + (tn < 120 ? (tn >> 3) / 5 : 0), c = u < 4 ? (u >> 1) * 10 + (u & 1) * 4 : 8, o2 = u < 4 ? 2 : 10;
      const uint4* wp = (const uint4*)(p.wout + (size_t)(kg * 8 + (tn & 7)) * kD + cb * 160) + c;
      const uint4 w0 = ldg4(wp), w1 = ldg4(wp + 1), w2 = ldg4(wp + o2), w3 = ldg4(wp + o2 + 1);
      uint8_t* dst = p.scr->wo + (size_t)cb * (12 * W_SLOT) + kg * 2560 + c * 128 + (tn & 7) * 16;
      const bool f = u < 4, on = tn < 120;
      stg4_if(dst, w0.x, f ? w1.x : w0.z, f ? w2.x : w1.x, f ? w3.x : w1.z, on);
      stg4_if(dst + 128, w0.y, f ? w1.y : w0.w, f ? w2.y : w1.y, f ? w3.y : w1.w, on);
      stg4_if(dst + o2 * 128, f ? w0.z : w2.x, f ? w1.z : w2.z, f ? w2.z : w3.x, w3.z, on);
      stg4_if(dst + o2 * 128 + 128, f ? w0.w : w2.y, f ? w1.w : w2.w, f ? w2.w : w3.y, w3.w, on);
      bar_arrive(NB_WO, 160);
    }
  }
}

struct U6 { uint64_t a, b, c; };
__device__ __forceinline__ uint64_t ld_ll2(const void* p) { uint64_t a; asm volatile("ld.relaxed.gpu.global.u64 %0, [%1];" : "=l"(a) : "l"(p) : "memory"); return a; }
__device__ __forceinline__ void gather_colsum(const Params& p, uint32_t sb, int part, int cb, uint32_t tag8, int lane) {
  const uint32_t* src = p.scr->colsum + (uint32_t)((part ? 0 : 768) + cb * 192 + lane * 2);
  const uint64_t t2 = tag8 * 0x100000001ull;
  const U6 v = poll3<false, PP, U6>([&]() { return U6{ld_ll2(src), ld_ll2(src + 64), ld_ll2(src + 128)}; },
                                    [&](const U6& u) { return (((u.a ^ t2) | (u.b ^ t2) | (u.c ^ t2)) & 0xff000000ffull) == 0; });
  const uint32_t dst = sb + OFF_CS + (part ? 0 : 768) + lane * 8;
  asm volatile("st.shared.u64 [%0], %1;\nst.shared.u64 [%0+256], %2;\nst.shared.u64 [%0+512], %3;" ::"r"(dst), "l"(v.a), "l"(v.b), "l"(v.c) : "memory");
  __syncwarp();
  mbar_arrive_if(sb + BAR_ST + 8 * part, lane == 0);
}

__device__ __forceinline__ void helper_cta(const Params& p, uint32_t sb, int cb, int warp, int lane TSP) {
  constexpr int NS = 9, ONES = NS * B_SLOT, BF = ONES + 256, BE = BF + 8 * NS;
  if (warp < NS && elect_one()) {
    mbar_init(sb + BF + 8 * warp, 1); mbar_init(sb + BE + 8 * warp, 1);
    fence_async_smem();
    if (warp == 0) { mbar_expect(sb + BF, B_SLOT); tma3d(sb, &p.tmW, 0, 0, 12 + cb * 3, sb + BF); }
  }
  if (warp == 15) { sts32(sb + ONES + lane * 4, 0x3f803f80u); sts32(sb + ONES + 128 + lane * 4, 0x3f803f80u); fence_async_smem(); }
  __syncthreads();
  if (warp == 4) {
    int s = 1, ph = 1;
    uint32_t tp = clock() + HP0;
#pragma unroll 1
    for (int it = 1; it < 20; it++) {
      if (HPD && it >= 10) pace(tp, HPD);
      mbar_wait(sb + BE + 8 * s, ph);
      if (elect_one()) { mbar_expect(sb + BF + 8 * s, B_SLOT); tma3d(sb + s * B_SLOT, &p.tmW, 0, (it < 10 ? it : it - 10) * 64, (it < 10 ? 12 : 0) + cb * 3, sb + BF + 8 * s); }
      if (++s == NS) { s = 0; ph ^= 1; }
    }
  } else if (warp < 4) {
    const uint32_t tag = load_epoch(p, 128 + cb, lane) + 1;
    const uint64_t db = mkdesc(sb + ONES, 128, 128, 0);
    uint32_t* dst = p.scr->colsum + cb * 192 + warp * 16 + (lane >> 2);
    if ((lane & 3) == 0) {
#pragma unroll 1
      for (int j = 0; j < 12; j++) st_relaxed(dst + (j < 6 ? 768 : 0) + ((j % 6) >> 1) * 64 + (j & 1) * 8, 0);
    }
    int s = 0, ph = 0;
#pragma unroll 1
    for (int part = 0; part < 2; part++) {
      float d[12];
#pragma unroll
      for (int i = 0; i < 12; i++) d[i] = 0.f;
#pragma unroll 1
      for (int it = 0; it < 10; it++) {
        mbar_wait(sb + BF + 8 * s, ph);
        const uint64_t da = mkdesc(sb + s * B_SLOT, 8192, 1024, 1);
        WG_FENCE();
#pragma unroll
        for (int j = 0; j < 12; j++) wgmma_colsum(d + 4 * (j % 3), da + (j % 3) * 512 + (j / 3) * 128, db);
        WG_COMMIT();
        WG_WAIT(1);
        mbar_arrive_if(sb + BE + 8 * (s == 0 ? NS - 1 : s - 1), threadIdx.x == 0 && (it | part) != 0);
        if (++s == NS) { s = 0; ph ^= 1; }
      }
      WG_WAIT(0);
      acc_fence<12>(d);
      if ((lane & 3) == 0) {
#pragma unroll
        for (int j = 0; j < 6; j++) st_relaxed(dst + (part ? 0 : 768) + (j >> 1) * 64 + (j & 1) * 8, tagged(d[2 * j], tag8(tag)));
      }
      STAMPW(1 + part);
    }
    if (threadIdx.x == 0) *(volatile uint32_t*)&p.scr->epoch[128 + cb] = tag;
  }
}

__global__ void __launch_bounds__(512, 1) fused_kernel(const __grid_constant__ Params p) {
  extern __shared__ __align__(1024) uint8_t smem[];
  const int warp = __shfl_sync(0xffffffff, (int)(threadIdx.x >> 5), 0);
  const int lane = threadIdx.x & 31;
  const uint32_t sb = __shfl_sync(0xffffffff, (uint32_t)__cvta_generic_to_shared(smem), 0);
  const uint32_t tstart = clock();
  if (elect_one()) {
    if (warp < 5) asm volatile("prefetch.tensormap [%0];" ::"l"(&p.tmX + warp) : "memory");
    mbar_init(sb + OFF_BAR + 8 * warp, 1); mbar_init(sb + OFF_BAR + 128 + 8 * warp, 1);
    if (warp != 3) mbar_init(sb + OFF_BAR + 256 + 8 * warp, (0x2224444444441111ull >> (4 * warp)) & 15);
    mbar_init(sb + OFF_BAR + 384 + 8 * warp, 2);
    if (warp < 2) mbar_init(sb + BAR_XL + 8 * warp, 1);
    asm volatile("fence.mbarrier_init.release.cluster;" ::: "memory");
  }
  int b = blockIdx.x;
  if (p.by_smid) asm volatile("mov.u32 %0, %%smid;" : "=r"(b));
  b = __shfl_sync(0xffffffff, b, 0);
  const int tp = b >> 1, t7 = (tp - 32) / 7;
  const int lin = tp < 32 ? ((tp & 7) ? (tp & 7) * 16 : 8) + (tp >> 3) * 2 + (b & 1)
                          : (tp < 60 ? (tp - 31 - t7 * 7) * 16 + 8 + t7 * 2 + (b & 1) : (tp < 62 ? -1 : b - 124));
  if (lin < 0) { helper_cta(p, sb, b & 3, warp, lane TSA); return; }
  const int cb = ((lin >> 4) & 1) * 2 + ((lin >> 3) & 1), rb = (lin >> 5) * 8 + (lin & 7);
  const int rot = ROT ? (MAP ? rb & 24 : rb & 28) : 0;
  const int chb = (cb >> 1) * 320 + rb * 2 + (cb & 1);
  if (elect_one()) {
    if (warp == 0) { mbar_expect(sb + BAR_AF, A_SLOT); tma2d(sb + OFF_A, &p.tmX, 0, rb * 64, sb + BAR_AF); }
    if (warp == 10) { mbar_expect(sb + BAR_BF, B_SLOT); tma3d(sb + OFF_B, &p.tmW, 0, 0, 12 + cb * 3, sb + BAR_BF); }
  }
  if (sb & 1023) die();
  __syncthreads();

  if (warp >= 12) {
    asm volatile("setmaxnreg.dec.sync.aligned.u32 32;");
    const uint8_t* z2s = p.scr->z2 + (size_t)cb * 32 * B_SLOT;
    const char* wq = (const char*)p.wsp + (rb * 64 + cb * 16 + (lane >> 1)) * (kS * 2) + (lane & 1) * 128;
    if (warp == 12) {
      int s = 1, ph = 1, nx = 1;
#pragma unroll 1
      for (int it = 1; it < 20; it++) {
        if (it >= 5) mbar_wait<true>(sb + BAR_BE + 8 * s, ph);
        const int xt = XL ? min(10, it + XL) : min(10, it + 1);
#pragma unroll 1
        for (; nx < xt; nx++)
          if (elect_one()) { mbar_expect(sb + BAR_AF + 8 * nx, A_SLOT); tma2d(sb + OFF_A + nx * A_SLOT, &p.tmX, nx * 64, rb * 64, sb + BAR_AF + 8 * nx); }
        if (elect_one()) {
          mbar_expect(sb + BAR_BF + 8 * s, B_SLOT);
          tma3d(sb + OFF_B + s * B_SLOT, &p.tmW, 0, (it < 10 ? it : it - 10) * 64, (it < 10 ? 12 : 0) + cb * 3, sb + BAR_BF + 8 * s);
        }
        if (XL == 0 && it == 4) {
#pragma unroll 1
          for (; nx < 10; nx++)
            if (elect_one()) { mbar_expect(sb + BAR_AF + 8 * nx, A_SLOT); tma2d(sb + OFF_A + nx * A_SLOT, &p.tmX, nx * 64, rb * 64, sb + BAR_AF + 8 * nx); }
          bar_arrive(NB_KF, 160);
        }
        STAMP2(32 + it);
        if (++s == 5) { s = 0; ph ^= 1; }
      }
      const uint32_t ztarget = (load_epoch(p, lin, lane) + 1) * 128;
#pragma unroll 1
      for (int i = 0; i < LEAD; i++) {
        mbar_wait<true>(sb + BAR_AE + 8 * (3 + i), 0);
        if (elect_one()) { mbar_expect(sb + BAR_AF + 8 * (3 + i), A_SLOT); tma2d(sb + OFF_A + (3 + i) * A_SLOT, &p.tmWsp, ((i + rot) & 31) * 64, rb * 64, sb + BAR_AF + 8 * (3 + i)); }
      }
      mbar_wait<true>(sb + BAR_ZP, 0);
      if (ZPD) { uint32_t tp = clock(); pace(tp, ZPD); }
      poll_counter<true>(p.scr->cnt + CNT_Z, ztarget);
      STAMP(24);
#pragma unroll 1
      for (int it = 0; it < 32; it++) {
        mbar_wait<true>(sb + BAR_BE + 8 * s, ph);
        if (elect_one()) {
          mbar_expect(sb + BAR_BF + 8 * s, B_SLOT);
          bulk_g2s(sb + OFF_B + s * B_SLOT, z2s + ((it + rot) & 31) * B_SLOT, B_SLOT, sb + BAR_BF + 8 * s);
        }
        if (it == 0) STAMP(22);
        if (HE && it == HE - 1 && elect_one()) mbar_arrive(sb + BAR_ZG);
        const int ia = it + LEAD - 1, sa = (ia + 3) & 7;
        if (it >= 1 && ia < 32) {
          mbar_wait<true>(sb + BAR_AE + 8 * sa, (ia >> 3) & 1);
          if (elect_one()) { mbar_expect(sb + BAR_AF + 8 * sa, A_SLOT); tma2d(sb + OFF_A + sa * A_SLOT, &p.tmWsp, ((ia + rot) & 31) * 64, rb * 64, sb + BAR_AF + 8 * sa); }
        }
        if (HOLD < 27) mbar_arrive_if(sb + BAR_HOLD, it == HOLD + 5 && lane == 0);
        STAMP2(52 + it);
        if (++s == 5) { s = 0; ph ^= 1; }
      }
      mbar_wait<true>(sb + BAR_WO, 0);
      acquire_fence();
      s = 0;
#pragma unroll 1
      for (int it = 0; it < 12; it++) {
        if (it < 6) mbar_wait<true>(sb + BAR_BE + 8 * ((0x110443 >> (4 * it)) & 7), it < 3 ? 1 : 0);
        else mbar_wait<true>(sb + BAR_WE + 8 * s, 0);
        if (HOLD >= 27 && HOLD < 32) mbar_arrive_if(sb + BAR_HOLD, it == (HOLD <= 28 ? 0 : (HOLD == 29 ? 1 : HOLD - 27)) && lane == 0);
        if (elect_one()) {
          mbar_expect(sb + BAR_WF + 8 * s, W_SLOT);
          bulk_g2s(sb + OFF_B + (s >= 3 ? s - 3 : s + 3) * W_SLOT, p.scr->wo + (size_t)(cb * 12 + g3_block(cb, it)) * W_SLOT, W_SLOT, sb + BAR_WF + 8 * s);
        }
        STAMP2(84 + it);
        if (++s == 6) s = 0;
      }
      mbar_wait<true>(sb + BAR_WE, 1);
    } else if (warp == 13) {
      const uint32_t tag = load_epoch(p, lin, lane) + 1;
      if (elect_one()) reset_sector(&p.scr->hflag[rb * 32 + cb * 8]);
      if (lane == 0) sts32(sb + OFF_TAG, tag8(tag));
      mbar_wait(sb + BAR_AF + 8 * CSI, 0);
      if (CSD) { uint32_t tp = clock(); pace(tp, CSD); }
      gather_colsum(p, sb, 0, cb, tag8(tag), lane);
      STAMP(27);
      bar_sync(NB_Z, 160);
      if (elect_one()) {
        mbar_arrive(sb + BAR_ZG);
        bulk_s2g((void*)(z2s + rb * B_SLOT), sb + OFF_A, B_SLOT);
        bulk_commit_wait();
        mbar_arrive(sb + BAR_ZP);
        STAMPE(58);
        if (XP & 16) red_relaxed(p.scr->cnt + CNT_Z); else red_release(p.scr->cnt + CNT_Z);
      }
      __syncwarp();
      STAMP(28);
      {
        uint32_t tp = clock() + PF_W;
#pragma unroll 1
        for (int i = PF_N; i < 16; i++) {
          pace(tp, PF_D);
          prefetch_l2(wq + ((i + (rot >> 1)) & 15) * 256);
          if (i == LKI) bar_sync(NB_KL, 160);
          if ((i == LKI || i == LKI + 1) && elect_one()) {
            kv_store(p, sb + OFF_A + 8 * A_SLOT + (i - LKI) * 4096, rb * 2 + (cb & 1), (cb >> 1) * 5 + 3 + i - LKI);
            bulk_commit_wait();
            if (i > LKI) red_relaxed(p.scr->cnt + CNT_KV + 2 + (cb >> 1));
          }
          __syncwarp();
          if (i == LKI + 1) STAMP(59);
        }
      }
      poll_counter(p.scr->cnt + CNT_KV + 2 + (cb >> 1), tag * 64);
      if (elect_one()) mbar_arrive(sb + BAR_KV2);
      STAMP(34);
      const uint8_t* hs = p.scr->h + (size_t)rb * 12 * A_SLOT;
#pragma unroll 1
      for (int i = 0; i < 3; i++) {
        mbar_wait(sb + BAR_HR - 16 + 8 * i, 0);
        if (elect_one()) bulk_s2g((void*)(hs + (cb * 3 + i) * A_SLOT), sb + OFF_A + i * A_SLOT, A_SLOT);
      }
      if (elect_one()) {
        if (HA == 0) st_relaxed(&p.scr->hflag[rb * 32 + cb * 8], tag);
        bulk_commit_wait();
        if (HA == 1) st_relaxed(&p.scr->hflag[rb * 32 + cb * 8], tag);
        mbar_arrive(sb + BAR_ZP);
      }
      __syncwarp();
      STAMP(20);
      poll_flags4(p.scr->hflag + rb * 32, tag, lane);
      if (HD) { uint32_t tp = clock(); pace<false>(tp, HD); }
      STAMP(37);
#pragma unroll 1
      for (int it = 3; it < 12; it++) {
        const int s = it < 9 ? it : it - 9;
        if (it == 9) { if (BPART) bar_sync(NB_PC, 288); else mbar_wait(sb + BAR_WE + 16, 0); }
        if (elect_one()) { mbar_expect(sb + BAR_AF + 8 * s, A_SLOT); bulk_g2s(sb + OFF_A + s * A_SLOT, hs + g3_block(cb, it) * A_SLOT, A_SLOT, sb + BAR_AF + 8 * s); }
      }
      STAMP(21);
    } else if (warp == 14) {
      const uint32_t tag = load_epoch(p, lin, lane) + 1;
      const int tb = rb * 2 + (cb & 1), u0 = (cb >> 1) * 5;
      const uint32_t ks = sb + OFF_CV + CV_SZ, par = __shfl_sync(0xffffffff, tag, 0);
      {
        uint32_t tp = tstart;
        pace(tp, TP_T);
        const char* q = (const char*)p.ssmk + chb * 4096 + lane * 128;
        prefetch_l2(q); prefetch_l2(q + 64 * 4096);
      }
      if (ST_YIELD) mbar_wait2(sb + BAR_XS, 0, sb + BAR_ST, 0);
      bar_sync(NB_KU, 160);
      if (elect_one()) { kv_store(p, ks, tb, u0); kv_store(p, ks + 4096, tb, u0 + 1); bulk_commit_wait(); red_relaxed(p.scr->cnt + CNT_KV + (cb >> 1)); }
      __syncwarp();
      STAMP(35);
      bar_sync(NB_KU2, 160);
      if (elect_one()) { kv_store(p, ks + 8192, tb, u0 + 2); bulk_commit_wait(); }
      __syncwarp();
      zero_pads(ks, lane);
      bar_arrive(NB_G1D, 64);
      STAMP(30);
      {
        uint32_t tp = clock();
        const size_t o = (size_t)(tb * 32 + lane) * (kD * 2) + (u0 + 3) * 128;
        const char* r = (const char*)p.wout + (rb * 24 + min(lane, 23)) * (kD * 2) + cb * 320;
        const char* q = (const char*)p.ssmk + (chb + 128) * 4096 + lane * 128;
#pragma unroll 1
        for (int i = 0; i < 10; i++) {
          pace(tp, 500);
          prefetch_l2(i < 3 ? q + i * 64 * 4096 : (i < 7 ? (const char*)((i & 1) ? p.k : p.v) + o + ((i - 3) >> 1) * 128 : r + (i - 7) * 128));
        }
      }
      mbar_wait(sb + BAR_YT, 0);
      conv_service(p, sb, 0, chb + 64, par, lane, NoHook());
      bar_sync(NB_CD, 64);
      if (elect_one()) { if (YTAG == 1) red_relaxed(p.scr->cnt + CNT_Y + (cb >> 1)); else if (!YTAG) red_release(p.scr->cnt + CNT_Y + (cb >> 1)); }
      STAMP(47);
      if (YTAG < 2) poll_counter(p.scr->cnt + CNT_Y + (cb >> 1), tag * 64);
      else mbar_wait(sb + BAR_WE + 40, 0);
      if (YD) { uint32_t tp = clock(); pace<false>(tp, YD); }
      if (elect_one()) {
        mbar_expect(sb + BAR_YT, 20480);
#pragma unroll 1
        for (int i = 0; i < 4; i++) tma2d(sb + OFF_CV + i * 5120, &p.tmY, rb * 64, cb * 160 + i * 40, sb + BAR_YT);
      }
      if (lane == 0) *(volatile uint32_t*)&p.scr->epoch[lin] = tag;
      STAMP(23);
    } else {
      const uint32_t tag = load_epoch(p, lin, lane) + 1;
      mbar_wait(sb + BAR_AF + 72, 0);
      if (XSD) { uint32_t tp = clock(); pace(tp, XSD); }
      {
        const uint32_t t8 = tag8(tag);
        const uint4 u = poll3<false, PP, uint4>([&]() { return ld_ll4(&p.scr->xstat[rb * 64 + lane * 2]); },
                                                [&](const uint4& v) { return (((v.x ^ t8) | (v.y ^ t8) | (v.z ^ t8) | (v.w ^ t8)) & 255u) == 0; });
        sts128(sb + OFF_XS + lane * 16, u.x, u.y, u.z, u.w);
      }
      __syncwarp();
      if (lane == 0) mbar_arrive(sb + BAR_XS);
      STAMP(25);
      const uint32_t par = __shfl_sync(0xffffffff, tag, 0);
      bar_sync(NB_G1D, 64);
      poll_counter(p.scr->cnt + CNT_KV + (cb >> 1), tag * 64);
      convx_issue(p, sb, 1, chb);
      convx_issue(p, sb, 0, chb + 64);
#pragma unroll 1
      for (int h = 1; h >= 0; h--) convx_finish(p, sb, h, chb + 64 - 64 * h, 0, par, lane);
      STAMP(48);
      gather_colsum(p, sb, 1, cb, tag8(tag), lane);
      STAMP(38);
      mbar_wait(sb + BAR_YT, 0);
      conv_service(p, sb, 1, chb, par, lane, [&]() {
        bar_sync(NB_WO, 160);
        if (elect_one()) red_release(p.scr->cnt + CNT_WO + cb);
        STAMP(49);
        poll_counter(p.scr->cnt + CNT_WO + cb, tag * 32);
        if (elect_one()) mbar_arrive(sb + BAR_WO);
        STAMP(46);
      });
      bar_arrive(NB_CD, 64);
    }
  } else if (warp >= 8) {
    const int w = warp & 3;
    {
      const int tid = tid_now();
      uint2* xs = &p.scr->xstat[rb * 64 + cb * 16 + (tid >> 3)];
      if ((tid & 7) == 0) st_ll2(xs, 0, 0);
      const uint32_t epoch = load_epoch(p, lin, lane);
      float s = 0.f, q = 0.f;
#pragma unroll 1
      for (int i = 0; i < 10; i++) {
        mbar_wait(sb + BAR_AF + 8 * i, 0);
        const uint4 x4 = lds128(sb + OFF_A + i * A_SLOT + cb * 2048 + tid * 16);
        const uint32_t u[4] = {x4.x, x4.y, x4.z, x4.w};
#pragma unroll
        for (int e = 0; e < 4; e++) { const float a = bf_lo(u[e]), c = bf_hi(u[e]); s += a + c; q = fmaf(a, a, q); q = fmaf(c, c, q); }
      }
#pragma unroll
      for (int o = 1; o <= 4; o <<= 1) { s += __shfl_xor_sync(0xffffffff, s, o); q += __shfl_xor_sync(0xffffffff, q, o); }
      const float m = s * (1.f / kD);
      const float r = rsqrtf(fmaxf(fmaf(-m, m, q * (1.f / kD)), 0.f) + 1e-5f);
      if ((tid & 7) == 0) st_ll2(xs, tagged(m, tag8(epoch + 1)), tagged(r, tag8(epoch + 1)));
      STAMPW(12); TR(70);
      fence_async_smem();
    }
    asm volatile("setmaxnreg.inc.sync.aligned.u32 160;");
    const unsigned short* bp = (const unsigned short*)p.bsp + rb * 64 + w * 16 + (lane >> 2);
    const uint32_t bias = bp[0] | ((uint32_t)bp[8] << 16);
    float d[96];
    uint32_t z[48];
    {
      const uint64_t db = mkdesc(sb + OFF_B, 8192, 1024, 1);
#pragma unroll
      for (int i = 0; i < 96; i++) d[i] = 0.f;
      bar_sync(NB_G1, 256);
      TR(71);
      if (PAUSE) {
        gemm_seg<192, 3>(d, sb, db, 0, SEG1, 0, 0, tid_now() == 0, 0 TSA);
        STAMPW(54); TR(72);
        mbar_wait(sb + (PAUSE == 1 ? BAR_ZG : BAR_ZP), 0);
        gemm_seg<192, 3>(d, sb, db, SEG1, 10, SEG1 % 5, SEG1 == 5, tid_now() == 0, 1 TSA);
      } else {
        gemm_seg<192, 3>(d, sb, db, 0, 10, 0, 0, tid_now() == 0, 0 TSA);
      }
      mbar_arrive_if(sb + BAR_YT, tid_now() == 0);
      STAMPW(14); TR(74);
      mbar_wait2(sb + BAR_XS, 0, sb + BAR_ST + 8, 0);
      const uint32_t xa1 = sb + OFF_XS + (w * 16 + (lane >> 2)) * 8;
      gelu_tile<24, false>(d, z, nullptr, sb + OFF_CS + (lane & 3) * 8, lds64f(xa1), lds64f(xa1 + 64), sb + BAR_XS);
    }
#pragma unroll
    for (int j = 0; j < 96; j++) d[j] = (j & 2) ? bf_hi(bias) : bf_lo(bias);
    STAMPW(15); TR(76);
    gemm_seg<192, 1>(d, sb, mkdesc(sb + OFF_B, 8192, 1024, 1), 0, 32, 0, 0, tid_now() == 0, 1 TSA);
    STAMPW(16); TR(77);
    {
      const int l2 = tid_now() & 31;
      const uint32_t ha = swz_base(sb + OFF_A, w, l2);
      const bool tg = (l2 & 3) == (l2 >> 3);
      const uint32_t tm = tg ? ~1u : ~0u, tb = tg ? lds32<0>(sb + OFF_TAG) & 1 : 0;
#pragma unroll
      for (int j = 0; j < 24; j += 2) {
#pragma unroll
        for (int e = 0; e < 4; e++) z[2 * j + e] = hmul2(z[2 * j + e], pack2(d[4 * j + 2 * e], d[4 * j + 2 * e + 1]));
        stsm4((ha ^ ((j & 7) * 16)) + (j >> 3) * A_SLOT, (z[2 * j] & tm) | tb, (z[2 * j + 1] & tm) | tb, z[2 * j + 2], z[2 * j + 3]);
        if ((j & 7) == 6 && (HPC || j == 22)) {
          fence_async_smem();
          __syncwarp();
          if (!HPC) { mbar_arrive_if(sb + BAR_HR - 16, l2 == 0); mbar_arrive_if(sb + BAR_HR - 8, l2 == 0); }
          mbar_arrive_if(sb + BAR_HR - 16 + (j >> 3) * 8, l2 == 0);
        }
      }
    }
    STAMPW(17); TR(78);
    const int t3 = tid_now();
    if (BPART) {
      mbar_wait(sb + BAR_HR, 0);
      gemm_seg<160, 4>(d, sb, mkdesc(sb + OFF_B, 2560, 128, 0), 0, 3, 0, 0, t3 == 0, 0 TSA);
      TR(79);
      bar_sync(NB_C, 128);
      mbar_wait(sb + BAR_ZP, 1);
#pragma unroll
      for (int j = 0; j < 10; j++)
        sts128(sb + OFF_A + j * 2048 + t3 * 16, pack2(d[8 * j], d[8 * j + 1]), pack2(d[8 * j + 2], d[8 * j + 3]), pack2(d[8 * j + 4], d[8 * j + 5]),
               pack2(d[8 * j + 6], d[8 * j + 7]));
      bar_sync(NB_C, 128);
      mbar_arrive_if(sb + BAR_PART, t3 == 0);
      STAMPW(45); TR(80);
    }
    {
      const uint32_t par = __shfl_sync(0xffffffff, lds32<0>(sb + OFF_TAG), 0), a = sb + OFF_A + w * 2048 + val_off(t3 & 31);
      const uint8_t* hs = p.scr->h + (size_t)rb * 12 * A_SLOT + w * 2048;
      const uint32_t rt = sb + OFF_RT + 8 * w;
#pragma unroll 1
      for (int it = 3; it < 12; it++) {
        const int s = it < 9 ? it : it - 9;
        mbar_wait(sb + BAR_AF + 8 * s, 1);
        validate<2>(a + s * A_SLOT, par, rt, [&]() { bulk_g2s(sb + OFF_A + s * A_SLOT + w * 2048, hs + g3_block(cb, it) * A_SLOT, 2048, rt); });
        if (elect_one()) mbar_arrive(sb + BAR_HV + 8 * (it - 3));
        if (it == 3) STAMPW(26);
      }
      if (YTAG) {
        const int l = t3 & 31;
        mbar_wait(sb + BAR_YT, 1);
        validate<5>(sb + OFF_CV + w * 5120 + (l >> 2) * 128 + ((2 * (l & 3)) ^ (l >> 2)) * 16, par, rt, [&]() { tma2d(sb + OFF_CV + w * 5120, &p.tmY, rb * 64, cb * 160 + w * 40, rt); });
        bar_sync(NB_C, 128);
        mbar_arrive_if(sb + BAR_PART, t3 == 0);
        STAMPW(57);
      }
    }
  } else {
    const int h = warp >> 2, w = warp & 3;
    Taps k;
    asm volatile("setmaxnreg.inc.sync.aligned.u32 160;");
    if (h == 0) {
      uint4* zs = &p.scr->zstat[rb * 128 + w * 8 + (lane >> 2)];
      if ((lane & 3) == 0) st_ll4(zs + cb * 32, 0, 0, 0, 0);
      float d[96];
      uint32_t z[48];
#pragma unroll
      for (int i = 0; i < 96; i++) d[i] = 0.f;
      gemm_seg<192, 0>(d, sb, mkdesc(sb + OFF_B, 8192, 1024, 1), 0, 10, 0, 0, tid_now() == 0, 0 TSA, [&]() { if (!GATE) bar_arrive(NB_G1, 256); });
      STAMPW(1); TR(0);
      const int tid = tid_now(), lane = tid & 31, g = lane >> 2, t = lane & 3;
      mbar_wait2(sb + BAR_XS, 0, sb + BAR_ST, 0);
      STAMPW(52); TR(1);
      const uint32_t xa1 = sb + OFF_XS + (w * 16 + g) * 8;
      const uint32_t tag = lds32<0>(sb + OFF_TAG);
      const float2 s0 = lds64f(xa1), s1 = lds64f(xa1 + 64);
      float st[4];
      gelu_tile<24, true>(d, z, st, sb + OFF_CS + 768 + t * 8, s0, s1, 0);
      TR(2);
      float2 sq = quad_sum(st, t);
      if (t < 2) st_ll2((uint2*)(zs + cb * 32) + t, tagged(sq.x, tag), __float_as_uint(sq.y));
      if (GATE) bar_arrive(NB_G1, 256);
      STAMPW(2); TR(3);
      if (ZW) { uint32_t tp = clock(); pace<false>(tp, ZW); }
      const uint4 u = poll3<false, PP, uint4>([&]() { return ld_ll4(zs + t * 32); }, [&](const uint4& v) { return (((v.x ^ tag) | (v.z ^ tag)) & 255u) == 0; });
      STAMPW(3); TR(10);
      st[0] = __uint_as_float(u.x); st[1] = __uint_as_float(u.y); st[2] = __uint_as_float(u.z); st[3] = __uint_as_float(u.w);
      sq = quad_sum(st, t);
      const float ca = 0.5f * ((t & 1) ? s1.y : s0.y), ma = sq.x * (1.f / 768.f);
      const float ra = ca * rsqrtf(fmaf(fmaxf(fmaf(-ma, ma, sq.y * (1.f / 768.f)), 0.f), ca * ca, 1e-5f));
      const uint32_t r2 = pack2(ra, ra);
      const float na = -ma * bf_lo(r2);
      const uint32_t n2 = pack2(na, na), r2o = __shfl_xor_sync(0xffffffff, r2, 1), n2o = __shfl_xor_sync(0xffffffff, n2, 1);
      const uint32_t fr[2] = {(t & 1) ? r2o : r2, (t & 1) ? r2 : r2o}, fn[2] = {(t & 1) ? n2o : n2, (t & 1) ? n2 : n2o};
      const uint32_t za = swz_base(sb + OFF_A, w, lane);
      TR(11);
      mbar_wait(sb + BAR_AE + 16, 0);
      TR(12);
#pragma unroll
      for (int j = 0; j < 24; j += 2)
        stsm4((za ^ ((j & 7) * 16)) + (j >> 3) * A_SLOT, hfma2(z[2 * j], fr[0], fn[0]), hfma2(z[2 * j + 1], fr[1], fn[1]), hfma2(z[2 * j + 2], fr[0], fn[0]), hfma2(z[2 * j + 3], fr[1], fn[1]));
      TR(14);
      fence_async_smem();
      bar_arrive(NB_Z, 160);
      STAMPW(4); TR(15);
      load_taps(k, p, chb + 64, tid);
    } else {
      if (w == 0) zero_pads(sb + OFF_CV, lane);
      const uint32_t epoch = load_epoch(p, lin, lane);
      const int t0 = (rb * 2 + (cb & 1)) * 32 + w * 8, c0 = (cb >> 1) * 320 + lane * 2;
      const __nv_bfloat16* kp = p.k + (size_t)(t0 - 3) * kD + c0;
      const __nv_bfloat16* vp = p.v + (size_t)t0 * kD + c0;
      const __nv_bfloat16* sp = p.shift + c0 * 4;
      const uint32_t oa = sb + OFF_CV + CV_SZ + kv_stage_addr(w, lane);
      if (XL == 0) bar_sync(NB_KF, 160);
      uint32_t tp = tstart;
      pace(tp, KV_T0);
      KvRegs n0, n1;
      uint32_t o[8];
      kv_load(n0, kp, vp, sp, t0 > 0);
      kv_load(n1, kp + 64, vp + 64, sp + 256, t0 > 0);
      const uint32_t tm = w >= 2 ? ~1u : ~0u, tb = w >= 2 ? (epoch + 1) & 1 : 0;
      kv_calc(n0, o);
      kv_put(o, oa, tm, tb);
      kv_calc(n1, o);
      kv_put(o, oa + 4096, tm, tb);
      fence_async_smem();
      bar_arrive(NB_KU, 160);
      TR(0);
      if (KV2T) pace(tp, KV2T);
      kv_load(n0, kp + 128, vp + 128, sp + 512, t0 > 0);
      load_taps(k, p, chb, tid_now());
      kv_calc(n0, o);
      kv_put(o, oa + 8192, tm, tb);
      fence_async_smem();
      bar_arrive(NB_KU2, 160);
      STAMPW(13); TR(1);
    }
    {
      const int tid = tid_now();
      conv_worker(p, k, sb, h, chb + 64 - 64 * h, w, tid & 31, tid, rb, cb TSA);
    }
    float d[40];
    const int t3 = tid_now();
    const uint32_t o0 = (rb * 64 + w * 16 + ((t3 & 31) >> 2)) * kD + cb * 160 + h * 80;
    uint32_t xw[2][10];
    TR(60);
    if (BPART) {
      mbar_wait(sb + BAR_PART, 0);
      TR(61);
#pragma unroll
      for (int j = 0; j < 5; j++) {
        const uint4 v = lds128(sb + OFF_A + (h * 5 + j) * 2048 + t3 * 16);
        d[8 * j] = bf_lo(v.x); d[8 * j + 1] = bf_hi(v.x); d[8 * j + 2] = bf_lo(v.y); d[8 * j + 3] = bf_hi(v.y);
        d[8 * j + 4] = bf_lo(v.z); d[8 * j + 5] = bf_hi(v.z); d[8 * j + 6] = bf_lo(v.w); d[8 * j + 7] = bf_hi(v.w);
      }
      fence_async_smem();
      bar_arrive(NB_PC, 288);
    } else {
#pragma unroll
      for (int j = 0; j < 40; j++) d[j] = 0.f;
    }
    TR(62);
    gemm_seg<80, 2>(d, sb, mkdesc(sb + OFF_B + h * 1280, 2560, 128, 0), BPART ? 3 : 0, 12, BPART ? 3 : 0, 0, t3 == 0, BPART TSA, NoHook(), [&]() { final_load_x(xw, p.x + o0, t3 & 3); });
    STAMPW(h ? 18 : 10);
    TR(63);
    const int l3 = tid_now() & 31;
    const uint32_t xs_addr = sb + OFF_XS + (w * 16 + (l3 >> 2)) * 8;
    uint32_t gt[20];
    final_gate(d, gt, xw, lds64f(xs_addr), lds64f(xs_addr + 64));
    STAMPW(h ? 44 : 9);
    TR(64);
    if (YTAG) mbar_wait(sb + BAR_PART, BPART); else mbar_wait(sb + BAR_YT, 1);
    TR(65);
    final_out(gt, xw, sb + OFF_CV + h * 10240, p.out + o0, w, l3);
    TR(66);
    mbar_arrive_if(sb + BAR_WE, t3 == 0);
  }
}

typedef CUresult (*EncodeFn)(CUtensorMap*, CUtensorMapDataType, cuuint32_t, void*, const cuuint64_t*, const cuuint64_t*, const cuuint32_t*,
                             const cuuint32_t*, CUtensorMapInterleave, CUtensorMapSwizzle, CUtensorMapL2promotion, CUtensorMapFloatOOBfill);

void encode(EncodeFn fn, CUtensorMap* m, const void* ptr, int rank, const cuuint64_t* dims, const cuuint64_t* strides, const cuuint32_t* box,
            CUtensorMapSwizzle swz = CU_TENSOR_MAP_SWIZZLE_128B) {
  const cuuint32_t es[3] = {1, 1, 1};
  fn(m, CU_TENSOR_MAP_DATA_TYPE_BFLOAT16, rank, const_cast<void*>(ptr), dims, strides, box, es, CU_TENSOR_MAP_INTERLEAVE_NONE,
     swz, CU_TENSOR_MAP_L2_PROMOTION_L2_128B, CU_TENSOR_MAP_FLOAT_OOB_FILL_NONE);
}

}

extern "C" void kernel_launch(void* const* d_in, const int* in_sizes, int n_in, void* d_out, int out_size) {
  (void)in_sizes; (void)n_in; (void)out_size;
  static EncodeFn enc = nullptr;
  static Scratch* scr = nullptr;
  static int sms = 0;
  if (!enc) {
    void* fn = nullptr;
    cudaDriverEntryPointQueryResult qr;
    cudaGetDriverEntryPoint("cuTensorMapEncodeTiled", &fn, cudaEnableDefault, &qr);
    enc = (EncodeFn)fn;
    cudaFuncSetAttribute(fused_kernel, cudaFuncAttributeMaxDynamicSharedMemorySize, SMEM_BYTES);
    cudaGetSymbolAddress((void**)&scr, g_scr);
    int dev = 0;
    cudaGetDevice(&dev);
    cudaDeviceGetAttribute(&sms, cudaDevAttrMultiProcessorCount, dev);
  }
  Params p;
  p.scr = scr;
  p.by_smid = sms == 132;
  p.x = (const __nv_bfloat16*)d_in[0];
  p.k = (const __nv_bfloat16*)d_in[1];
  p.v = (const __nv_bfloat16*)d_in[2];
  p.shift = (const __nv_bfloat16*)d_in[3];
  p.ssmk = (const __nv_bfloat16*)d_in[4];
  p.ssmD = (const __nv_bfloat16*)d_in[5];
  p.wsp = (const __nv_bfloat16*)d_in[8];
  p.bsp = (const __nv_bfloat16*)d_in[9];
  p.wout = (const __nv_bfloat16*)d_in[10];
  p.out = (__nv_bfloat16*)d_out;
  {
    const cuuint64_t dims[2] = {kD, kS}, st[1] = {kD * 2};
    const cuuint32_t box[2] = {64, 64};
    encode(enc, &p.tmX, d_in[0], 2, dims, st, box);
  }
  {
    const cuuint64_t dims[3] = {64, kD, kF / 64}, st[2] = {kF * 2, 128};
    const cuuint32_t box[3] = {64, 64, 3};
    encode(enc, &p.tmW, d_in[7], 3, dims, st, box);
  }
  {
    const cuuint64_t dims[2] = {kS, kS}, st[1] = {kS * 2};
    const cuuint32_t box[2] = {64, 64};
    encode(enc, &p.tmWsp, d_in[8], 2, dims, st, box);
  }
  {
    const cuuint64_t dims[2] = {kS, kD}, st[1] = {kS * 2};
    const cuuint32_t box[2] = {64, 40};
    encode(enc, &p.tmY, scr->y, 2, dims, st, box);
  }
  {
    const cuuint64_t dims[3] = {1024, kD / 2, 4}, st[2] = {8192, 2048};
    const cuuint32_t box[3] = {16, 32, 4};
    encode(enc, &p.tmKV, scr->kvx, 3, dims, st, box, CU_TENSOR_MAP_SWIZZLE_32B);
  }
  fused_kernel<<<132, 512, SMEM_BYTES, cudaStreamPerThread>>>(p);
}
```

```cpp
#include <cuda_runtime.h>
#include <cuda.h>
#include <cuda_bf16.h>
#include <stdint.h>

template <int N> struct WG;
template <> struct WG<16> {
  static __device__ __forceinline__ void rs(float* d, const uint32_t* a, uint64_t db) {
    asm volatile("{\n.reg .pred p;\nsetp.ne.b32 p, 1, 0;\nwgmma.mma_async.sync.aligned.m64n16k16.f32.bf16.bf16 {"
      "%0, %1, %2, %3, %4, %5, %6, %7"
      "}, {%8, %9, %10, %11}, %12, p, 1, 1, 0;\n}\n"
      :
      "+f"(d[0]), "+f"(d[1]), "+f"(d[2]), "+f"(d[3]), "+f"(d[4]), "+f"(d[5]), "+f"(d[6]), "+f"(d[7])
      : "r"(a[0]), "r"(a[1]), "r"(a[2]), "r"(a[3]), "l"(db));
  }
};
template <> struct WG<32> {
  static __device__ __forceinline__ void rs(float* d, const uint32_t* a, uint64_t db) {
    asm volatile("{\n.reg .pred p;\nsetp.ne.b32 p, 1, 0;\nwgmma.mma_async.sync.aligned.m64n32k16.f32.bf16.bf16 {"
      "%0, %1, %2, %3, %4, %5, %6, %7, %8, %9, %10, %11, %12, %13, %14, %15"
      "}, {%16, %17, %18, %19}, %20, p, 1, 1, 0;\n}\n"
      :
      "+f"(d[0]), "+f"(d[1]), "+f"(d[2]), "+f"(d[3]), "+f"(d[4]), "+f"(d[5]), "+f"(d[6]), "+f"(d[7]),
      "+f"(d[8]), "+f"(d[9]), "+f"(d[10]), "+f"(d[11]), "+f"(d[12]), "+f"(d[13]), "+f"(d[14]), "+f"(d[15])
      : "r"(a[0]), "r"(a[1]), "r"(a[2]), "r"(a[3]), "l"(db));
  }
};
template <> struct WG<48> {
  static __device__ __forceinline__ void rs(float* d, const uint32_t* a, uint64_t db) {
    asm volatile("{\n.reg .pred p;\nsetp.ne.b32 p, 1, 0;\nwgmma.mma_async.sync.aligned.m64n48k16.f32.bf16.bf16 {"
      "%0, %1, %2, %3, %4, %5, %6, %7, %8, %9, %10, %11, %12, %13, %14, %15, "
      "%16, %17, %18, %19, %20, %21, %22, %23"
      "}, {%24, %25, %26, %27}, %28, p, 1, 1, 0;\n}\n"
      :
      "+f"(d[0]), "+f"(d[1]), "+f"(d[2]), "+f"(d[3]), "+f"(d[4]), "+f"(d[5]), "+f"(d[6]), "+f"(d[7]),
      "+f"(d[8]), "+f"(d[9]), "+f"(d[10]), "+f"(d[11]), "+f"(d[12]), "+f"(d[13]), "+f"(d[14]), "+f"(d[15]),
      "+f"(d[16]), "+f"(d[17]), "+f"(d[18]), "+f"(d[19]), "+f"(d[20]), "+f"(d[21]), "+f"(d[22]), "+f"(d[23])
      : "r"(a[0]), "r"(a[1]), "r"(a[2]), "r"(a[3]), "l"(db));
  }
};
template <> struct WG<64> {
  static __device__ __forceinline__ void rs(float* d, const uint32_t* a, uint64_t db) {
    asm volatile("{\n.reg .pred p;\nsetp.ne.b32 p, 1, 0;\nwgmma.mma_async.sync.aligned.m64n64k16.f32.bf16.bf16 {"
      "%0, %1, %2, %3, %4, %5, %6, %7, %8, %9, %10, %11, %12, %13, %14, %15, "
      "%16, %17, %18, %19, %20, %21, %22, %23, %24, %25, %26, %27, %28, %29, %30, %31"
      "}, {%32, %33, %34, %35}, %36, p, 1, 1, 0;\n}\n"
      :
      "+f"(d[0]), "+f"(d[1]), "+f"(d[2]), "+f"(d[3]), "+f"(d[4]), "+f"(d[5]), "+f"(d[6]), "+f"(d[7]),
      "+f"(d[8]), "+f"(d[9]), "+f"(d[10]), "+f"(d[11]), "+f"(d[12]), "+f"(d[13]), "+f"(d[14]), "+f"(d[15]),
      "+f"(d[16]), "+f"(d[17]), "+f"(d[18]), "+f"(d[19]), "+f"(d[20]), "+f"(d[21]), "+f"(d[22]), "+f"(d[23]),
      "+f"(d[24]), "+f"(d[25]), "+f"(d[26]), "+f"(d[27]), "+f"(d[28]), "+f"(d[29]), "+f"(d[30]), "+f"(d[31])
      : "r"(a[0]), "r"(a[1]), "r"(a[2]), "r"(a[3]), "l"(db));
  }
};
template <> struct WG<80> {
  static __device__ __forceinline__ void rs(float* d, const uint32_t* a, uint64_t db) {
    asm volatile("{\n.reg .pred p;\nsetp.ne.b32 p, 1, 0;\nwgmma.mma_async.sync.aligned.m64n80k16.f32.bf16.bf16 {"
      "%0, %1, %2, %3, %4, %5, %6, %7, %8, %9, %10, %11, %12, %13, %14, %15, "
      "%16, %17, %18, %19, %20, %21, %22, %23, %24, %25, %26, %27, %28, %29, %30, %31, "
      "%32, %33, %34, %35, %36, %37, %38, %39"
      "}, {%40, %41, %42, %43}, %44, p, 1, 1, 0;\n}\n"
      :
      "+f"(d[0]), "+f"(d[1]), "+f"(d[2]), "+f"(d[3]), "+f"(d[4]), "+f"(d[5]), "+f"(d[6]), "+f"(d[7]),
      "+f"(d[8]), "+f"(d[9]), "+f"(d[10]), "+f"(d[11]), "+f"(d[12]), "+f"(d[13]), "+f"(d[14]), "+f"(d[15]),
      "+f"(d[16]), "+f"(d[17]), "+f"(d[18]), "+f"(d[19]), "+f"(d[20]), "+f"(d[21]), "+f"(d[22]), "+f"(d[23]),
      "+f"(d[24]), "+f"(d[25]), "+f"(d[26]), "+f"(d[27]), "+f"(d[28]), "+f"(d[29]), "+f"(d[30]), "+f"(d[31]),
      "+f"(d[32]), "+f"(d[33]), "+f"(d[34]), "+f"(d[35]), "+f"(d[36]), "+f"(d[37]), "+f"(d[38]), "+f"(d[39])
      : "r"(a[0]), "r"(a[1]), "r"(a[2]), "r"(a[3]), "l"(db));
  }
};
template <> struct WG<96> {
  static __device__ __forceinline__ void rs(float* d, const uint32_t* a, uint64_t db) {
    asm volatile("{\n.reg .pred p;\nsetp.ne.b32 p, 1, 0;\nwgmma.mma_async.sync.aligned.m64n96k16.f32.bf16.bf16 {"
      "%0, %1, %2, %3, %4, %5, %6, %7, %8, %9, %10, %11, %12, %13, %14, %15, "
      "%16, %17, %18, %19, %20, %21, %22, %23, %24, %25, %26, %27, %28, %29, %30, %31, "
      "%32, %33, %34, %35, %36, %37, %38, %39, %40, %41, %42, %43, %44, %45, %46, %47"
      "}, {%48, %49, %50, %51}, %52, p, 1, 1, 0;\n}\n"
      :
      "+f"(d[0]), "+f"(d[1]), "+f"(d[2]), "+f"(d[3]), "+f"(d[4]), "+f"(d[5]), "+f"(d[6]), "+f"(d[7]),
      "+f"(d[8]), "+f"(d[9]), "+f"(d[10]), "+f"(d[11]), "+f"(d[12]), "+f"(d[13]), "+f"(d[14]), "+f"(d[15]),
      "+f"(d[16]), "+f"(d[17]), "+f"(d[18]), "+f"(d[19]), "+f"(d[20]), "+f"(d[21]), "+f"(d[22]), "+f"(d[23]),
      "+f"(d[24]), "+f"(d[25]), "+f"(d[26]), "+f"(d[27]), "+f"(d[28]), "+f"(d[29]), "+f"(d[30]), "+f"(d[31]),
      "+f"(d[32]), "+f"(d[33]), "+f"(d[34]), "+f"(d[35]), "+f"(d[36]), "+f"(d[37]), "+f"(d[38]), "+f"(d[39]),
      "+f"(d[40]), "+f"(d[41]), "+f"(d[42]), "+f"(d[43]), "+f"(d[44]), "+f"(d[45]), "+f"(d[46]), "+f"(d[47])
      : "r"(a[0]), "r"(a[1]), "r"(a[2]), "r"(a[3]), "l"(db));
  }
};
template <> struct WG<112> {
  static __device__ __forceinline__ void rs(float* d, const uint32_t* a, uint64_t db) {
    asm volatile("{\n.reg .pred p;\nsetp.ne.b32 p, 1, 0;\nwgmma.mma_async.sync.aligned.m64n112k16.f32.bf16.bf16 {"
      "%0, %1, %2, %3, %4, %5, %6, %7, %8, %9, %10, %11, %12, %13, %14, %15, "
      "%16, %17, %18, %19, %20, %21, %22, %23, %24, %25, %26, %27, %28, %29, %30, %31, "
      "%32, %33, %34, %35, %36, %37, %38, %39, %40, %41, %42, %43, %44, %45, %46, %47, "
      "%48, %49, %50, %51, %52, %53, %54, %55"
      "}, {%56, %57, %58, %59}, %60, p, 1, 1, 0;\n}\n"
      :
      "+f"(d[0]), "+f"(d[1]), "+f"(d[2]), "+f"(d[3]), "+f"(d[4]), "+f"(d[5]), "+f"(d[6]), "+f"(d[7]),
      "+f"(d[8]), "+f"(d[9]), "+f"(d[10]), "+f"(d[11]), "+f"(d[12]), "+f"(d[13]), "+f"(d[14]), "+f"(d[15]),
      "+f"(d[16]), "+f"(d[17]), "+f"(d[18]), "+f"(d[19]), "+f"(d[20]), "+f"(d[21]), "+f"(d[22]), "+f"(d[23]),
      "+f"(d[24]), "+f"(d[25]), "+f"(d[26]), "+f"(d[27]), "+f"(d[28]), "+f"(d[29]), "+f"(d[30]), "+f"(d[31]),
      "+f"(d[32]), "+f"(d[33]), "+f"(d[34]), "+f"(d[35]), "+f"(d[36]), "+f"(d[37]), "+f"(d[38]), "+f"(d[39]),
      "+f"(d[40]), "+f"(d[41]), "+f"(d[42]), "+f"(d[43]), "+f"(d[44]), "+f"(d[45]), "+f"(d[46]), "+f"(d[47]),
      "+f"(d[48]), "+f"(d[49]), "+f"(d[50]), "+f"(d[51]), "+f"(d[52]), "+f"(d[53]), "+f"(d[54]), "+f"(d[55])
      : "r"(a[0]), "r"(a[1]), "r"(a[2]), "r"(a[3]), "l"(db));
  }
};
template <> struct WG<128> {
  static __device__ __forceinline__ void rs(float* d, const uint32_t* a, uint64_t db) {
    asm volatile("{\n.reg .pred p;\nsetp.ne.b32 p, 1, 0;\nwgmma.mma_async.sync.aligned.m64n128k16.f32.bf16.bf16 {"
      "%0, %1, %2, %3, %4, %5, %6, %7, %8, %9, %10, %11, %12, %13, %14, %15, "
      "%16, %17, %18, %19, %20, %21, %22, %23, %24, %25, %26, %27, %28, %29, %30, %31, "
      "%32, %33, %34, %35, %36, %37, %38, %39, %40, %41, %42, %43, %44, %45, %46, %47, "
      "%48, %49, %50, %51, %52, %53, %54, %55, %56, %57, %58, %59, %60, %61, %62, %63"
      "}, {%64, %65, %66, %67}, %68, p, 1, 1, 0;\n}\n"
      :
      "+f"(d[0]), "+f"(d[1]), "+f"(d[2]), "+f"(d[3]), "+f"(d[4]), "+f"(d[5]), "+f"(d[6]), "+f"(d[7]),
      "+f"(d[8]), "+f"(d[9]), "+f"(d[10]), "+f"(d[11]), "+f"(d[12]), "+f"(d[13]), "+f"(d[14]), "+f"(d[15]),
      "+f"(d[16]), "+f"(d[17]), "+f"(d[18]), "+f"(d[19]), "+f"(d[20]), "+f"(d[21]), "+f"(d[22]), "+f"(d[23]),
      "+f"(d[24]), "+f"(d[25]), "+f"(d[26]), "+f"(d[27]), "+f"(d[28]), "+f"(d[29]), "+f"(d[30]), "+f"(d[31]),
      "+f"(d[32]), "+f"(d[33]), "+f"(d[34]), "+f"(d[35]), "+f"(d[36]), "+f"(d[37]), "+f"(d[38]), "+f"(d[39]),
      "+f"(d[40]), "+f"(d[41]), "+f"(d[42]), "+f"(d[43]), "+f"(d[44]), "+f"(d[45]), "+f"(d[46]), "+f"(d[47]),
      "+f"(d[48]), "+f"(d[49]), "+f"(d[50]), "+f"(d[51]), "+f"(d[52]), "+f"(d[53]), "+f"(d[54]), "+f"(d[55]),
      "+f"(d[56]), "+f"(d[57]), "+f"(d[58]), "+f"(d[59]), "+f"(d[60]), "+f"(d[61]), "+f"(d[62]), "+f"(d[63])
      : "r"(a[0]), "r"(a[1]), "r"(a[2]), "r"(a[3]), "l"(db));
  }
};
template <int N> struct KB;
template <> struct KB<80> {
  template <int W, int RC, bool RA, int BSTEP, bool D1> static __device__ __forceinline__ void run(float* d, uint64_t da, uint64_t db, uint32_t rel, uint32_t rela, uint32_t doR, uint32_t fa, uint32_t pa, uint32_t fb, uint32_t pb, uint32_t acc) {
    if constexpr (W == 0 && RC == 1 && RA == 0 && D1 == 0) asm volatile(
    "{\n.reg .pred p, q, r, t;\n.reg .b64 a, b;\n.reg .u32 n;\nsetp.ne.b32 t, 1, 0;\nsetp.ne.b32 r, %49, 0;\n"
    "wgmma.mma_async.sync.aligned.m64n80k16.f32.bf16.bf16 {"
      "%0, %1, %2, %3, %4, %5, %6, %7, %8, %9, %10, %11, %12, %13, %14, %15, "
      "%16, %17, %18, %19, %20, %21, %22, %23, %24, %25, %26, %27, %28, %29, %30, %31, "
      "%32, %33, %34, %35, %36, %37, %38, %39"
      "}, %40, %41, r, 1, 1, 0, 1;\n"
    "add.u64 a, %40, 2;\nadd.u64 b, %41, %48;\n"
    "wgmma.mma_async.sync.aligned.m64n80k16.f32.bf16.bf16 {"
      "%0, %1, %2, %3, %4, %5, %6, %7, %8, %9, %10, %11, %12, %13, %14, %15, "
      "%16, %17, %18, %19, %20, %21, %22, %23, %24, %25, %26, %27, %28, %29, %30, %31, "
      "%32, %33, %34, %35, %36, %37, %38, %39"
      "}, a, b, t, 1, 1, 0, 1;\n"
    "wgmma.commit_group.sync.aligned;\nwgmma.wait_group.sync.aligned 1;\n"
    "add.u64 a, %40, 4;\nadd.u64 b, %41, 2*%48;\n"
    "wgmma.mma_async.sync.aligned.m64n80k16.f32.bf16.bf16 {"
      "%0, %1, %2, %3, %4, %5, %6, %7, %8, %9, %10, %11, %12, %13, %14, %15, "
      "%16, %17, %18, %19, %20, %21, %22, %23, %24, %25, %26, %27, %28, %29, %30, %31, "
      "%32, %33, %34, %35, %36, %37, %38, %39"
      "}, a, b, t, 1, 1, 0, 1;\n"
    "setp.ne.u32 q, %43, 0;\n@q mbarrier.arrive.shared::cta.b64 _, [%42];\n"
    "add.u64 a, %40, 6;\nadd.u64 b, %41, 3*%48;\n"
    "wgmma.mma_async.sync.aligned.m64n80k16.f32.bf16.bf16 {"
      "%0, %1, %2, %3, %4, %5, %6, %7, %8, %9, %10, %11, %12, %13, %14, %15, "
      "%16, %17, %18, %19, %20, %21, %22, %23, %24, %25, %26, %27, %28, %29, %30, %31, "
      "%32, %33, %34, %35, %36, %37, %38, %39"
      "}, a, b, t, 1, 1, 0, 1;\n"
    "wgmma.commit_group.sync.aligned;\n"
    "}\n"
      :
      "+f"(d[0]), "+f"(d[1]), "+f"(d[2]), "+f"(d[3]), "+f"(d[4]), "+f"(d[5]), "+f"(d[6]), "+f"(d[7]),
      "+f"(d[8]), "+f"(d[9]), "+f"(d[10]), "+f"(d[11]), "+f"(d[12]), "+f"(d[13]), "+f"(d[14]), "+f"(d[15]),
      "+f"(d[16]), "+f"(d[17]), "+f"(d[18]), "+f"(d[19]), "+f"(d[20]), "+f"(d[21]), "+f"(d[22]), "+f"(d[23]),
      "+f"(d[24]), "+f"(d[25]), "+f"(d[26]), "+f"(d[27]), "+f"(d[28]), "+f"(d[29]), "+f"(d[30]), "+f"(d[31]),
      "+f"(d[32]), "+f"(d[33]), "+f"(d[34]), "+f"(d[35]), "+f"(d[36]), "+f"(d[37]), "+f"(d[38]), "+f"(d[39])
      : "l"(da), "l"(db), "r"(rel), "r"(doR), "r"(fa), "r"(pa), "r"(fb), "r"(pb), "n"(BSTEP), "r"(acc), "r"(rela) : "memory");
    else if constexpr (W == 2 && RC == 1 && RA == 0 && D1 == 0) asm volatile(
    "{\n.reg .pred p, q, r, t;\n.reg .b64 a, b;\n.reg .u32 n;\nsetp.ne.b32 t, 1, 0;\nsetp.ne.b32 r, %49, 0;\n"
    "wgmma.mma_async.sync.aligned.m64n80k16.f32.bf16.bf16 {"
      "%0, %1, %2, %3, %4, %5, %6, %7, %8, %9, %10, %11, %12, %13, %14, %15, "
      "%16, %17, %18, %19, %20, %21, %22, %23, %24, %25, %26, %27, %28, %29, %30, %31, "
      "%32, %33, %34, %35, %36, %37, %38, %39"
      "}, %40, %41, r, 1, 1, 0, 1;\n"
    "add.u64 a, %40, 2;\nadd.u64 b, %41, %48;\n"
    "wgmma.mma_async.sync.aligned.m64n80k16.f32.bf16.bf16 {"
      "%0, %1, %2, %3, %4, %5, %6, %7, %8, %9, %10, %11, %12, %13, %14, %15, "
      "%16, %17, %18, %19, %20, %21, %22, %23, %24, %25, %26, %27, %28, %29, %30, %31, "
      "%32, %33, %34, %35, %36, %37, %38, %39"
      "}, a, b, t, 1, 1, 0, 1;\n"
    "wgmma.commit_group.sync.aligned;\nwgmma.wait_group.sync.aligned 1;\n"
    "add.u64 a, %40, 4;\nadd.u64 b, %41, 2*%48;\n"
    "wgmma.mma_async.sync.aligned.m64n80k16.f32.bf16.bf16 {"
      "%0, %1, %2, %3, %4, %5, %6, %7, %8, %9, %10, %11, %12, %13, %14, %15, "
      "%16, %17, %18, %19, %20, %21, %22, %23, %24, %25, %26, %27, %28, %29, %30, %31, "
      "%32, %33, %34, %35, %36, %37, %38, %39"
      "}, a, b, t, 1, 1, 0, 1;\n"
    "setp.ne.u32 q, %43, 0;\n@q mbarrier.arrive.shared::cta.b64 _, [%42];\n"
    "mbarrier.test_wait.parity.shared::cta.b64 p, [%46], %47;\n"
    "mbarrier.test_wait.parity.shared::cta.b64 r, [%44], %45;\nand.pred p, p, r;\n"
    "add.u64 a, %40, 6;\nadd.u64 b, %41, 3*%48;\n"
    "wgmma.mma_async.sync.aligned.m64n80k16.f32.bf16.bf16 {"
      "%0, %1, %2, %3, %4, %5, %6, %7, %8, %9, %10, %11, %12, %13, %14, %15, "
      "%16, %17, %18, %19, %20, %21, %22, %23, %24, %25, %26, %27, %28, %29, %30, %31, "
      "%32, %33, %34, %35, %36, %37, %38, %39"
      "}, a, b, t, 1, 1, 0, 1;\n"
    "wgmma.commit_group.sync.aligned;\n"
    "@p bra.uni DN;\nmov.u32 n, 0;\nWT: mbarrier.try_wait.parity.shared::cta.b64 p, [%46], %47;\nmbarrier.try_wait.parity.shared::cta.b64 r, [%44], %45;\nand.pred p, p, r;\n@p bra.uni DN;\nadd.u32 n, n, 1;\nsetp.lt.u32 p, n, 0x100000;\n@p bra.uni WT;\nDN:\n"
    "}\n"
      :
      "+f"(d[0]), "+f"(d[1]), "+f"(d[2]), "+f"(d[3]), "+f"(d[4]), "+f"(d[5]), "+f"(d[6]), "+f"(d[7]),
      "+f"(d[8]), "+f"(d[9]), "+f"(d[10]), "+f"(d[11]), "+f"(d[12]), "+f"(d[13]), "+f"(d[14]), "+f"(d[15]),
      "+f"(d[16]), "+f"(d[17]), "+f"(d[18]), "+f"(d[19]), "+f"(d[20]), "+f"(d[21]), "+f"(d[22]), "+f"(d[23]),
      "+f"(d[24]), "+f"(d[25]), "+f"(d[26]), "+f"(d[27]), "+f"(d[28]), "+f"(d[29]), "+f"(d[30]), "+f"(d[31]),
      "+f"(d[32]), "+f"(d[33]), "+f"(d[34]), "+f"(d[35]), "+f"(d[36]), "+f"(d[37]), "+f"(d[38]), "+f"(d[39])
      : "l"(da), "l"(db), "r"(rel), "r"(doR), "r"(fa), "r"(pa), "r"(fb), "r"(pb), "n"(BSTEP), "r"(acc), "r"(rela) : "memory");
    else static_assert(W < 0, "variant not generated");
  }
};
template <> struct KB<160> {
  template <int W, int RC, bool RA, int BSTEP, bool D1> static __device__ __forceinline__ void run(float* d, uint64_t da, uint64_t db, uint32_t rel, uint32_t rela, uint32_t doR, uint32_t fa, uint32_t pa, uint32_t fb, uint32_t pb, uint32_t acc) {
    if constexpr (W == 0 && RC == 2 && RA == 0 && D1 == 0) asm volatile(
    "{\n.reg .pred p, q, r, t;\n.reg .b64 a, b;\n.reg .u32 n;\nsetp.ne.b32 t, 1, 0;\nsetp.ne.b32 r, %89, 0;\n"
    "wgmma.mma_async.sync.aligned.m64n160k16.f32.bf16.bf16 {"
      "%0, %1, %2, %3, %4, %5, %6, %7, %8, %9, %10, %11, %12, %13, %14, %15, "
      "%16, %17, %18, %19, %20, %21, %22, %23, %24, %25, %26, %27, %28, %29, %30, %31, "
      "%32, %33, %34, %35, %36, %37, %38, %39, %40, %41, %42, %43, %44, %45, %46, %47, "
      "%48, %49, %50, %51, %52, %53, %54, %55, %56, %57, %58, %59, %60, %61, %62, %63, "
      "%64, %65, %66, %67, %68, %69, %70, %71, %72, %73, %74, %75, %76, %77, %78, %79"
      "}, %80, %81, r, 1, 1, 0, 1;\n"
    "add.u64 a, %80, 2;\nadd.u64 b, %81, %88;\n"
    "wgmma.mma_async.sync.aligned.m64n160k16.f32.bf16.bf16 {"
      "%0, %1, %2, %3, %4, %5, %6, %7, %8, %9, %10, %11, %12, %13, %14, %15, "
      "%16, %17, %18, %19, %20, %21, %22, %23, %24, %25, %26, %27, %28, %29, %30, %31, "
      "%32, %33, %34, %35, %36, %37, %38, %39, %40, %41, %42, %43, %44, %45, %46, %47, "
      "%48, %49, %50, %51, %52, %53, %54, %55, %56, %57, %58, %59, %60, %61, %62, %63, "
      "%64, %65, %66, %67, %68, %69, %70, %71, %72, %73, %74, %75, %76, %77, %78, %79"
      "}, a, b, t, 1, 1, 0, 1;\n"
    "wgmma.commit_group.sync.aligned;\nwgmma.wait_group.sync.aligned 1;\n"
    "add.u64 a, %80, 4;\nadd.u64 b, %81, 2*%88;\n"
    "wgmma.mma_async.sync.aligned.m64n160k16.f32.bf16.bf16 {"
      "%0, %1, %2, %3, %4, %5, %6, %7, %8, %9, %10, %11, %12, %13, %14, %15, "
      "%16, %17, %18, %19, %20, %21, %22, %23, %24, %25, %26, %27, %28, %29, %30, %31, "
      "%32, %33, %34, %35, %36, %37, %38, %39, %40, %41, %42, %43, %44, %45, %46, %47, "
      "%48, %49, %50, %51, %52, %53, %54, %55, %56, %57, %58, %59, %60, %61, %62, %63, "
      "%64, %65, %66, %67, %68, %69, %70, %71, %72, %73, %74, %75, %76, %77, %78, %79"
      "}, a, b, t, 1, 1, 0, 1;\n"
    "setp.ne.u32 q, %83, 0;\n@q mbarrier.arrive.shared::cta.b64 _, [%82];\n@q mbarrier.arrive.shared::cta.b64 _, [%82];\n"
    "add.u64 a, %80, 6;\nadd.u64 b, %81, 3*%88;\n"
    "wgmma.mma_async.sync.aligned.m64n160k16.f32.bf16.bf16 {"
      "%0, %1, %2, %3, %4, %5, %6, %7, %8, %9, %10, %11, %12, %13, %14, %15, "
      "%16, %17, %18, %19, %20, %21, %22, %23, %24, %25, %26, %27, %28, %29, %30, %31, "
      "%32, %33, %34, %35, %36, %37, %38, %39, %40, %41, %42, %43, %44, %45, %46, %47, "
      "%48, %49, %50, %51, %52, %53, %54, %55, %56, %57, %58, %59, %60, %61, %62, %63, "
      "%64, %65, %66, %67, %68, %69, %70, %71, %72, %73, %74, %75, %76, %77, %78, %79"
      "}, a, b, t, 1, 1, 0, 1;\n"
    "wgmma.commit_group.sync.aligned;\n"
    "}\n"
      :
      "+f"(d[0]), "+f"(d[1]), "+f"(d[2]), "+f"(d[3]), "+f"(d[4]), "+f"(d[5]), "+f"(d[6]), "+f"(d[7]),
      "+f"(d[8]), "+f"(d[9]), "+f"(d[10]), "+f"(d[11]), "+f"(d[12]), "+f"(d[13]), "+f"(d[14]), "+f"(d[15]),
      "+f"(d[16]), "+f"(d[17]), "+f"(d[18]), "+f"(d[19]), "+f"(d[20]), "+f"(d[21]), "+f"(d[22]), "+f"(d[23]),
      "+f"(d[24]), "+f"(d[25]), "+f"(d[26]), "+f"(d[27]), "+f"(d[28]), "+f"(d[29]), "+f"(d[30]), "+f"(d[31]),
      "+f"(d[32]), "+f"(d[33]), "+f"(d[34]), "+f"(d[35]), "+f"(d[36]), "+f"(d[37]), "+f"(d[38]), "+f"(d[39]),
      "+f"(d[40]), "+f"(d[41]), "+f"(d[42]), "+f"(d[43]), "+f"(d[44]), "+f"(d[45]), "+f"(d[46]), "+f"(d[47]),
      "+f"(d[48]), "+f"(d[49]), "+f"(d[50]), "+f"(d[51]), "+f"(d[52]), "+f"(d[53]), "+f"(d[54]), "+f"(d[55]),
      "+f"(d[56]), "+f"(d[57]), "+f"(d[58]), "+f"(d[59]), "+f"(d[60]), "+f"(d[61]), "+f"(d[62]), "+f"(d[63]),
      "+f"(d[64]), "+f"(d[65]), "+f"(d[66]), "+f"(d[67]), "+f"(d[68]), "+f"(d[69]), "+f"(d[70]), "+f"(d[71]),
      "+f"(d[72]), "+f"(d[73]), "+f"(d[74]), "+f"(d[75]), "+f"(d[76]), "+f"(d[77]), "+f"(d[78]), "+f"(d[79])
      : "l"(da), "l"(db), "r"(rel), "r"(doR), "r"(fa), "r"(pa), "r"(fb), "r"(pb), "n"(BSTEP), "r"(acc), "r"(rela) : "memory");
    else if constexpr (W == 1 && RC == 2 && RA == 0 && D1 == 0) asm volatile(
    "{\n.reg .pred p, q, r, t;\n.reg .b64 a, b;\n.reg .u32 n;\nsetp.ne.b32 t, 1, 0;\nsetp.ne.b32 r, %89, 0;\n"
    "wgmma.mma_async.sync.aligned.m64n160k16.f32.bf16.bf16 {"
      "%0, %1, %2, %3, %4, %5, %6, %7, %8, %9, %10, %11, %12, %13, %14, %15, "
      "%16, %17, %18, %19, %20, %21, %22, %23, %24, %25, %26, %27, %28, %29, %30, %31, "
      "%32, %33, %34, %35, %36, %37, %38, %39, %40, %41, %42, %43, %44, %45, %46, %47, "
      "%48, %49, %50, %51, %52, %53, %54, %55, %56, %57, %58, %59, %60, %61, %62, %63, "
      "%64, %65, %66, %67, %68, %69, %70, %71, %72, %73, %74, %75, %76, %77, %78, %79"
      "}, %80, %81, r, 1, 1, 0, 1;\n"
    "add.u64 a, %80, 2;\nadd.u64 b, %81, %88;\n"
    "wgmma.mma_async.sync.aligned.m64n160k16.f32.bf16.bf16 {"
      "%0, %1, %2, %3, %4, %5, %6, %7, %8, %9, %10, %11, %12, %13, %14, %15, "
      "%16, %17, %18, %19, %20, %21, %22, %23, %24, %25, %26, %27, %28, %29, %30, %31, "
      "%32, %33, %34, %35, %36, %37, %38, %39, %40, %41, %42, %43, %44, %45, %46, %47, "
      "%48, %49, %50, %51, %52, %53, %54, %55, %56, %57, %58, %59, %60, %61, %62, %63, "
      "%64, %65, %66, %67, %68, %69, %70, %71, %72, %73, %74, %75, %76, %77, %78, %79"
      "}, a, b, t, 1, 1, 0, 1;\n"
    "wgmma.commit_group.sync.aligned;\nwgmma.wait_group.sync.aligned 1;\n"
    "add.u64 a, %80, 4;\nadd.u64 b, %81, 2*%88;\n"
    "wgmma.mma_async.sync.aligned.m64n160k16.f32.bf16.bf16 {"
      "%0, %1, %2, %3, %4, %5, %6, %7, %8, %9, %10, %11, %12, %13, %14, %15, "
      "%16, %17, %18, %19, %20, %21, %22, %23, %24, %25, %26, %27, %28, %29, %30, %31, "
      "%32, %33, %34, %35, %36, %37, %38, %39, %40, %41, %42, %43, %44, %45, %46, %47, "
      "%48, %49, %50, %51, %52, %53, %54, %55, %56, %57, %58, %59, %60, %61, %62, %63, "
      "%64, %65, %66, %67, %68, %69, %70, %71, %72, %73, %74, %75, %76, %77, %78, %79"
      "}, a, b, t, 1, 1, 0, 1;\n"
    "setp.ne.u32 q, %83, 0;\n@q mbarrier.arrive.shared::cta.b64 _, [%82];\n@q mbarrier.arrive.shared::cta.b64 _, [%82];\n"
    "mbarrier.test_wait.parity.shared::cta.b64 p, [%86], %87;\n"
    "add.u64 a, %80, 6;\nadd.u64 b, %81, 3*%88;\n"
    "wgmma.mma_async.sync.aligned.m64n160k16.f32.bf16.bf16 {"
      "%0, %1, %2, %3, %4, %5, %6, %7, %8, %9, %10, %11, %12, %13, %14, %15, "
      "%16, %17, %18, %19, %20, %21, %22, %23, %24, %25, %26, %27, %28, %29, %30, %31, "
      "%32, %33, %34, %35, %36, %37, %38, %39, %40, %41, %42, %43, %44, %45, %46, %47, "
      "%48, %49, %50, %51, %52, %53, %54, %55, %56, %57, %58, %59, %60, %61, %62, %63, "
      "%64, %65, %66, %67, %68, %69, %70, %71, %72, %73, %74, %75, %76, %77, %78, %79"
      "}, a, b, t, 1, 1, 0, 1;\n"
    "wgmma.commit_group.sync.aligned;\n"
    "@p bra.uni DN;\nmov.u32 n, 0;\nWT: mbarrier.try_wait.parity.shared::cta.b64 p, [%86], %87;\n@p bra.uni DN;\nadd.u32 n, n, 1;\nsetp.lt.u32 p, n, 0x100000;\n@p bra.uni WT;\nDN:\n"
    "}\n"
      :
      "+f"(d[0]), "+f"(d[1]), "+f"(d[2]), "+f"(d[3]), "+f"(d[4]), "+f"(d[5]), "+f"(d[6]), "+f"(d[7]),
      "+f"(d[8]), "+f"(d[9]), "+f"(d[10]), "+f"(d[11]), "+f"(d[12]), "+f"(d[13]), "+f"(d[14]), "+f"(d[15]),
      "+f"(d[16]), "+f"(d[17]), "+f"(d[18]), "+f"(d[19]), "+f"(d[20]), "+f"(d[21]), "+f"(d[22]), "+f"(d[23]),
      "+f"(d[24]), "+f"(d[25]), "+f"(d[26]), "+f"(d[27]), "+f"(d[28]), "+f"(d[29]), "+f"(d[30]), "+f"(d[31]),
      "+f"(d[32]), "+f"(d[33]), "+f"(d[34]), "+f"(d[35]), "+f"(d[36]), "+f"(d[37]), "+f"(d[38]), "+f"(d[39]),
      "+f"(d[40]), "+f"(d[41]), "+f"(d[42]), "+f"(d[43]), "+f"(d[44]), "+f"(d[45]), "+f"(d[46]), "+f"(d[47]),
      "+f"(d[48]), "+f"(d[49]), "+f"(d[50]), "+f"(d[51]), "+f"(d[52]), "+f"(d[53]), "+f"(d[54]), "+f"(d[55]),
      "+f"(d[56]), "+f"(d[57]), "+f"(d[58]), "+f"(d[59]), "+f"(d[60]), "+f"(d[61]), "+f"(d[62]), "+f"(d[63]),
      "+f"(d[64]), "+f"(d[65]), "+f"(d[66]), "+f"(d[67]), "+f"(d[68]), "+f"(d[69]), "+f"(d[70]), "+f"(d[71]),
      "+f"(d[72]), "+f"(d[73]), "+f"(d[74]), "+f"(d[75]), "+f"(d[76]), "+f"(d[77]), "+f"(d[78]), "+f"(d[79])
      : "l"(da), "l"(db), "r"(rel), "r"(doR), "r"(fa), "r"(pa), "r"(fb), "r"(pb), "n"(BSTEP), "r"(acc), "r"(rela) : "memory");
    else static_assert(W < 0, "variant not generated");
  }
};
template <> struct KB<192> {
  template <int W, int RC, bool RA, int BSTEP, bool D1> static __device__ __forceinline__ void run(float* d, uint64_t da, uint64_t db, uint32_t rel, uint32_t rela, uint32_t doR, uint32_t fa, uint32_t pa, uint32_t fb, uint32_t pb, uint32_t acc) {
    if constexpr (W == 0 && RC == 2 && RA == 0 && D1 == 0) asm volatile(
    "{\n.reg .pred p, q, r, t;\n.reg .b64 a, b;\n.reg .u32 n;\nsetp.ne.b32 t, 1, 0;\nsetp.ne.b32 r, %105, 0;\n"
    "wgmma.mma_async.sync.aligned.m64n192k16.f32.bf16.bf16 {"
      "%0, %1, %2, %3, %4, %5, %6, %7, %8, %9, %10, %11, %12, %13, %14, %15, "
      "%16, %17, %18, %19, %20, %21, %22, %23, %24, %25, %26, %27, %28, %29, %30, %31, "
      "%32, %33, %34, %35, %36, %37, %38, %39, %40, %41, %42, %43, %44, %45, %46, %47, "
      "%48, %49, %50, %51, %52, %53, %54, %55, %56, %57, %58, %59, %60, %61, %62, %63, "
      "%64, %65, %66, %67, %68, %69, %70, %71, %72, %73, %74, %75, %76, %77, %78, %79, "
      "%80, %81, %82, %83, %84, %85, %86, %87, %88, %89, %90, %91, %92, %93, %94, %95"
      "}, %96, %97, r, 1, 1, 0, 1;\n"
    "add.u64 a, %96, 2;\nadd.u64 b, %97, %104;\n"
    "wgmma.mma_async.sync.aligned.m64n192k16.f32.bf16.bf16 {"
      "%0, %1, %2, %3, %4, %5, %6, %7, %8, %9, %10, %11, %12, %13, %14, %15, "
      "%16, %17, %18, %19, %20, %21, %22, %23, %24, %25, %26, %27, %28, %29, %30, %31, "
      "%32, %33, %34, %35, %36, %37, %38, %39, %40, %41, %42, %43, %44, %45, %46, %47, "
      "%48, %49, %50, %51, %52, %53, %54, %55, %56, %57, %58, %59, %60, %61, %62, %63, "
      "%64, %65, %66, %67, %68, %69, %70, %71, %72, %73, %74, %75, %76, %77, %78, %79, "
      "%80, %81, %82, %83, %84, %85, %86, %87, %88, %89, %90, %91, %92, %93, %94, %95"
      "}, a, b, t, 1, 1, 0, 1;\n"
    "wgmma.commit_group.sync.aligned;\nwgmma.wait_group.sync.aligned 1;\n"
    "add.u64 a, %96, 4;\nadd.u64 b, %97, 2*%104;\n"
    "wgmma.mma_async.sync.aligned.m64n192k16.f32.bf16.bf16 {"
      "%0, %1, %2, %3, %4, %5, %6, %7, %8, %9, %10, %11, %12, %13, %14, %15, "
      "%16, %17, %18, %19, %20, %21, %22, %23, %24, %25, %26, %27, %28, %29, %30, %31, "
      "%32, %33, %34, %35, %36, %37, %38, %39, %40, %41, %42, %43, %44, %45, %46, %47, "
      "%48, %49, %50, %51, %52, %53, %54, %55, %56, %57, %58, %59, %60, %61, %62, %63, "
      "%64, %65, %66, %67, %68, %69, %70, %71, %72, %73, %74, %75, %76, %77, %78, %79, "
      "%80, %81, %82, %83, %84, %85, %86, %87, %88, %89, %90, %91, %92, %93, %94, %95"
      "}, a, b, t, 1, 1, 0, 1;\n"
    "setp.ne.u32 q, %99, 0;\n@q mbarrier.arrive.shared::cta.b64 _, [%98];\n@q mbarrier.arrive.shared::cta.b64 _, [%98];\n"
    "add.u64 a, %96, 6;\nadd.u64 b, %97, 3*%104;\n"
    "wgmma.mma_async.sync.aligned.m64n192k16.f32.bf16.bf16 {"
      "%0, %1, %2, %3, %4, %5, %6, %7, %8, %9, %10, %11, %12, %13, %14, %15, "
      "%16, %17, %18, %19, %20, %21, %22, %23, %24, %25, %26, %27, %28, %29, %30, %31, "
      "%32, %33, %34, %35, %36, %37, %38, %39, %40, %41, %42, %43, %44, %45, %46, %47, "
      "%48, %49, %50, %51, %52, %53, %54, %55, %56, %57, %58, %59, %60, %61, %62, %63, "
      "%64, %65, %66, %67, %68, %69, %70, %71, %72, %73, %74, %75, %76, %77, %78, %79, "
      "%80, %81, %82, %83, %84, %85, %86, %87, %88, %89, %90, %91, %92, %93, %94, %95"
      "}, a, b, t, 1, 1, 0, 1;\n"
    "wgmma.commit_group.sync.aligned;\n"
    "}\n"
      :
      "+f"(d[0]), "+f"(d[1]), "+f"(d[2]), "+f"(d[3]), "+f"(d[4]), "+f"(d[5]), "+f"(d[6]), "+f"(d[7]),
      "+f"(d[8]), "+f"(d[9]), "+f"(d[10]), "+f"(d[11]), "+f"(d[12]), "+f"(d[13]), "+f"(d[14]), "+f"(d[15]),
      "+f"(d[16]), "+f"(d[17]), "+f"(d[18]), "+f"(d[19]), "+f"(d[20]), "+f"(d[21]), "+f"(d[22]), "+f"(d[23]),
      "+f"(d[24]), "+f"(d[25]), "+f"(d[26]), "+f"(d[27]), "+f"(d[28]), "+f"(d[29]), "+f"(d[30]), "+f"(d[31]),
      "+f"(d[32]), "+f"(d[33]), "+f"(d[34]), "+f"(d[35]), "+f"(d[36]), "+f"(d[37]), "+f"(d[38]), "+f"(d[39]),
      "+f"(d[40]), "+f"(d[41]), "+f"(d[42]), "+f"(d[43]), "+f"(d[44]), "+f"(d[45]), "+f"(d[46]), "+f"(d[47]),
      "+f"(d[48]), "+f"(d[49]), "+f"(d[50]), "+f"(d[51]), "+f"(d[52]), "+f"(d[53]), "+f"(d[54]), "+f"(d[55]),
      "+f"(d[56]), "+f"(d[57]), "+f"(d[58]), "+f"(d[59]), "+f"(d[60]), "+f"(d[61]), "+f"(d[62]), "+f"(d[63]),
      "+f"(d[64]), "+f"(d[65]), "+f"(d[66]), "+f"(d[67]), "+f"(d[68]), "+f"(d[69]), "+f"(d[70]), "+f"(d[71]),
      "+f"(d[72]), "+f"(d[73]), "+f"(d[74]), "+f"(d[75]), "+f"(d[76]), "+f"(d[77]), "+f"(d[78]), "+f"(d[79]),
      "+f"(d[80]), "+f"(d[81]), "+f"(d[82]), "+f"(d[83]), "+f"(d[84]), "+f"(d[85]), "+f"(d[86]), "+f"(d[87]),
      "+f"(d[88]), "+f"(d[89]), "+f"(d[90]), "+f"(d[91]), "+f"(d[92]), "+f"(d[93]), "+f"(d[94]), "+f"(d[95])
      : "l"(da), "l"(db), "r"(rel), "r"(doR), "r"(fa), "r"(pa), "r"(fb), "r"(pb), "n"(BSTEP), "r"(acc), "r"(rela) : "memory");
    else if constexpr (W == 0 && RC == 2 && RA == 1 && D1 == 0) asm volatile(
    "{\n.reg .pred p, q, r, t;\n.reg .b64 a, b;\n.reg .u32 n;\nsetp.ne.b32 t, 1, 0;\nsetp.ne.b32 r, %105, 0;\n"
    "wgmma.mma_async.sync.aligned.m64n192k16.f32.bf16.bf16 {"
      "%0, %1, %2, %3, %4, %5, %6, %7, %8, %9, %10, %11, %12, %13, %14, %15, "
      "%16, %17, %18, %19, %20, %21, %22, %23, %24, %25, %26, %27, %28, %29, %30, %31, "
      "%32, %33, %34, %35, %36, %37, %38, %39, %40, %41, %42, %43, %44, %45, %46, %47, "
      "%48, %49, %50, %51, %52, %53, %54, %55, %56, %57, %58, %59, %60, %61, %62, %63, "
      "%64, %65, %66, %67, %68, %69, %70, %71, %72, %73, %74, %75, %76, %77, %78, %79, "
      "%80, %81, %82, %83, %84, %85, %86, %87, %88, %89, %90, %91, %92, %93, %94, %95"
      "}, %96, %97, r, 1, 1, 0, 1;\n"
    "add.u64 a, %96, 2;\nadd.u64 b, %97, %104;\n"
    "wgmma.mma_async.sync.aligned.m64n192k16.f32.bf16.bf16 {"
      "%0, %1, %2, %3, %4, %5, %6, %7, %8, %9, %10, %11, %12, %13, %14, %15, "
      "%16, %17, %18, %19, %20, %21, %22, %23, %24, %25, %26, %27, %28, %29, %30, %31, "
      "%32, %33, %34, %35, %36, %37, %38, %39, %40, %41, %42, %43, %44, %45, %46, %47, "
      "%48, %49, %50, %51, %52, %53, %54, %55, %56, %57, %58, %59, %60, %61, %62, %63, "
      "%64, %65, %66, %67, %68, %69, %70, %71, %72, %73, %74, %75, %76, %77, %78, %79, "
      "%80, %81, %82, %83, %84, %85, %86, %87, %88, %89, %90, %91, %92, %93, %94, %95"
      "}, a, b, t, 1, 1, 0, 1;\n"
    "wgmma.commit_group.sync.aligned;\nwgmma.wait_group.sync.aligned 1;\n"
    "add.u64 a, %96, 4;\nadd.u64 b, %97, 2*%104;\n"
    "wgmma.mma_async.sync.aligned.m64n192k16.f32.bf16.bf16 {"
      "%0, %1, %2, %3, %4, %5, %6, %7, %8, %9, %10, %11, %12, %13, %14, %15, "
      "%16, %17, %18, %19, %20, %21, %22, %23, %24, %25, %26, %27, %28, %29, %30, %31, "
      "%32, %33, %34, %35, %36, %37, %38, %39, %40, %41, %42, %43, %44, %45, %46, %47, "
      "%48, %49, %50, %51, %52, %53, %54, %55, %56, %57, %58, %59, %60, %61, %62, %63, "
      "%64, %65, %66, %67, %68, %69, %70, %71, %72, %73, %74, %75, %76, %77, %78, %79, "
      "%80, %81, %82, %83, %84, %85, %86, %87, %88, %89, %90, %91, %92, %93, %94, %95"
      "}, a, b, t, 1, 1, 0, 1;\n"
    "setp.ne.u32 q, %99, 0;\n@q mbarrier.arrive.shared::cta.b64 _, [%98];\n@q mbarrier.arrive.shared::cta.b64 _, [%98];\n@q mbarrier.arrive.shared::cta.b64 _, [%106];\n@q mbarrier.arrive.shared::cta.b64 _, [%106];\n"
    "add.u64 a, %96, 6;\nadd.u64 b, %97, 3*%104;\n"
    "wgmma.mma_async.sync.aligned.m64n192k16.f32.bf16.bf16 {"
      "%0, %1, %2, %3, %4, %5, %6, %7, %8, %9, %10, %11, %12, %13, %14, %15, "
      "%16, %17, %18, %19, %20, %21, %22, %23, %24, %25, %26, %27, %28, %29, %30, %31, "
      "%32, %33, %34, %35, %36, %37, %38, %39, %40, %41, %42, %43, %44, %45, %46, %47, "
      "%48, %49, %50, %51, %52, %53, %54, %55, %56, %57, %58, %59, %60, %61, %62, %63, "
      "%64, %65, %66, %67, %68, %69, %70, %71, %72, %73, %74, %75, %76, %77, %78, %79, "
      "%80, %81, %82, %83, %84, %85, %86, %87, %88, %89, %90, %91, %92, %93, %94, %95"
      "}, a, b, t, 1, 1, 0, 1;\n"
    "wgmma.commit_group.sync.aligned;\n"
    "}\n"
      :
      "+f"(d[0]), "+f"(d[1]), "+f"(d[2]), "+f"(d[3]), "+f"(d[4]), "+f"(d[5]), "+f"(d[6]), "+f"(d[7]),
      "+f"(d[8]), "+f"(d[9]), "+f"(d[10]), "+f"(d[11]), "+f"(d[12]), "+f"(d[13]), "+f"(d[14]), "+f"(d[15]),
      "+f"(d[16]), "+f"(d[17]), "+f"(d[18]), "+f"(d[19]), "+f"(d[20]), "+f"(d[21]), "+f"(d[22]), "+f"(d[23]),
      "+f"(d[24]), "+f"(d[25]), "+f"(d[26]), "+f"(d[27]), "+f"(d[28]), "+f"(d[29]), "+f"(d[30]), "+f"(d[31]),
      "+f"(d[32]), "+f"(d[33]), "+f"(d[34]), "+f"(d[35]), "+f"(d[36]), "+f"(d[37]), "+f"(d[38]), "+f"(d[39]),
      "+f"(d[40]), "+f"(d[41]), "+f"(d[42]), "+f"(d[43]), "+f"(d[44]), "+f"(d[45]), "+f"(d[46]), "+f"(d[47]),
      "+f"(d[48]), "+f"(d[49]), "+f"(d[50]), "+f"(d[51]), "+f"(d[52]), "+f"(d[53]), "+f"(d[54]), "+f"(d[55]),
      "+f"(d[56]), "+f"(d[57]), "+f"(d[58]), "+f"(d[59]), "+f"(d[60]), "+f"(d[61]), "+f"(d[62]), "+f"(d[63]),
      "+f"(d[64]), "+f"(d[65]), "+f"(d[66]), "+f"(d[67]), "+f"(d[68]), "+f"(d[69]), "+f"(d[70]), "+f"(d[71]),
      "+f"(d[72]), "+f"(d[73]), "+f"(d[74]), "+f"(d[75]), "+f"(d[76]), "+f"(d[77]), "+f"(d[78]), "+f"(d[79]),
      "+f"(d[80]), "+f"(d[81]), "+f"(d[82]), "+f"(d[83]), "+f"(d[84]), "+f"(d[85]), "+f"(d[86]), "+f"(d[87]),
      "+f"(d[88]), "+f"(d[89]), "+f"(d[90]), "+f"(d[91]), "+f"(d[92]), "+f"(d[93]), "+f"(d[94]), "+f"(d[95])
      : "l"(da), "l"(db), "r"(rel), "r"(doR), "r"(fa), "r"(pa), "r"(fb), "r"(pb), "n"(BSTEP), "r"(acc), "r"(rela) : "memory");
    else if constexpr (W == 1 && RC == 2 && RA == 1 && D1 == 0) asm volatile(
    "{\n.reg .pred p, q, r, t;\n.reg .b64 a, b;\n.reg .u32 n;\nsetp.ne.b32 t, 1, 0;\nsetp.ne.b32 r, %105, 0;\n"
    "wgmma.mma_async.sync.aligned.m64n192k16.f32.bf16.bf16 {"
      "%0, %1, %2, %3, %4, %5, %6, %7, %8, %9, %10, %11, %12, %13, %14, %15, "
      "%16, %17, %18, %19, %20, %21, %22, %23, %24, %25, %26, %27, %28, %29, %30, %31, "
      "%32, %33, %34, %35, %36, %37, %38, %39, %40, %41, %42, %43, %44, %45, %46, %47, "
      "%48, %49, %50, %51, %52, %53, %54, %55, %56, %57, %58, %59, %60, %61, %62, %63, "
      "%64, %65, %66, %67, %68, %69, %70, %71, %72, %73, %74, %75, %76, %77, %78, %79, "
      "%80, %81, %82, %83, %84, %85, %86, %87, %88, %89, %90, %91, %92, %93, %94, %95"
      "}, %96, %97, r, 1, 1, 0, 1;\n"
    "add.u64 a, %96, 2;\nadd.u64 b, %97, %104;\n"
    "wgmma.mma_async.sync.aligned.m64n192k16.f32.bf16.bf16 {"
      "%0, %1, %2, %3, %4, %5, %6, %7, %8, %9, %10, %11, %12, %13, %14, %15, "
      "%16, %17, %18, %19, %20, %21, %22, %23, %24, %25, %26, %27, %28, %29, %30, %31, "
      "%32, %33, %34, %35, %36, %37, %38, %39, %40, %41, %42, %43, %44, %45, %46, %47, "
      "%48, %49, %50, %51, %52, %53, %54, %55, %56, %57, %58, %59, %60, %61, %62, %63, "
      "%64, %65, %66, %67, %68, %69, %70, %71, %72, %73, %74, %75, %76, %77, %78, %79, "
      "%80, %81, %82, %83, %84, %85, %86, %87, %88, %89, %90, %91, %92, %93, %94, %95"
      "}, a, b, t, 1, 1, 0, 1;\n"
    "wgmma.commit_group.sync.aligned;\nwgmma.wait_group.sync.aligned 1;\n"
    "add.u64 a, %96, 4;\nadd.u64 b, %97, 2*%104;\n"
    "wgmma.mma_async.sync.aligned.m64n192k16.f32.bf16.bf16 {"
      "%0, %1, %2, %3, %4, %5, %6, %7, %8, %9, %10, %11, %12, %13, %14, %15, "
      "%16, %17, %18, %19, %20, %21, %22, %23, %24, %25, %26, %27, %28, %29, %30, %31, "
      "%32, %33, %34, %35, %36, %37, %38, %39, %40, %41, %42, %43, %44, %45, %46, %47, "
      "%48, %49, %50, %51, %52, %53, %54, %55, %56, %57, %58, %59, %60, %61, %62, %63, "
      "%64, %65, %66, %67, %68, %69, %70, %71, %72, %73, %74, %75, %76, %77, %78, %79, "
      "%80, %81, %82, %83, %84, %85, %86, %87, %88, %89, %90, %91, %92, %93, %94, %95"
      "}, a, b, t, 1, 1, 0, 1;\n"
    "setp.ne.u32 q, %99, 0;\n@q mbarrier.arrive.shared::cta.b64 _, [%98];\n@q mbarrier.arrive.shared::cta.b64 _, [%98];\n@q mbarrier.arrive.shared::cta.b64 _, [%106];\n@q mbarrier.arrive.shared::cta.b64 _, [%106];\n"
    "mbarrier.test_wait.parity.shared::cta.b64 p, [%102], %103;\n"
    "add.u64 a, %96, 6;\nadd.u64 b, %97, 3*%104;\n"
    "wgmma.mma_async.sync.aligned.m64n192k16.f32.bf16.bf16 {"
      "%0, %1, %2, %3, %4, %5, %6, %7, %8, %9, %10, %11, %12, %13, %14, %15, "
      "%16, %17, %18, %19, %20, %21, %22, %23, %24, %25, %26, %27, %28, %29, %30, %31, "
      "%32, %33, %34, %35, %36, %37, %38, %39, %40, %41, %42, %43, %44, %45, %46, %47, "
      "%48, %49, %50, %51, %52, %53, %54, %55, %56, %57, %58, %59, %60, %61, %62, %63, "
      "%64, %65, %66, %67, %68, %69, %70, %71, %72, %73, %74, %75, %76, %77, %78, %79, "
      "%80, %81, %82, %83, %84, %85, %86, %87, %88, %89, %90, %91, %92, %93, %94, %95"
      "}, a, b, t, 1, 1, 0, 1;\n"
    "wgmma.commit_group.sync.aligned;\n"
    "@p bra.uni DN;\nmov.u32 n, 0;\nWT: mbarrier.try_wait.parity.shared::cta.b64 p, [%102], %103;\n@p bra.uni DN;\nadd.u32 n, n, 1;\nsetp.lt.u32 p, n, 0x100000;\n@p bra.uni WT;\nDN:\n"
    "}\n"
      :
      "+f"(d[0]), "+f"(d[1]), "+f"(d[2]), "+f"(d[3]), "+f"(d[4]), "+f"(d[5]), "+f"(d[6]), "+f"(d[7]),
      "+f"(d[8]), "+f"(d[9]), "+f"(d[10]), "+f"(d[11]), "+f"(d[12]), "+f"(d[13]), "+f"(d[14]), "+f"(d[15]),
      "+f"(d[16]), "+f"(d[17]), "+f"(d[18]), "+f"(d[19]), "+f"(d[20]), "+f"(d[21]), "+f"(d[22]), "+f"(d[23]),
      "+f"(d[24]), "+f"(d[25]), "+f"(d[26]), "+f"(d[27]), "+f"(d[28]), "+f"(d[29]), "+f"(d[30]), "+f"(d[31]),
      "+f"(d[32]), "+f"(d[33]), "+f"(d[34]), "+f"(d[35]), "+f"(d[36]), "+f"(d[37]), "+f"(d[38]), "+f"(d[39]),
      "+f"(d[40]), "+f"(d[41]), "+f"(d[42]), "+f"(d[43]), "+f"(d[44]), "+f"(d[45]), "+f"(d[46]), "+f"(d[47]),
      "+f"(d[48]), "+f"(d[49]), "+f"(d[50]), "+f"(d[51]), "+f"(d[52]), "+f"(d[53]), "+f"(d[54]), "+f"(d[55]),
      "+f"(d[56]), "+f"(d[57]), "+f"(d[58]), "+f"(d[59]), "+f"(d[60]), "+f"(d[61]), "+f"(d[62]), "+f"(d[63]),
      "+f"(d[64]), "+f"(d[65]), "+f"(d[66]), "+f"(d[67]), "+f"(d[68]), "+f"(d[69]), "+f"(d[70]), "+f"(d[71]),
      "+f"(d[72]), "+f"(d[73]), "+f"(d[74]), "+f"(d[75]), "+f"(d[76]), "+f"(d[77]), "+f"(d[78]), "+f"(d[79]),
      "+f"(d[80]), "+f"(d[81]), "+f"(d[82]), "+f"(d[83]), "+f"(d[84]), "+f"(d[85]), "+f"(d[86]), "+f"(d[87]),
      "+f"(d[88]), "+f"(d[89]), "+f"(d[90]), "+f"(d[91]), "+f"(d[92]), "+f"(d[93]), "+f"(d[94]), "+f"(d[95])
      : "l"(da), "l"(db), "r"(rel), "r"(doR), "r"(fa), "r"(pa), "r"(fb), "r"(pb), "n"(BSTEP), "r"(acc), "r"(rela) : "memory");
    else if constexpr (W == 2 && RC == 2 && RA == 0 && D1 == 0) asm volatile(
    "{\n.reg .pred p, q, r, t;\n.reg .b64 a, b;\n.reg .u32 n;\nsetp.ne.b32 t, 1, 0;\nsetp.ne.b32 r, %105, 0;\n"
    "wgmma.mma_async.sync.aligned.m64n192k16.f32.bf16.bf16 {"
      "%0, %1, %2, %3, %4, %5, %6, %7, %8, %9, %10, %11, %12, %13, %14, %15, "
      "%16, %17, %18, %19, %20, %21, %22, %23, %24, %25, %26, %27, %28, %29, %30, %31, "
      "%32, %33, %34, %35, %36, %37, %38, %39, %40, %41, %42, %43, %44, %45, %46, %47, "
      "%48, %49, %50, %51, %52, %53, %54, %55, %56, %57, %58, %59, %60, %61, %62, %63, "
      "%64, %65, %66, %67, %68, %69, %70, %71, %72, %73, %74, %75, %76, %77, %78, %79, "
      "%80, %81, %82, %83, %84, %85, %86, %87, %88, %89, %90, %91, %92, %93, %94, %95"
      "}, %96, %97, r, 1, 1, 0, 1;\n"
    "add.u64 a, %96, 2;\nadd.u64 b, %97, %104;\n"
    "wgmma.mma_async.sync.aligned.m64n192k16.f32.bf16.bf16 {"
      "%0, %1, %2, %3, %4, %5, %6, %7, %8, %9, %10, %11, %12, %13, %14, %15, "
      "%16, %17, %18, %19, %20, %21, %22, %23, %24, %25, %26, %27, %28, %29, %30, %31, "
      "%32, %33, %34, %35, %36, %37, %38, %39, %40, %41, %42, %43, %44, %45, %46, %47, "
      "%48, %49, %50, %51, %52, %53, %54, %55, %56, %57, %58, %59, %60, %61, %62, %63, "
      "%64, %65, %66, %67, %68, %69, %70, %71, %72, %73, %74, %75, %76, %77, %78, %79, "
      "%80, %81, %82, %83, %84, %85, %86, %87, %88, %89, %90, %91, %92, %93, %94, %95"
      "}, a, b, t, 1, 1, 0, 1;\n"
    "wgmma.commit_group.sync.aligned;\nwgmma.wait_group.sync.aligned 1;\n"
    "add.u64 a, %96, 4;\nadd.u64 b, %97, 2*%104;\n"
    "wgmma.mma_async.sync.aligned.m64n192k16.f32.bf16.bf16 {"
      "%0, %1, %2, %3, %4, %5, %6, %7, %8, %9, %10, %11, %12, %13, %14, %15, "
      "%16, %17, %18, %19, %20, %21, %22, %23, %24, %25, %26, %27, %28, %29, %30, %31, "
      "%32, %33, %34, %35, %36, %37, %38, %39, %40, %41, %42, %43, %44, %45, %46, %47, "
      "%48, %49, %50, %51, %52, %53, %54, %55, %56, %57, %58, %59, %60, %61, %62, %63, "
      "%64, %65, %66, %67, %68, %69, %70, %71, %72, %73, %74, %75, %76, %77, %78, %79, "
      "%80, %81, %82, %83, %84, %85, %86, %87, %88, %89, %90, %91, %92, %93, %94, %95"
      "}, a, b, t, 1, 1, 0, 1;\n"
    "setp.ne.u32 q, %99, 0;\n@q mbarrier.arrive.shared::cta.b64 _, [%98];\n@q mbarrier.arrive.shared::cta.b64 _, [%98];\n"
    "mbarrier.test_wait.parity.shared::cta.b64 p, [%102], %103;\n"
    "mbarrier.test_wait.parity.shared::cta.b64 r, [%100], %101;\nand.pred p, p, r;\n"
    "add.u64 a, %96, 6;\nadd.u64 b, %97, 3*%104;\n"
    "wgmma.mma_async.sync.aligned.m64n192k16.f32.bf16.bf16 {"
      "%0, %1, %2, %3, %4, %5, %6, %7, %8, %9, %10, %11, %12, %13, %14, %15, "
      "%16, %17, %18, %19, %20, %21, %22, %23, %24, %25, %26, %27, %28, %29, %30, %31, "
      "%32, %33, %34, %35, %36, %37, %38, %39, %40, %41, %42, %43, %44, %45, %46, %47, "
      "%48, %49, %50, %51, %52, %53, %54, %55, %56, %57, %58, %59, %60, %61, %62, %63, "
      "%64, %65, %66, %67, %68, %69, %70, %71, %72, %73, %74, %75, %76, %77, %78, %79, "
      "%80, %81, %82, %83, %84, %85, %86, %87, %88, %89, %90, %91, %92, %93, %94, %95"
      "}, a, b, t, 1, 1, 0, 1;\n"
    "wgmma.commit_group.sync.aligned;\n"
    "@p bra.uni DN;\nmov.u32 n, 0;\nWT: mbarrier.try_wait.parity.shared::cta.b64 p, [%102], %103;\nmbarrier.try_wait.parity.shared::cta.b64 r, [%100], %101;\nand.pred p, p, r;\n@p bra.uni DN;\nadd.u32 n, n, 1;\nsetp.lt.u32 p, n, 0x100000;\n@p bra.uni WT;\nDN:\n"
    "}\n"
      :
      "+f"(d[0]), "+f"(d[1]), "+f"(d[2]), "+f"(d[3]), "+f"(d[4]), "+f"(d[5]), "+f"(d[6]), "+f"(d[7]),
      "+f"(d[8]), "+f"(d[9]), "+f"(d[10]), "+f"(d[11]), "+f"(d[12]), "+f"(d[13]), "+f"(d[14]), "+f"(d[15]),
      "+f"(d[16]), "+f"(d[17]), "+f"(d[18]), "+f"(d[19]), "+f"(d[20]), "+f"(d[21]), "+f"(d[22]), "+f"(d[23]),
      "+f"(d[24]), "+f"(d[25]), "+f"(d[26]), "+f"(d[27]), "+f"(d[28]), "+f"(d[29]), "+f"(d[30]), "+f"(d[31]),
      "+f"(d[32]), "+f"(d[33]), "+f"(d[34]), "+f"(d[35]), "+f"(d[36]), "+f"(d[37]), "+f"(d[38]), "+f"(d[39]),
      "+f"(d[40]), "+f"(d[41]), "+f"(d[42]), "+f"(d[43]), "+f"(d[44]), "+f"(d[45]), "+f"(d[46]), "+f"(d[47]),
      "+f"(d[48]), "+f"(d[49]), "+f"(d[50]), "+f"(d[51]), "+f"(d[52]), "+f"(d[53]), "+f"(d[54]), "+f"(d[55]),
      "+f"(d[56]), "+f"(d[57]), "+f"(d[58]), "+f"(d[59]), "+f"(d[60]), "+f"(d[61]), "+f"(d[62]), "+f"(d[63]),
      "+f"(d[64]), "+f"(d[65]), "+f"(d[66]), "+f"(d[67]), "+f"(d[68]), "+f"(d[69]), "+f"(d[70]), "+f"(d[71]),
      "+f"(d[72]), "+f"(d[73]), "+f"(d[74]), "+f"(d[75]), "+f"(d[76]), "+f"(d[77]), "+f"(d[78]), "+f"(d[79]),
      "+f"(d[80]), "+f"(d[81]), "+f"(d[82]), "+f"(d[83]), "+f"(d[84]), "+f"(d[85]), "+f"(d[86]), "+f"(d[87]),
      "+f"(d[88]), "+f"(d[89]), "+f"(d[90]), "+f"(d[91]), "+f"(d[92]), "+f"(d[93]), "+f"(d[94]), "+f"(d[95])
      : "l"(da), "l"(db), "r"(rel), "r"(doR), "r"(fa), "r"(pa), "r"(fb), "r"(pb), "n"(BSTEP), "r"(acc), "r"(rela) : "memory");
    else if constexpr (W == 2 && RC == 2 && RA == 1 && D1 == 0) asm volatile(
    "{\n.reg .pred p, q, r, t;\n.reg .b64 a, b;\n.reg .u32 n;\nsetp.ne.b32 t, 1, 0;\nsetp.ne.b32 r, %105, 0;\n"
    "wgmma.mma_async.sync.aligned.m64n192k16.f32.bf16.bf16 {"
      "%0, %1, %2, %3, %4, %5, %6, %7, %8, %9, %10, %11, %12, %13, %14, %15, "
      "%16, %17, %18, %19, %20, %21, %22, %23, %24, %25, %26, %27, %28, %29, %30, %31, "
      "%32, %33, %34, %35, %36, %37, %38, %39, %40, %41, %42, %43, %44, %45, %46, %47, "
      "%48, %49, %50, %51, %52, %53, %54, %55, %56, %57, %58, %59, %60, %61, %62, %63, "
      "%64, %65, %66, %67, %68, %69, %70, %71, %72, %73, %74, %75, %76, %77, %78, %79, "
      "%80, %81, %82, %83, %84, %85, %86, %87, %88, %89, %90, %91, %92, %93, %94, %95"
      "}, %96, %97, r, 1, 1, 0, 1;\n"
    "add.u64 a, %96, 2;\nadd.u64 b, %97, %104;\n"
    "wgmma.mma_async.sync.aligned.m64n192k16.f32.bf16.bf16 {"
      "%0, %1, %2, %3, %4, %5, %6, %7, %8, %9, %10, %11, %12, %13, %14, %15, "
      "%16, %17, %18, %19, %20, %21, %22, %23, %24, %25, %26, %27, %28, %29, %30, %31, "
      "%32, %33, %34, %35, %36, %37, %38, %39, %40, %41, %42, %43, %44, %45, %46, %47, "
      "%48, %49, %50, %51, %52, %53, %54, %55, %56, %57, %58, %59, %60, %61, %62, %63, "
      "%64, %65, %66, %67, %68, %69, %70, %71, %72, %73, %74, %75, %76, %77, %78, %79, "
      "%80, %81, %82, %83, %84, %85, %86, %87, %88, %89, %90, %91, %92, %93, %94, %95"
      "}, a, b, t, 1, 1, 0, 1;\n"
    "wgmma.commit_group.sync.aligned;\nwgmma.wait_group.sync.aligned 1;\n"
    "add.u64 a, %96, 4;\nadd.u64 b, %97, 2*%104;\n"
    "wgmma.mma_async.sync.aligned.m64n192k16.f32.bf16.bf16 {"
      "%0, %1, %2, %3, %4, %5, %6, %7, %8, %9, %10, %11, %12, %13, %14, %15, "
      "%16, %17, %18, %19, %20, %21, %22, %23, %24, %25, %26, %27, %28, %29, %30, %31, "
      "%32, %33, %34, %35, %36, %37, %38, %39, %40, %41, %42, %43, %44, %45, %46, %47, "
      "%48, %49, %50, %51, %52, %53, %54, %55, %56, %57, %58, %59, %60, %61, %62, %63, "
      "%64, %65, %66, %67, %68, %69, %70, %71, %72, %73, %74, %75, %76, %77, %78, %79, "
      "%80, %81, %82, %83, %84, %85, %86, %87, %88, %89, %90, %91, %92, %93, %94, %95"
      "}, a, b, t, 1, 1, 0, 1;\n"
    "setp.ne.u32 q, %99, 0;\n@q mbarrier.arrive.shared::cta.b64 _, [%98];\n@q mbarrier.arrive.shared::cta.b64 _, [%98];\n@q mbarrier.arrive.shared::cta.b64 _, [%106];\n@q mbarrier.arrive.shared::cta.b64 _, [%106];\n"
    "mbarrier.test_wait.parity.shared::cta.b64 p, [%102], %103;\n"
    "mbarrier.test_wait.parity.shared::cta.b64 r, [%100], %101;\nand.pred p, p, r;\n"
    "add.u64 a, %96, 6;\nadd.u64 b, %97, 3*%104;\n"
    "wgmma.mma_async.sync.aligned.m64n192k16.f32.bf16.bf16 {"
      "%0, %1, %2, %3, %4, %5, %6, %7, %8, %9, %10, %11, %12, %13, %14, %15, "
      "%16, %17, %18, %19, %20, %21, %22, %23, %24, %25, %26, %27, %28, %29, %30, %31, "
      "%32, %33, %34, %35, %36, %37, %38, %39, %40, %41, %42, %43, %44, %45, %46, %47, "
      "%48, %49, %50, %51, %52, %53, %54, %55, %56, %57, %58, %59, %60, %61, %62, %63, "
      "%64, %65, %66, %67, %68, %69, %70, %71, %72, %73, %74, %75, %76, %77, %78, %79, "
      "%80, %81, %82, %83, %84, %85, %86, %87, %88, %89, %90, %91, %92, %93, %94, %95"
      "}, a, b, t, 1, 1, 0, 1;\n"
    "wgmma.commit_group.sync.aligned;\n"
    "@p bra.uni DN;\nmov.u32 n, 0;\nWT: mbarrier.try_wait.parity.shared::cta.b64 p, [%102], %103;\nmbarrier.try_wait.parity.shared::cta.b64 r, [%100], %101;\nand.pred p, p, r;\n@p bra.uni DN;\nadd.u32 n, n, 1;\nsetp.lt.u32 p, n, 0x100000;\n@p bra.uni WT;\nDN:\n"
    "}\n"
      :
      "+f"(d[0]), "+f"(d[1]), "+f"(d[2]), "+f"(d[3]), "+f"(d[4]), "+f"(d[5]), "+f"(d[6]), "+f"(d[7]),
      "+f"(d[8]), "+f"(d[9]), "+f"(d[10]), "+f"(d[11]), "+f"(d[12]), "+f"(d[13]), "+f"(d[14]), "+f"(d[15]),
      "+f"(d[16]), "+f"(d[17]), "+f"(d[18]), "+f"(d[19]), "+f"(d[20]), "+f"(d[21]), "+f"(d[22]), "+f"(d[23]),
      "+f"(d[24]), "+f"(d[25]), "+f"(d[26]), "+f"(d[27]), "+f"(d[28]), "+f"(d[29]), "+f"(d[30]), "+f"(d[31]),
      "+f"(d[32]), "+f"(d[33]), "+f"(d[34]), "+f"(d[35]), "+f"(d[36]), "+f"(d[37]), "+f"(d[38]), "+f"(d[39]),
      "+f"(d[40]), "+f"(d[41]), "+f"(d[42]), "+f"(d[43]), "+f"(d[44]), "+f"(d[45]), "+f"(d[46]), "+f"(d[47]),
      "+f"(d[48]), "+f"(d[49]), "+f"(d[50]), "+f"(d[51]), "+f"(d[52]), "+f"(d[53]), "+f"(d[54]), "+f"(d[55]),
      "+f"(d[56]), "+f"(d[57]), "+f"(d[58]), "+f"(d[59]), "+f"(d[60]), "+f"(d[61]), "+f"(d[62]), "+f"(d[63]),
      "+f"(d[64]), "+f"(d[65]), "+f"(d[66]), "+f"(d[67]), "+f"(d[68]), "+f"(d[69]), "+f"(d[70]), "+f"(d[71]),
      "+f"(d[72]), "+f"(d[73]), "+f"(d[74]), "+f"(d[75]), "+f"(d[76]), "+f"(d[77]), "+f"(d[78]), "+f"(d[79]),
      "+f"(d[80]), "+f"(d[81]), "+f"(d[82]), "+f"(d[83]), "+f"(d[84]), "+f"(d[85]), "+f"(d[86]), "+f"(d[87]),
      "+f"(d[88]), "+f"(d[89]), "+f"(d[90]), "+f"(d[91]), "+f"(d[92]), "+f"(d[93]), "+f"(d[94]), "+f"(d[95])
      : "l"(da), "l"(db), "r"(rel), "r"(doR), "r"(fa), "r"(pa), "r"(fb), "r"(pb), "n"(BSTEP), "r"(acc), "r"(rela) : "memory");
    else if constexpr (W == 0 && RC == 2 && RA == 1 && D1 == 1) asm volatile(
    "{\n.reg .pred p, q, r, t;\n.reg .b64 a, b;\n.reg .u32 n;\nsetp.ne.b32 t, 1, 0;\nsetp.ne.b32 r, %105, 0;\n"
    "wgmma.mma_async.sync.aligned.m64n192k16.f32.bf16.bf16 {"
      "%0, %1, %2, %3, %4, %5, %6, %7, %8, %9, %10, %11, %12, %13, %14, %15, "
      "%16, %17, %18, %19, %20, %21, %22, %23, %24, %25, %26, %27, %28, %29, %30, %31, "
      "%32, %33, %34, %35, %36, %37, %38, %39, %40, %41, %42, %43, %44, %45, %46, %47, "
      "%48, %49, %50, %51, %52, %53, %54, %55, %56, %57, %58, %59, %60, %61, %62, %63, "
      "%64, %65, %66, %67, %68, %69, %70, %71, %72, %73, %74, %75, %76, %77, %78, %79, "
      "%80, %81, %82, %83, %84, %85, %86, %87, %88, %89, %90, %91, %92, %93, %94, %95"
      "}, %96, %97, r, 1, 1, 0, 1;\n"
    "wgmma.commit_group.sync.aligned;\nwgmma.wait_group.sync.aligned 1;\n"
    "add.u64 a, %96, 2;\nadd.u64 b, %97, %104;\n"
    "wgmma.mma_async.sync.aligned.m64n192k16.f32.bf16.bf16 {"
      "%0, %1, %2, %3, %4, %5, %6, %7, %8, %9, %10, %11, %12, %13, %14, %15, "
      "%16, %17, %18, %19, %20, %21, %22, %23, %24, %25, %26, %27, %28, %29, %30, %31, "
      "%32, %33, %34, %35, %36, %37, %38, %39, %40, %41, %42, %43, %44, %45, %46, %47, "
      "%48, %49, %50, %51, %52, %53, %54, %55, %56, %57, %58, %59, %60, %61, %62, %63, "
      "%64, %65, %66, %67, %68, %69, %70, %71, %72, %73, %74, %75, %76, %77, %78, %79, "
      "%80, %81, %82, %83, %84, %85, %86, %87, %88, %89, %90, %91, %92, %93, %94, %95"
      "}, a, b, t, 1, 1, 0, 1;\n"
    "wgmma.commit_group.sync.aligned;\nwgmma.wait_group.sync.aligned 1;\n"
    "add.u64 a, %96, 4;\nadd.u64 b, %97, 2*%104;\n"
    "wgmma.mma_async.sync.aligned.m64n192k16.f32.bf16.bf16 {"
      "%0, %1, %2, %3, %4, %5, %6, %7, %8, %9, %10, %11, %12, %13, %14, %15, "
      "%16, %17, %18, %19, %20, %21, %22, %23, %24, %25, %26, %27, %28, %29, %30, %31, "
      "%32, %33, %34, %35, %36, %37, %38, %39, %40, %41, %42, %43, %44, %45, %46, %47, "
      "%48, %49, %50, %51, %52, %53, %54, %55, %56, %57, %58, %59, %60, %61, %62, %63, "
      "%64, %65, %66, %67, %68, %69, %70, %71, %72, %73, %74, %75, %76, %77, %78, %79, "
      "%80, %81, %82, %83, %84, %85, %86, %87, %88, %89, %90, %91, %92, %93, %94, %95"
      "}, a, b, t, 1, 1, 0, 1;\n"
    "wgmma.commit_group.sync.aligned;\n"
    "setp.ne.u32 q, %99, 0;\n@q mbarrier.arrive.shared::cta.b64 _, [%98];\n@q mbarrier.arrive.shared::cta.b64 _, [%98];\n@q mbarrier.arrive.shared::cta.b64 _, [%106];\n@q mbarrier.arrive.shared::cta.b64 _, [%106];\n"
    "wgmma.wait_group.sync.aligned 1;\n"
    "add.u64 a, %96, 6;\nadd.u64 b, %97, 3*%104;\n"
    "wgmma.mma_async.sync.aligned.m64n192k16.f32.bf16.bf16 {"
      "%0, %1, %2, %3, %4, %5, %6, %7, %8, %9, %10, %11, %12, %13, %14, %15, "
      "%16, %17, %18, %19, %20, %21, %22, %23, %24, %25, %26, %27, %28, %29, %30, %31, "
      "%32, %33, %34, %35, %36, %37, %38, %39, %40, %41, %42, %43, %44, %45, %46, %47, "
      "%48, %49, %50, %51, %52, %53, %54, %55, %56, %57, %58, %59, %60, %61, %62, %63, "
      "%64, %65, %66, %67, %68, %69, %70, %71, %72, %73, %74, %75, %76, %77, %78, %79, "
      "%80, %81, %82, %83, %84, %85, %86, %87, %88, %89, %90, %91, %92, %93, %94, %95"
      "}, a, b, t, 1, 1, 0, 1;\n"
    "wgmma.commit_group.sync.aligned;\n"
    "}\n"
      :
      "+f"(d[0]), "+f"(d[1]), "+f"(d[2]), "+f"(d[3]), "+f"(d[4]), "+f"(d[5]), "+f"(d[6]), "+f"(d[7]),
      "+f"(d[8]), "+f"(d[9]), "+f"(d[10]), "+f"(d[11]), "+f"(d[12]), "+f"(d[13]), "+f"(d[14]), "+f"(d[15]),
      "+f"(d[16]), "+f"(d[17]), "+f"(d[18]), "+f"(d[19]), "+f"(d[20]), "+f"(d[21]), "+f"(d[22]), "+f"(d[23]),
      "+f"(d[24]), "+f"(d[25]), "+f"(d[26]), "+f"(d[27]), "+f"(d[28]), "+f"(d[29]), "+f"(d[30]), "+f"(d[31]),
      "+f"(d[32]), "+f"(d[33]), "+f"(d[34]), "+f"(d[35]), "+f"(d[36]), "+f"(d[37]), "+f"(d[38]), "+f"(d[39]),
      "+f"(d[40]), "+f"(d[41]), "+f"(d[42]), "+f"(d[43]), "+f"(d[44]), "+f"(d[45]), "+f"(d[46]), "+f"(d[47]),
      "+f"(d[48]), "+f"(d[49]), "+f"(d[50]), "+f"(d[51]), "+f"(d[52]), "+f"(d[53]), "+f"(d[54]), "+f"(d[55]),
      "+f"(d[56]), "+f"(d[57]), "+f"(d[58]), "+f"(d[59]), "+f"(d[60]), "+f"(d[61]), "+f"(d[62]), "+f"(d[63]),
      "+f"(d[64]), "+f"(d[65]), "+f"(d[66]), "+f"(d[67]), "+f"(d[68]), "+f"(d[69]), "+f"(d[70]), "+f"(d[71]),
      "+f"(d[72]), "+f"(d[73]), "+f"(d[74]), "+f"(d[75]), "+f"(d[76]), "+f"(d[77]), "+f"(d[78]), "+f"(d[79]),
      "+f"(d[80]), "+f"(d[81]), "+f"(d[82]), "+f"(d[83]), "+f"(d[84]), "+f"(d[85]), "+f"(d[86]), "+f"(d[87]),
      "+f"(d[88]), "+f"(d[89]), "+f"(d[90]), "+f"(d[91]), "+f"(d[92]), "+f"(d[93]), "+f"(d[94]), "+f"(d[95])
      : "l"(da), "l"(db), "r"(rel), "r"(doR), "r"(fa), "r"(pa), "r"(fb), "r"(pb), "n"(BSTEP), "r"(acc), "r"(rela) : "memory");
    else if constexpr (W == 2 && RC == 2 && RA == 1 && D1 == 1) asm volatile(
    "{\n.reg .pred p, q, r, t;\n.reg .b64 a, b;\n.reg .u32 n;\nsetp.ne.b32 t, 1, 0;\nsetp.ne.b32 r, %105, 0;\n"
    "wgmma.mma_async.sync.aligned.m64n192k16.f32.bf16.bf16 {"
      "%0, %1, %2, %3, %4, %5, %6, %7, %8, %9, %10, %11, %12, %13, %14, %15, "
      "%16, %17, %18, %19, %20, %21, %22, %23, %24, %25, %26, %27, %28, %29, %30, %31, "
      "%32, %33, %34, %35, %36, %37, %38, %39, %40, %41, %42, %43, %44, %45, %46, %47, "
      "%48, %49, %50, %51, %52, %53, %54, %55, %56, %57, %58, %59, %60, %61, %62, %63, "
      "%64, %65, %66, %67, %68, %69, %70, %71, %72, %73, %74, %75, %76, %77, %78, %79, "
      "%80, %81, %82, %83, %84, %85, %86, %87, %88, %89, %90, %91, %92, %93, %94, %95"
      "}, %96, %97, r, 1, 1, 0, 1;\n"
    "wgmma.commit_group.sync.aligned;\nwgmma.wait_group.sync.aligned 1;\n"
    "add.u64 a, %96, 2;\nadd.u64 b, %97, %104;\n"
    "wgmma.mma_async.sync.aligned.m64n192k16.f32.bf16.bf16 {"
      "%0, %1, %2, %3, %4, %5, %6, %7, %8, %9, %10, %11, %12, %13, %14, %15, "
      "%16, %17, %18, %19, %20, %21, %22, %23, %24, %25, %26, %27, %28, %29, %30, %31, "
      "%32, %33, %34, %35, %36, %37, %38, %39, %40, %41, %42, %43, %44, %45, %46, %47, "
      "%48, %49, %50, %51, %52, %53, %54, %55, %56, %57, %58, %59, %60, %61, %62, %63, "
      "%64, %65, %66, %67, %68, %69, %70, %71, %72, %73, %74, %75, %76, %77, %78, %79, "
      "%80, %81, %82, %83, %84, %85, %86, %87, %88, %89, %90, %91, %92, %93, %94, %95"
      "}, a, b, t, 1, 1, 0, 1;\n"
    "wgmma.commit_group.sync.aligned;\nwgmma.wait_group.sync.aligned 1;\n"
    "add.u64 a, %96, 4;\nadd.u64 b, %97, 2*%104;\n"
    "wgmma.mma_async.sync.aligned.m64n192k16.f32.bf16.bf16 {"
      "%0, %1, %2, %3, %4, %5, %6, %7, %8, %9, %10, %11, %12, %13, %14, %15, "
      "%16, %17, %18, %19, %20, %21, %22, %23, %24, %25, %26, %27, %28, %29, %30, %31, "
      "%32, %33, %34, %35, %36, %37, %38, %39, %40, %41, %42, %43, %44, %45, %46, %47, "
      "%48, %49, %50, %51, %52, %53, %54, %55, %56, %57, %58, %59, %60, %61, %62, %63, "
      "%64, %65, %66, %67, %68, %69, %70, %71, %72, %73, %74, %75, %76, %77, %78, %79, "
      "%80, %81, %82, %83, %84, %85, %86, %87, %88, %89, %90, %91, %92, %93, %94, %95"
      "}, a, b, t, 1, 1, 0, 1;\n"
    "wgmma.commit_group.sync.aligned;\n"
    "setp.ne.u32 q, %99, 0;\n@q mbarrier.arrive.shared::cta.b64 _, [%98];\n@q mbarrier.arrive.shared::cta.b64 _, [%98];\n@q mbarrier.arrive.shared::cta.b64 _, [%106];\n@q mbarrier.arrive.shared::cta.b64 _, [%106];\n"
    "mbarrier.test_wait.parity.shared::cta.b64 p, [%102], %103;\n"
    "mbarrier.test_wait.parity.shared::cta.b64 r, [%100], %101;\nand.pred p, p, r;\n"
    "wgmma.wait_group.sync.aligned 1;\n"
    "add.u64 a, %96, 6;\nadd.u64 b, %97, 3*%104;\n"
    "wgmma.mma_async.sync.aligned.m64n192k16.f32.bf16.bf16 {"
      "%0, %1, %2, %3, %4, %5, %6, %7, %8, %9, %10, %11, %12, %13, %14, %15, "
      "%16, %17, %18, %19, %20, %21, %22, %23, %24, %25, %26, %27, %28, %29, %30, %31, "
      "%32, %33, %34, %35, %36, %37, %38, %39, %40, %41, %42, %43, %44, %45, %46, %47, "
      "%48, %49, %50, %51, %52, %53, %54, %55, %56, %57, %58, %59, %60, %61, %62, %63, "
      "%64, %65, %66, %67, %68, %69, %70, %71, %72, %73, %74, %75, %76, %77, %78, %79, "
      "%80, %81, %82, %83, %84, %85, %86, %87, %88, %89, %90, %91, %92, %93, %94, %95"
      "}, a, b, t, 1, 1, 0, 1;\n"
    "wgmma.commit_group.sync.aligned;\n"
    "@p bra.uni DN;\nmov.u32 n, 0;\nWT: mbarrier.try_wait.parity.shared::cta.b64 p, [%102], %103;\nmbarrier.try_wait.parity.shared::cta.b64 r, [%100], %101;\nand.pred p, p, r;\n@p bra.uni DN;\nadd.u32 n, n, 1;\nsetp.lt.u32 p, n, 0x100000;\n@p bra.uni WT;\nDN:\n"
    "}\n"
      :
      "+f"(d[0]), "+f"(d[1]), "+f"(d[2]), "+f"(d[3]), "+f"(d[4]), "+f"(d[5]), "+f"(d[6]), "+f"(d[7]),
      "+f"(d[8]), "+f"(d[9]), "+f"(d[10]), "+f"(d[11]), "+f"(d[12]), "+f"(d[13]), "+f"(d[14]), "+f"(d[15]),
      "+f"(d[16]), "+f"(d[17]), "+f"(d[18]), "+f"(d[19]), "+f"(d[20]), "+f"(d[21]), "+f"(d[22]), "+f"(d[23]),
      "+f"(d[24]), "+f"(d[25]), "+f"(d[26]), "+f"(d[27]), "+f"(d[28]), "+f"(d[29]), "+f"(d[30]), "+f"(d[31]),
      "+f"(d[32]), "+f"(d[33]), "+f"(d[34]), "+f"(d[35]), "+f"(d[36]), "+f"(d[37]), "+f"(d[38]), "+f"(d[39]),
      "+f"(d[40]), "+f"(d[41]), "+f"(d[42]), "+f"(d[43]), "+f"(d[44]), "+f"(d[45]), "+f"(d[46]), "+f"(d[47]),
      "+f"(d[48]), "+f"(d[49]), "+f"(d[50]), "+f"(d[51]), "+f"(d[52]), "+f"(d[53]), "+f"(d[54]), "+f"(d[55]),
      "+f"(d[56]), "+f"(d[57]), "+f"(d[58]), "+f"(d[59]), "+f"(d[60]), "+f"(d[61]), "+f"(d[62]), "+f"(d[63]),
      "+f"(d[64]), "+f"(d[65]), "+f"(d[66]), "+f"(d[67]), "+f"(d[68]), "+f"(d[69]), "+f"(d[70]), "+f"(d[71]),
      "+f"(d[72]), "+f"(d[73]), "+f"(d[74]), "+f"(d[75]), "+f"(d[76]), "+f"(d[77]), "+f"(d[78]), "+f"(d[79]),
      "+f"(d[80]), "+f"(d[81]), "+f"(d[82]), "+f"(d[83]), "+f"(d[84]), "+f"(d[85]), "+f"(d[86]), "+f"(d[87]),
      "+f"(d[88]), "+f"(d[89]), "+f"(d[90]), "+f"(d[91]), "+f"(d[92]), "+f"(d[93]), "+f"(d[94]), "+f"(d[95])
      : "l"(da), "l"(db), "r"(rel), "r"(doR), "r"(fa), "r"(pa), "r"(fb), "r"(pb), "n"(BSTEP), "r"(acc), "r"(rela) : "memory");
    else static_assert(W < 0, "variant not generated");
  }
};

#define HPC 1
#define PF_W 0
#define YTAG 2
#define YD 600
#define PP 0
#define PPC 0
#define ZPD 0
#define CL 8
#define XSD 400
#define CSD 600
#define XP 0
#define KV2T 2000
#define LSD 800
#define TP_T 5000
#define HVY 0
#define HE 0
#define STG 2
#define LKI 14
#define NPRE 2
#define GO_D 0
#define GP 0
#define GO 200
#define XR 0
#define FO 0
#define ARV 1
#define FOLD 0
#define FV 0
#define GDL 0
#define EARLY 0
#define HNF 0
#define PF2_D 200
#define PF2_Z -1
#define PF2_W 2500
#define XL 0
#define XPF 1
#define KV_T0 4000
#define GATE 0
#define PAUSE 0
#define SEG1 4
#define ZW 300
#define HK1 1
#define HOLD 28
#define BPART 1
#define LEAD 2
#define HA 0
#define HD 300
#define ROT 0
#define CSI 9
#define PF_T 11000
#define PF_D 600
#define PF_N 1
#define HP0 3500
#define HPD 450
#define D2 4
#define NSLEEP 100
#define MAP 4
#define ST_YIELD 1

namespace {

constexpr int kS = 2048, kD = 640, kF = 1536;
constexpr int A_SLOT = 8192, B_SLOT = 24576, W_SLOT = 20480;
constexpr int OFF_A = 0;
constexpr int OFF_B = OFF_A + 10 * A_SLOT;
constexpr int XB_PL = 2112;
constexpr int CV_KE = 4224, CV_KO = CV_KE + 4160;
constexpr int CV_SZ = CV_KO + 4160;
constexpr int OFF_CV = OFF_B + 5 * B_SLOT;
constexpr int OFF_CS = OFF_CV + 2 * CV_SZ;
constexpr int OFF_XS = OFF_CS + 1536;
constexpr int OFF_BAR = OFF_XS + 512;
constexpr int SMEM_BYTES = OFF_BAR + 512;
static_assert(SMEM_BYTES <= 232448, "smem");
constexpr int OFF_RT = OFF_CS + 768;
constexpr int BAR_AF = OFF_BAR, BAR_BF = OFF_BAR + 8 * 10, BAR_WF = OFF_BAR + 8 * 15, BAR_ST = OFF_BAR + 8 * 21, BAR_XF = OFF_BAR + 8 * 23;
constexpr int BAR_ZP = OFF_BAR + 8 * 25, BAR_DUMMY = OFF_BAR + 8 * 27, BAR_PART = OFF_BAR + 8 * 28, BAR_WO = OFF_BAR + 8 * 29;
constexpr int BAR_YT = OFF_BAR + 8 * 30, BAR_KV2 = OFF_BAR + 8 * 31, BAR_XS = OFF_BAR + 8 * 32, BAR_HOLD = OFF_BAR + 8 * 33, BAR_ZG = OFF_BAR + 8 * 34;
constexpr int OFF_TAG = OFF_BAR + 8 * 35;
constexpr int BAR_HV = OFF_BAR + 8 * 36;
constexpr int BAR_HR = BAR_HV + 64;
constexpr int BAR_XL = OFF_CS - 16;
constexpr int BAR_AE = OFF_BAR + 8 * 45, BAR_BE = OFF_BAR + 8 * 53, BAR_WE = OFF_BAR + 8 * 58;
constexpr int NB_WG = 1, NB_G1 = 3, NB_WO = 4, NB_CD = 5, NB_Z = 6, NB_C = 7, NB_KU = 8, NB_SV = 9, NB_PC = 11, NB_KF = 12, NB_G1D = 13, NB_KU2 = 14, NB_KL = 15;

#define NB_SV2(h) ((h) ? NB_KU2 : NB_KU)

constexpr int CNT_KV = 0, CNT_WO = 4, CNT_ZT = CL, CNT_Z = CL + 2, CNT_Y = CL + 4;
struct Scratch {
  uint8_t kvx[kD * 4096];
  uint8_t z2[4 * 32 * 24576];
  uint8_t h[32 * 12 * 8192];
  uint8_t wo[4 * 12 * 20480];
  uint8_t y[kD * 4096];
  uint4 zstat[32 * 128];
  uint2 xstat[kS];
  uint32_t colsum[kF];
  uint32_t cnt[64];
  uint32_t hflag[32 * 32];
  uint32_t epoch[136];

};
__device__ __align__(1024) Scratch g_scr;
#define TSP
#define TSA
#define TR(i)
#define STAMP(i)
#define STAMPE(i)
#define STAMP2(i)
#define STAMPW(i)

struct Params {
  Scratch* scr;
  int by_smid;
  const __nv_bfloat16 *x, *k, *v, *shift, *ssmk, *ssmD, *wsp, *bsp, *wout;
  __nv_bfloat16* out;
  CUtensorMap tmX, tmW, tmWsp, tmY, tmKV;
  uint16_t job[132];
};

__device__ __forceinline__ uint64_t mkdesc(uint32_t addr, uint32_t lbo, uint32_t sbo, uint32_t swz) {
  return (uint64_t)((addr & 0x3FFFF) >> 4) | ((uint64_t)(lbo >> 4) << 16) | ((uint64_t)(sbo >> 4) << 32) | ((uint64_t)swz << 62);
}
#define WG_FENCE() asm volatile("wgmma.fence.sync.aligned;" ::: "memory")
#define WG_COMMIT() asm volatile("wgmma.commit_group.sync.aligned;" ::: "memory")
#define WG_WAIT(n) asm volatile("wgmma.wait_group.sync.aligned %0;" ::"n"(n) : "memory")
template <int N> __device__ __forceinline__ void acc_fence(float* d) {
#pragma unroll
  for (int i = 0; i < N; i++) asm volatile("" : "+f"(d[i])::"memory");
}
__device__ __forceinline__ void mbar_init(uint32_t bar, int cnt) { asm volatile("mbarrier.init.shared::cta.b64 [%0], %1;" ::"r"(bar), "r"(cnt) : "memory"); }
__device__ __forceinline__ void mbar_expect(uint32_t bar, uint32_t bytes) { asm volatile("mbarrier.arrive.expect_tx.shared::cta.b64 _, [%0], %1;" ::"r"(bar), "r"(bytes) : "memory"); }
__device__ __forceinline__ void mbar_arrive(uint32_t bar) { asm volatile("mbarrier.arrive.shared::cta.b64 _, [%0];" ::"r"(bar) : "memory"); }
__device__ __forceinline__ void mbar_arrive_if(uint32_t bar, bool c) {
  asm volatile("{\n.reg .pred p;\nsetp.ne.u32 p, %1, 0;\n@p mbarrier.arrive.shared::cta.b64 _, [%0];\n}\n" ::"r"(bar), "r"((uint32_t)c) : "memory");
}
__device__ __forceinline__ bool mbar_try(uint32_t bar, uint32_t parity) {
  uint32_t ok;
  asm volatile("{\n.reg .pred p;\nmbarrier.try_wait.parity.shared::cta.b64 p, [%1], %2;\nselp.u32 %0, 1, 0, p;\n}\n" : "=r"(ok) : "r"(bar), "r"(parity) : "memory");
  return ok;
}
__device__ __forceinline__ void die() { asm volatile("st.volatile.global.u32 [%0], %1;" ::"l"(0ull), "r"(0) : "memory"); }
#define GALL 0
template <bool G = false> __device__ __forceinline__ void spin_guard(uint32_t& n, uint32_t = 0) {
  if (G || GALL == 1) { if (++n == (1u << 20)) die(); }
  else if (GALL == 2) __nanosleep(0);
  else if (GALL == 3) __syncwarp();
}
template <bool G = false> __device__ __forceinline__ void mbar_wait(uint32_t bar, uint32_t parity) {
  uint32_t t0 = 0;
#pragma unroll 1
  while (!mbar_try(bar, parity)) spin_guard<G>(t0, bar);
}
__device__ __forceinline__ void mbar_wait2(uint32_t b0, uint32_t p0, uint32_t b1, uint32_t p1) { mbar_wait(b0, p0); mbar_wait(b1, p1); }
__device__ __forceinline__ int tid_now() { int v; asm volatile("mov.u32 %0, %%tid.x;" : "=r"(v)); return v & 127; }
__device__ __forceinline__ bool elect_one() {
  uint32_t p;
  asm volatile("{\n.reg .pred P;\nelect.sync _|P, 0xffffffff;\nselp.u32 %0, 1, 0, P;\n}\n" : "=r"(p));
  return p;
}
__device__ __forceinline__ void bar_sync(int id, int n) { asm volatile("bar.sync %0, %1;" ::"r"(id), "r"(n) : "memory"); }
__device__ __forceinline__ void bar_arrive(int id, int n) { asm volatile("bar.arrive %0, %1;" ::"r"(id), "r"(n) : "memory"); }
__device__ __forceinline__ void fence_async_smem() { asm volatile("fence.proxy.async.shared::cta;" ::: "memory"); }
__device__ __forceinline__ void bulk_g2s(uint32_t dst, const void* src, uint32_t bytes, uint32_t bar) {
  asm volatile("cp.async.bulk.shared::cluster.global.mbarrier::complete_tx::bytes [%0], [%1], %2, [%3];" ::"r"(dst), "l"(src), "r"(bytes), "r"(bar) : "memory");
}
__device__ __forceinline__ void bulk_s2g(void* dst, uint32_t src, uint32_t bytes) {
  asm volatile("cp.async.bulk.global.shared::cta.bulk_group [%0], [%1], %2;" ::"l"(dst), "r"(src), "r"(bytes) : "memory");
}
__device__ __forceinline__ void tma2d(uint32_t dst, const CUtensorMap* m, int c0, int c1, uint32_t bar) {
  asm volatile("cp.async.bulk.tensor.2d.shared::cluster.global.mbarrier::complete_tx::bytes [%0], [%1, {%3, %4}], [%2];" ::"r"(dst), "l"(m), "r"(bar), "r"(c0), "r"(c1) : "memory");
}
__device__ __forceinline__ void tma3d(uint32_t dst, const CUtensorMap* m, int c0, int c1, int c2, uint32_t bar) {
  asm volatile("cp.async.bulk.tensor.3d.shared::cluster.global.mbarrier::complete_tx::bytes [%0], [%1, {%3, %4, %5}], [%2];" ::"r"(dst), "l"(m), "r"(bar), "r"(c0), "r"(c1), "r"(c2) : "memory");
}
__device__ __forceinline__ uint4 ld_ll4(const void* p) {
  uint64_t a, b;
  asm volatile("ld.relaxed.gpu.global.v2.u64 {%0,%1}, [%2];" : "=l"(a), "=l"(b) : "l"(p) : "memory");
  return make_uint4((uint32_t)a, (uint32_t)(a >> 32), (uint32_t)b, (uint32_t)(b >> 32));
}
__device__ __forceinline__ void st_ll4(void* p, uint32_t a, uint32_t b, uint32_t c, uint32_t d) {
  asm volatile("st.relaxed.gpu.global.v2.u64 [%0], {%1,%2};" ::"l"(p), "l"(a | ((uint64_t)b << 32)), "l"(c | ((uint64_t)d << 32)) : "memory");
}
__device__ __forceinline__ void st_ll2(void* p, uint32_t a, uint32_t b) { asm volatile("st.relaxed.gpu.global.u64 [%0], %1;" ::"l"(p), "l"(a | ((uint64_t)b << 32)) : "memory"); }
__device__ __forceinline__ void wgmma_colsum(float* d, uint64_t da, uint64_t db) {
  asm volatile("{\n.reg .pred p;\nsetp.ne.b32 p, 1, 0;\nwgmma.mma_async.sync.aligned.m64n8k16.f32.bf16.bf16 {%0, %1, %2, %3}, %4, %5, p, 1, 1, 1, 0;\n}\n"
               : "+f"(d[0]), "+f"(d[1]), "+f"(d[2]), "+f"(d[3]) : "l"(da), "l"(db));
}
__device__ __forceinline__ void prefetch_l2(const void* p) { asm volatile("prefetch.global.L2 [%0];" ::"l"(p)); }
template <bool SLEEP = true> __device__ __forceinline__ void pace(uint32_t& t, uint32_t dt) {
  t += dt;
  while ((int32_t)((uint32_t)clock() - t) < 0) { if (SLEEP) __nanosleep(NSLEEP); }
}
__device__ __forceinline__ void red_release(uint32_t* p) { asm volatile("red.release.gpu.global.add.u32 [%0], 1;" ::"l"(p) : "memory"); }
__device__ __forceinline__ uint4 ldg4(const void* p) { uint4 v; asm volatile("ld.global.v4.u32 {%0,%1,%2,%3}, [%4];" : "=r"(v.x), "=r"(v.y), "=r"(v.z), "=r"(v.w) : "l"(p) : "memory"); return v; }
__device__ __forceinline__ uint32_t ldg1(const void* p) { uint32_t v; asm volatile("ld.global.u32 %0, [%1];" : "=r"(v) : "l"(p) : "memory"); return v; }
__device__ __forceinline__ void stg4_if(void* p, uint32_t a, uint32_t b, uint32_t c, uint32_t d, bool on) {
  asm volatile("{\n.reg .pred p;\nsetp.ne.u32 p, %5, 0;\n@p st.global.v4.u32 [%0], {%1,%2,%3,%4};\n}\n" ::"l"(p), "r"(a), "r"(b), "r"(c), "r"(d), "r"((uint32_t)on) : "memory");
}
template <int OFF> __device__ __forceinline__ uint32_t lds32(uint32_t a) { uint32_t v; asm volatile("ld.shared.u32 %0, [%1+%2];" : "=r"(v) : "r"(a), "n"(OFF)); return v; }
__device__ __forceinline__ uint4 lds128(uint32_t a) { uint4 v; asm volatile("ld.shared.v4.u32 {%0,%1,%2,%3}, [%4];" : "=r"(v.x), "=r"(v.y), "=r"(v.z), "=r"(v.w) : "r"(a) : "memory"); return v; }
__device__ __forceinline__ float2 lds64f(uint32_t a) { float2 v; asm volatile("ld.shared.v2.f32 {%0,%1}, [%2];" : "=f"(v.x), "=f"(v.y) : "r"(a) : "memory"); return v; }
__device__ __forceinline__ void sts64f(uint32_t a, float x, float y) { asm volatile("st.shared.v2.f32 [%0], {%1,%2};" ::"r"(a), "f"(x), "f"(y) : "memory"); }
__device__ __forceinline__ void sts32(uint32_t a, uint32_t x) { asm volatile("st.shared.u32 [%0], %1;" ::"r"(a), "r"(x) : "memory"); }
__device__ __forceinline__ void sts128(uint32_t a, uint32_t x, uint32_t y, uint32_t z, uint32_t w) { asm volatile("st.shared.v4.u32 [%0], {%1,%2,%3,%4};" ::"r"(a), "r"(x), "r"(y), "r"(z), "r"(w) : "memory"); }
__device__ __forceinline__ void stsm4(uint32_t a, uint32_t r0, uint32_t r1, uint32_t r2, uint32_t r3) {
  asm volatile("stmatrix.sync.aligned.m8n8.x4.shared.b16 [%0], {%1,%2,%3,%4};" ::"r"(a), "r"(r0), "r"(r1), "r"(r2), "r"(r3) : "memory");
}
__device__ __forceinline__ void stsm4t(uint32_t a, uint32_t r0, uint32_t r1, uint32_t r2, uint32_t r3) {
  asm volatile("stmatrix.sync.aligned.m8n8.x4.trans.shared.b16 [%0], {%1,%2,%3,%4};" ::"r"(a), "r"(r0), "r"(r1), "r"(r2), "r"(r3) : "memory");
}
__device__ __forceinline__ void ldsm4t(uint32_t* r, uint32_t a) {
  asm volatile("ldmatrix.sync.aligned.m8n8.x4.trans.shared.b16 {%0,%1,%2,%3}, [%4];" : "=r"(r[0]), "=r"(r[1]), "=r"(r[2]), "=r"(r[3]) : "r"(a) : "memory");
}
__device__ __forceinline__ uint32_t pack2(float lo, float hi) { uint32_t r; asm("cvt.rn.bf16x2.f32 %0, %1, %2;" : "=r"(r) : "f"(hi), "f"(lo)); return r; }
__device__ __forceinline__ float bf_lo(uint32_t u) { return __uint_as_float(u << 16); }
__device__ __forceinline__ float bf_hi(uint32_t u) { return __uint_as_float(u & 0xffff0000u); }
__device__ __forceinline__ float tanh_fast(float x) { float y; asm("tanh.approx.f32 %0, %1;" : "=f"(y) : "f"(x)); return y; }
__device__ __forceinline__ uint32_t hmul2(uint32_t a, uint32_t b) { uint32_t r; asm("mul.rn.bf16x2 %0, %1, %2;" : "=r"(r) : "r"(a), "r"(b)); return r; }
__device__ __forceinline__ uint32_t hfma2(uint32_t a, uint32_t b, uint32_t c) { uint32_t r; asm("fma.rn.bf16x2 %0, %1, %2, %3;" : "=r"(r) : "r"(a), "r"(b), "r"(c)); return r; }
__device__ __forceinline__ uint32_t prmt(uint32_t a, uint32_t b, uint32_t s) { return __byte_perm(a, b, s); }

__device__ __forceinline__ uint32_t ld_relaxed(const uint32_t* p) { uint32_t v; asm volatile("ld.relaxed.gpu.global.u32 %0, [%1];" : "=r"(v) : "l"(p) : "memory"); return v; }
__device__ __forceinline__ void acquire_fence() { asm volatile("fence.acquire.gpu;\nfence.proxy.async.global;" ::: "memory"); }
__device__ __forceinline__ uint32_t load_epoch(const Params& p, int idx, int lane) { return ld_relaxed(&p.scr->epoch[idx + (((lane * lane) & 3) == 2 ? 1 : 0)]); }
template <bool G, int DT, class T, class L, class C>
__device__ __forceinline__ T poll3(L load, C ok) {
  uint32_t t0 = 0;
  T a = load();
#pragma unroll 1
  while (!__all_sync(0xffffffff, ok(a))) { spin_guard<G>(t0); if (DT) __nanosleep(DT); a = load(); }
  return a;
}
__device__ __forceinline__ void poll_flags4(const uint32_t* flags, uint32_t tag, int lane) {
  poll3<false, PPC, uint32_t>([&]() { return ld_relaxed(flags + (lane & 3) * 8); }, [&](uint32_t v) { return v == tag; });
  acquire_fence();
}
__device__ __forceinline__ void st_relaxed(uint32_t* p, uint32_t v) { asm volatile("st.relaxed.gpu.global.u32 [%0], %1;" ::"l"(p), "r"(v) : "memory"); }
__device__ __forceinline__ uint32_t tag8(uint32_t tag) { return (tag & 127) | 128; }
__device__ __forceinline__ uint32_t tagged(float v, uint32_t t8) { return (__float_as_uint(v) & ~255u) | t8; }
__device__ __forceinline__ void reset_sector(uint32_t* f) { st_ll4(f, 0, 0, 0, 0); st_ll4(f + 4, 0, 0, 0, 0); }
__device__ __forceinline__ uint64_t gtime() { uint64_t t; asm volatile("mov.u64 %0, %%globaltimer;" : "=l"(t)); return t; }
__device__ __forceinline__ void arrive_timed(uint32_t* cnt) {
  asm volatile("red.relaxed.gpu.global.max.u64 [%0], %1;\nred.relaxed.gpu.global.add.u32 [%0+8], 1;" ::"l"(cnt + CNT_ZT), "l"(gtime()) : "memory");
}
__device__ __forceinline__ void wait_timed(const uint32_t* cnt, uint32_t target) {
  uint32_t t0 = 0;
  uint4 v;
#pragma unroll 1
  while (true) {
    v = ld_ll4(cnt + CNT_ZT);
    if (__all_sync(0xffffffff, v.z == target)) break;
    spin_guard<true>(t0);
  }
  acquire_fence();
  const uint32_t go = v.x + GO_D;
#pragma unroll 1
  while ((int32_t)((uint32_t)gtime() - go) < 0) spin_guard<true>(t0);
}
template <bool G = false> __device__ __forceinline__ void poll_counter(const uint32_t* cnt, uint32_t target) {
  poll3<G, PPC, uint32_t>([&]() { return ld_relaxed(cnt); }, [&](uint32_t v) { return v == target; });
  acquire_fence();
}

__device__ __forceinline__ uint32_t hadd2(uint32_t a, uint32_t b) { uint32_t r; asm("add.rn.bf16x2 %0, %1, %2;" : "=r"(r) : "r"(a), "r"(b)); return r; }
__device__ __forceinline__ uint32_t htanh2(uint32_t a) { uint32_t r; asm("tanh.approx.bf16x2 %0, %1;" : "=r"(r) : "r"(a)); return r; }
__device__ __forceinline__ void red_relaxed(uint32_t* p) { asm volatile("red.relaxed.gpu.global.add.u32 [%0], 1;" ::"l"(p) : "memory"); }
__device__ __forceinline__ void bulk_commit_wait() { asm volatile("cp.async.bulk.commit_group;\ncp.async.bulk.wait_group 0;" ::: "memory"); }

__device__ __forceinline__ int g3_block(int cb, int it) { return it < 3 ? cb * 3 + it : (it - 3 < cb * 3 ? it - 3 : it); }

#define GSTAMP(m, i)
struct NoHook { __device__ __forceinline__ void operator()(int = 0) const {} };
template <int N, int MODE, class F = NoHook, class F0 = NoHook>
__device__ __forceinline__ void gemm_seg(float* d, uint32_t sb, uint64_t db0, int i0, int i1, int s, uint32_t pb, uint32_t doR, uint32_t acc TSP, F hook = F(), F0 pre = F0()) {
  constexpr bool G3 = MODE == 2 || MODE == 4, RA = MODE == 1 || MODE == 3;
  constexpr int W = MODE <= 2 ? 2 : 1, RC = MODE == 2 ? 1 : 2, NS = G3 ? 6 : 5, BSTEP = G3 ? 320 : 128;
  const uint64_t da0 = mkdesc(sb + OFF_A, 16, 1024, 1);
  auto sa = [](int i) { return MODE == 1 ? (i + 3) & 7 : (G3 && i >= 9 ? i - 9 : i); };
  auto fa = [&](int i) { return sb + (MODE == 2 ? (i < 3 ? BAR_HR : BAR_HV + 8 * (i - 3)) : BAR_AF + 8 * sa(i)); };
  auto pa = [](int i) { return MODE == 1 ? ((i >> 3) & 1) ^ 1 : MODE == 2 && i >= 9; };
  auto fb = [&](int s_) { return sb + (G3 ? BAR_WF : BAR_BF) + 8 * s_; };
  auto db = [&](int s_) { return db0 + (G3 ? (s_ >= 3 ? s_ - 3 : s_ + 3) * (W_SLOT >> 4) : s_ * (B_SLOT >> 4)); };
  const uint32_t dummy = sb + BAR_DUMMY;
  auto ea = [&](int i) { return MODE == 3 && i >= 8 ? dummy : sb + BAR_AE + 8 * sa(i); };
  uint32_t rel = dummy, rela = dummy;
  acc_fence<N / 2>(d);
  pre();
  if (W == 2) mbar_wait(fa(i0), pa(i0));
  mbar_wait(fb(s), pb);
  WG_FENCE();
#pragma unroll 1
  for (int i = i0; i < i1 - 1; i++) {
    GSTAMP(MODE, i);
    const int n = s + 1 == NS ? 0 : s + 1;
    if (n == 0) pb ^= 1;
    KB<N>::template run<W, RC, RA, BSTEP, MODE == 1 && D2 == 1>(d, da0 + sa(i) * (A_SLOT >> 4), db(s), rel, rela, doR, fa(i + 1), pa(i + 1), fb(n), pb, acc);
    rel = G3 ? (i < 6 ? sb + BAR_WE + 8 * s : dummy) : sb + BAR_BE + 8 * s;
    rela = ea(i);
    s = n;
    acc = 1;
  }
  hook();
  GSTAMP(MODE, i1 - 1);
  KB<N>::template run<0, RC, RA, BSTEP, MODE == 1 && D2 == 1>(d, da0 + sa(i1 - 1) * (A_SLOT >> 4), db(s), rel, rela, doR, 0, 0, 0, 0, 1);
  WG_WAIT(0);
  GSTAMP(MODE, i1);
  acc_fence<N / 2>(d);
  if (MODE != 2) {
    rel = sb + (G3 ? BAR_WE : BAR_BE) + 8 * s;
    mbar_arrive_if(rel, doR);
    mbar_arrive_if(rel, doR);
    if (RA) { mbar_arrive_if(ea(i1 - 1), doR); mbar_arrive_if(ea(i1 - 1), doR); }
  }
}

__device__ __forceinline__ uint32_t val_off(int lane) { return lane * 32 + ((lane >> 2) & 1) * 16 + (lane >> 3) * 4; }
template <int NK, int PAD = 0, class F>
__device__ __forceinline__ void validate(uint32_t a, uint32_t par, uint32_t rt, F reload) {
  uint32_t t0 = 0;
#pragma unroll 1
  while (true) {
    uint32_t v[NK], any = 0;
#pragma unroll
    for (int i = 0; i < NK; i++) asm volatile("ld.shared.u32 %0, [%1];" : "=r"(v[i]) : "r"(a + i * 1024 + (i >> 1) * PAD) : "memory");
#pragma unroll
    for (int i = 0; i < NK; i++) any |= v[i] ^ par;
    if (!__any_sync(0xffffffff, any & 1)) break;
    spin_guard(t0);
    fence_async_smem();
    __syncwarp();
    if (elect_one()) { mbar_init(rt, 1); fence_async_smem(); mbar_expect(rt, NK * 1024); reload(); }
    __syncwarp();
    mbar_wait(rt, 0);
    __syncwarp();
    if (elect_one()) asm volatile("mbarrier.inval.shared::cta.b64 [%0];" ::"r"(rt) : "memory");
  }
}
__device__ __forceinline__ uint32_t swz_base(uint32_t img, int w, int lane) { return img + (w * 16 + (lane & 15)) * 128 + (((lane >> 4) ^ lane) & 7) * 16; }

template <bool STATS>
__device__ __forceinline__ void gelu_tile(const float* d, uint32_t* z, float* st, uint32_t cs0, float2 s0, float2 s1, uint32_t done) {
  const float kA = 0.7978845608028654f, kB = 0.7978845608028654f * 0.044715f;
  const float ra = STATS || !FOLD ? s0.y : 4.f, rb = STATS || !FOLD ? s1.y : 4.f;
  const float a1 = kA * ra, a3 = kB * ra * ra * ra, b1 = kA * rb, b3 = kB * rb * rb * rb;
  const uint32_t c1[2] = {pack2(a1, a1), pack2(b1, b1)}, c3[2] = {pack2(a3, a3), pack2(b3, b3)};
  const float m[2] = {-s0.x, -s1.x}, c[2] = {0.25f * s0.y, 0.25f * s1.y};
  uint32_t S[2][2], Q[2][2];
#pragma unroll
  for (int j = 0; j < 24; j++) {
    if (!STATS && j && j % 6 == 0) mbar_wait(done, 0);
    const float2 cs = lds64f(cs0 + j * 32);
#pragma unroll
    for (int r = 0; r < 2; r++) {
      const float v0 = fmaf(m[r], cs.x, d[4 * j + 2 * r]), v1 = fmaf(m[r], cs.y, d[4 * j + 2 * r + 1]);
      const uint32_t v = STATS || !FOLD ? pack2(v0, v1) : pack2(v0 * c[r], v1 * c[r]);
      uint32_t y = (XP & 1) && !STATS ? v : hfma2(v, htanh2(hmul2(v, hfma2(hmul2(v, v), c3[r], c1[r]))), v);
      asm volatile("" : "+r"(y));
      z[2 * j + r] = y;
      if (STATS) {
        S[r][j & 1] = j < 2 ? y : hadd2(S[r][j & 1], y);
        Q[r][j & 1] = j < 2 ? hmul2(y, y) : hfma2(y, y, Q[r][j & 1]);
      }
    }
  }
  if (STATS) {
#pragma unroll
    for (int r = 0; r < 2; r++) {
      st[2 * r] = (bf_lo(S[r][0]) + bf_hi(S[r][0])) + (bf_lo(S[r][1]) + bf_hi(S[r][1]));
      st[2 * r + 1] = (bf_lo(Q[r][0]) + bf_hi(Q[r][0])) + (bf_lo(Q[r][1]) + bf_hi(Q[r][1]));
    }
  }
}

__device__ __forceinline__ float2 quad_sum(const float* st, int t) {
  const bool o = t & 1;
  float s = (o ? st[2] : st[0]) + __shfl_xor_sync(0xffffffff, o ? st[0] : st[2], 1);
  float q = (o ? st[3] : st[1]) + __shfl_xor_sync(0xffffffff, o ? st[1] : st[3], 1);
  s += __shfl_xor_sync(0xffffffff, s, 2);
  q += __shfl_xor_sync(0xffffffff, q, 2);
  return make_float2(s, q);
}
template <int Q> __device__ __forceinline__ void conv_load(uint32_t* a, uint32_t ab) {
  a[0] = lds32<512 * Q>(ab);       a[1] = lds32<512 * Q + 256>(ab);  a[2] = lds32<512 * Q + 16>(ab);   a[3] = lds32<512 * Q + 272>(ab);
  a[4] = lds32<512 * Q + 32>(ab);  a[5] = lds32<512 * Q + 288>(ab);  a[6] = lds32<512 * Q + 48>(ab);   a[7] = lds32<512 * Q + 304>(ab);
  a[8] = lds32<512 * Q + 64>(ab);  a[9] = lds32<512 * Q + 320>(ab);  a[10] = lds32<512 * Q + 80>(ab);  a[11] = lds32<512 * Q + 336>(ab);
  a[12] = lds32<512 * Q + 96>(ab); a[13] = lds32<512 * Q + 352>(ab); a[14] = lds32<512 * Q + 112>(ab); a[15] = lds32<512 * Q + 368>(ab);
}
template <int Q, int L> __device__ __forceinline__ void conv_step(float* d, uint32_t (*a)[16], uint32_t ab, uint64_t db) {
  WG_FENCE();
#pragma unroll
  for (int s = 0; s < 4; s++) WG<128 - 16 * Q>::rs(d, a[Q] + 4 * s, db + s + 16 * Q);
  WG_COMMIT();
  WG_WAIT(1);
  if (L >= 0) conv_load<(L >= 0 ? L : 0)>(a[L >= 0 ? L : 0], ab);
  if (Q == 0) WG_WAIT(0);
}

__device__ __forceinline__ void final_load_x(uint32_t (*xw)[10], const __nv_bfloat16* x0, int t) {
#pragma unroll
  for (int r = 0; r < 2; r++) {
    const __nv_bfloat16* q = x0 + r * 8 * kD;
    const uint4 u = ldg4(q + t * 8), v = ldg4(q + 32 + t * 8);
    asm volatile("ld.global.v2.u32 {%0,%1}, [%2];" : "=r"(xw[r][8]), "=r"(xw[r][9]) : "l"(q + 64 + t * 4) : "memory");
    xw[r][0] = u.x; xw[r][1] = u.y; xw[r][2] = u.z; xw[r][3] = u.w;
    xw[r][4] = v.x; xw[r][5] = v.y; xw[r][6] = v.z; xw[r][7] = v.w;
  }
}
template <class F>
__device__ __forceinline__ void final_out(const float* d, const uint32_t (*xw)[10], const uint32_t* rn, const float* c, uint32_t yt, __nv_bfloat16* o0, int w, int lane, F wait_y) {
  const int r8 = lane & 7, mi = lane >> 3, t = lane & 3;
  const uint32_t ya = yt + ((mi >> 1) * 8 + r8) * 128 + (((2 * w + (mi & 1)) ^ r8) << 4);
#pragma unroll
  for (int qq = 0; qq < 3; qq++) {
    const int q = FO ? (qq + 2) % 3 : qq, n = q < 2 ? 8 : 4;
    uint32_t gt[8], y[8];
#pragma unroll
    for (int e = 0; e < n; e++) {
      const int i = q * 8 + e;
      const float h0 = FOLD ? d[2 * i] : d[2 * i] * c[i & 1], h1 = FOLD ? d[2 * i + 1] : d[2 * i + 1] * c[i & 1];
      const uint32_t h = pack2(h0, h1);
      gt[e] = hmul2(FV ? pack2(fmaf(h0, tanh_fast(h0), h0), fmaf(h1, tanh_fast(h1), h1)) : hfma2(h, htanh2(h), h), hfma2(xw[i & 1][i >> 1], rn[i & 1], rn[2 + (i & 1)]));
      if (qq == 0) asm volatile("" : "+r"(gt[e]));
    }
    if (qq == 0) wait_y();
    ldsm4t(y, ya + q * 4096);
    if (q < 2) ldsm4t(y + 4, ya + q * 4096 + 2048);
#pragma unroll
    for (int e = 0; e < n; e++) y[e] = hfma2(gt[e], y[e], xw[e & 1][q * 4 + (e >> 1)]);
#pragma unroll
    for (int r = 0; r < 2; r++) {
      __nv_bfloat16* o = o0 + r * 8 * kD;
      if (q < 2) stg4_if(o + q * 32 + t * 8, y[r], y[2 + r], y[4 + r], y[6 + r], true);
      else asm volatile("st.global.v2.u32 [%0], {%1,%2};" ::"l"(o + 64 + t * 4), "r"(y[r]), "r"(y[2 + r]) : "memory");
    }
  }
}

struct Taps { uint4 r0, r1; uint32_t n0, n1, dd; };
__device__ __forceinline__ void load_taps(Taps& k, const Params& p, int ch, int tid) {
  const uint4* kp = (const uint4*)(p.ssmk + (size_t)ch * kS);
  k.r0 = ldg4(kp + tid); k.r1 = ldg4(kp + 128 + tid);
  k.n0 = ldg1(kp + tid + 1); k.n1 = tid < 127 ? ldg1(kp + 129 + tid) : 0u;
  k.dd = __bfloat16_as_ushort(p.ssmD[ch]);
}
__device__ __forceinline__ void convx_copy(const Params& p, uint32_t cv, uint32_t bar, int ch) {
  bulk_g2s(cv, p.scr->kvx + (size_t)ch * 4096, 2048, bar);
  bulk_g2s(cv + XB_PL, p.scr->kvx + (size_t)ch * 4096 + 2048, 2048, bar);
}
__device__ __forceinline__ void convx_issue(const Params& p, uint32_t sb, int h, int ch) {
  if (elect_one()) { mbar_expect(sb + BAR_XL + 8 * h, 4096); convx_copy(p, sb + OFF_CV + (1 - h) * CV_SZ, sb + BAR_XL + 8 * h, ch); }
}
__device__ __forceinline__ void convx_finish(const Params& p, uint32_t sb, int h, int ch, int i, uint32_t par, int lane) {
  const uint32_t cv = sb + OFF_CV + (1 - h) * CV_SZ, rt = sb + BAR_XL - 16 + 8 * h;
  mbar_wait(sb + BAR_XL + 8 * h, i & 1);
  validate<4, XB_PL - 2048>(cv + lane * 32, par, rt, [&]() { convx_copy(p, cv, rt, ch); });
  if (elect_one()) mbar_arrive(sb + BAR_XF + 8 * h);
}
__device__ __forceinline__ void zero_pads(uint32_t cv, int lane) {
  if (lane < 8) sts128(cv + (lane >> 2) * XB_PL + 2048 + (lane & 3) * 16, 0, 0, 0, 0);
  else if (lane < 12) sts128(cv + ((lane & 2) ? CV_KO : CV_KE) + (lane & 1) * 16, 0, 0, 0, 0);
  fence_async_smem();
  __syncwarp();
}
__device__ __forceinline__ int y_row(int c) {
  const int cc = c % 80;
  return c - cc + (cc & 1) + (cc < 64 ? (cc & 32) + ((cc >> 1) & 3) * 8 + ((cc >> 3) & 3) * 2 : 64 + ((cc >> 1) & 1) * 8 + ((cc >> 2) & 3) * 2);
}
struct KvRegs { uint32_t k[11], v[8]; uint4 sh; };
__device__ __forceinline__ void kv_load(KvRegs& q, const __nv_bfloat16* kp, const __nv_bfloat16* vp, const __nv_bfloat16* sp, bool halo) {
  if (XP & 8) { for (int i = 0; i < 11; i++) q.k[i] = (uint32_t)(size_t)kp + i; for (int i = 0; i < 8; i++) q.v[i] = i; q.sh = make_uint4(1, 2, 3, 4); return; }
#pragma unroll
  for (int i = 0; i < 11; i++) q.k[i] = (i >= 3 || halo) ? ldg1(kp + i * kD) : 0u;
#pragma unroll
  for (int i = 0; i < 8; i++) q.v[i] = ldg1(vp + i * kD);
  q.sh = ldg4(sp);
}
__device__ __forceinline__ void kv_calc(const KvRegs& q, uint32_t* o) {
  const uint32_t w0 = prmt(q.sh.x, q.sh.z, 0x5410), w1 = prmt(q.sh.x, q.sh.z, 0x7632), w2 = prmt(q.sh.y, q.sh.w, 0x5410), w3 = prmt(q.sh.y, q.sh.w, 0x7632);
  uint32_t r[8];
#pragma unroll
  for (int i = 0; i < 8; i++) r[i] = hmul2(hfma2(q.k[i + 3], w0, hfma2(q.k[i + 2], w1, hfma2(q.k[i + 1], w2, hmul2(q.k[i], w3)))), q.v[i]);
#pragma unroll
  for (int i = 0; i < 4; i++) { o[i] = prmt(r[7 - 2 * i], r[6 - 2 * i], 0x5410); o[4 + i] = prmt(r[7 - 2 * i], r[6 - 2 * i], 0x7632); }
}
__device__ __forceinline__ void kv_put(const uint32_t* o, uint32_t oa, uint32_t tm, uint32_t tb) {
  sts128(oa, (o[0] & tm) | tb, o[1], o[2], o[3]);
  sts128(oa + 2048, (o[4] & tm) | tb, o[5], o[6], o[7]);
}

__device__ __forceinline__ void kv_store(const Params& p, uint32_t src, int tb, int unit) {
  asm volatile("cp.async.bulk.tensor.3d.global.shared::cta.bulk_group [%0, {%2, %3, %4}], [%1];" ::"l"(&p.tmKV), "r"(src), "r"((63 - tb) * 16), "r"(unit * 32), "r"(0) : "memory");
}
__device__ __forceinline__ uint32_t kv_stage_addr(int w, int lane) { return ((3 - w) & 1) * 1024 + lane * 32 + ((((3 - w) >> 1) ^ (lane >> 2)) & 1) * 16; }

template <class F>
__device__ __forceinline__ void conv_service(const Params& p, uint32_t sb, int h, int ch, uint32_t par, int lane, F mid) {
#pragma unroll 1
  for (int i = 0; i < 2 + h; i++, ch += 128) {
    bar_sync(NB_SV + h, 160);
    if (i < h) convx_issue(p, sb, h, ch + 128);
    uint8_t* dst = p.scr->y + (size_t)y_row(ch) * 4096;
    bar_sync(ARV ? NB_SV2(h) : NB_SV + h, 160);
    if (elect_one()) {
      bulk_s2g(dst, sb + OFF_A + 9 * A_SLOT + h * 4096, 4096);
      bulk_commit_wait();
    }
    __syncwarp();
    if (i > h) break;
    if (i == h) { mid(); mbar_wait(sb + BAR_KV2, 0); convx_issue(p, sb, h, ch + 128); }
    convx_finish(p, sb, h, ch + 128, i + 1, par, lane);
  }
}
__device__ __forceinline__ void conv_worker(const Params& p, Taps& k, uint32_t sb, int h, int ch0, int w, int lane, int tid, int rb, int cb TSP) {
  const uint32_t cv = sb + OFF_CV + (1 - h) * CV_SZ, yb0 = sb + OFF_A + 9 * A_SLOT + h * 4096, xbar = sb + BAR_XF + 8 * h;
  const int n = 2 + h, nbar = NB_WG + h;
  const int g = lane >> 2, t = lane & 3, w0 = w & 1, w1 = w >> 1;
  const uint32_t ab = cv + ((g & 1) ? CV_KE : CV_KO) + 32 + 2 * (64 * w0 + 8 * w1 + ((g - 15) & ~1) + 2 * t);
  const uint32_t scA = cv + (w1 ? CV_KO : CV_KE) + 32, scB = scA + 2048;
  const int dl = (t >> 1) ^ 1, col = lane & 7, mi = lane >> 3;
  if (h == 0) mbar_wait(xbar, 0);
  TR(26);
#pragma unroll 1
  for (int i = 0; i < n; i++) {
    if (tid == 0) {
      k.r0.x = (k.r0.x & 0xffff0000u) | (pack2(bf_lo(k.r0.x) + bf_lo(k.dd), 0.f) & 0xffffu);
      sts32(cv + CV_KO + 28, k.r0.x << 16);
    }
    sts128(cv + CV_KE + 32 + tid * 16, k.r0.x, k.r0.y, k.r0.z, k.r0.w);
    sts128(cv + CV_KO + 32 + tid * 16, prmt(k.r0.x, k.r0.y, 0x5432), prmt(k.r0.y, k.r0.z, 0x5432), prmt(k.r0.z, k.r0.w, 0x5432), prmt(k.r0.w, k.n0, 0x5432));
    sts128(cv + CV_KE + 2080 + tid * 16, k.r1.x, k.r1.y, k.r1.z, k.r1.w);
    sts128(cv + CV_KO + 2080 + tid * 16, prmt(k.r1.x, k.r1.y, 0x5432), prmt(k.r1.y, k.r1.z, 0x5432), prmt(k.r1.z, k.r1.w, 0x5432), prmt(k.r1.w, k.n1, 0x5432));
    TR(30 + i * 10);
    if (i + 1 < n) load_taps(k, p, ch0 + (i + 1) * 128, tid);
    bar_sync(nbar, 128);
    TR(31 + i * 10);
    const uint64_t db = mkdesc(cv + (i & 0x1000), XB_PL, 128, 0);
    float d[64];
    uint32_t a[8][16];
    conv_load<7>(a[7], ab);
    conv_load<6>(a[6], ab);
    conv_load<5>(a[5], ab);
    conv_load<4>(a[4], ab);
#pragma unroll
    for (int j = 0; j < 64; j++) d[j] = 0.f;
    if (i == 0) STAMPW(h ? 43 : 8);
    TR(32 + i * 10);
    const uint32_t hold = sb + (i + 1 == n ? (HOLD == 32 || (STG && STG != h + 1) ? BAR_HR : BAR_HOLD) : (HK1 == 0 || i ? BAR_XS : (HK1 == 1 ? BAR_ZG : (HK1 == 2 ? BAR_ZP : (HK1 == 3 ? BAR_YT : BAR_AE + 8 * (HK1 - 4))))));
    if (HVY) {
      mbar_wait(xbar, i & 1);
      conv_step<7, -1>(d, a, ab, db); conv_step<6, 3>(d, a, ab, db); conv_step<5, 2>(d, a, ab, db); conv_step<4, 1>(d, a, ab, db);
      WG_WAIT(0);
      conv_load<0>(a[0], ab);
      TR(39 + i * 10);
      mbar_wait(hold, 0);
    } else {
      mbar_wait2(xbar, i & 1, hold, 0);
    }
    if (i == 0) STAMPW(h ? 51 : 7);
    TR(33 + i * 10);
    if (!((XP & 32) && i == 1 && h == 1) && !((XP & 128) && i + 1 == n) && !((XP & 256) && i == 0)) {
    if (HVY) {
      conv_step<3, -1>(d, a, ab, db); conv_step<2, -1>(d, a, ab, db); conv_step<1, -1>(d, a, ab, db); conv_step<0, -1>(d, a, ab, db);
    } else {
    conv_step<7, -1>(d, a, ab, db); conv_step<6, -1>(d, a, ab, db); conv_step<5, -1>(d, a, ab, db); conv_step<4, 3>(d, a, ab, db);
    conv_step<3, 2>(d, a, ab, db); conv_step<2, 1>(d, a, ab, db); conv_step<1, 0>(d, a, ab, db); conv_step<0, -1>(d, a, ab, db);
    }
    }
    acc_fence<64>(d);
    TR(34 + i * 10);
    if (HE && i == 0) mbar_wait(sb + BAR_ZG, 1);
    if (ARV) bar_arrive(NB_SV + h, 160); else bar_sync(NB_SV + h, 160);
    if (ARV && i == 0) mbar_wait(sb + BAR_YT, 0);
    const uint32_t par = lds32<0>(sb + OFF_TAG);
    TR(35 + i * 10);
    float E[16][2];
#pragma unroll
    for (int j = 0; j < 15; j++) { E[j][0] = d[4 * j] + d[4 * j + 6]; E[j][1] = d[4 * j + 1] + d[4 * j + 7]; }
    E[15][0] = d[60]; E[15][1] = d[61];
    if (w0 == 0) {
#pragma unroll
      for (int j = 8; j < 16; j++) sts64f(scA + (j - 8) * 256 + lane * 8, E[j][0], E[j][1]);
    } else {
      const uint32_t a = scB - dl * 256 + (lane ^ 2) * 8;
#pragma unroll
      for (int j = 1; j < 8; j++) sts64f(a + j * 256, E[j][0], E[j][1]);
      sts64f(scB + (dl ? 7 * 256 : 0) + (lane ^ 2) * 8, dl ? E[8][0] : E[0][0], dl ? E[8][1] : E[0][1]);
    }
    TR(36 + i * 10);
    bar_sync(nbar, 128);
    uint32_t pk[8];
    const bool tg = YTAG && w1 == 0 && g == 0;
    const uint32_t tm = tg ? ~0x10001u : ~0u, tb = tg && (par & 1) ? 0x10001u : 0;
    if (w0 == 0) {
#pragma unroll
      for (int j = 0; j < 8; j++) { const float2 v = lds64f(scB + j * 256 + lane * 8); pk[j] = (pack2(E[j][0] + v.x, E[j][1] + v.y) & tm) | tb; }
      const uint32_t ya = yb0 + 32 * (127 - (8 * mi + col)) + 16 * w1;
      stsm4t(ya, pk[0], pk[1], pk[2], pk[3]);
      stsm4t(ya - 1024, pk[4], pk[5], pk[6], pk[7]);
    } else {
      const uint32_t a0 = scA - dl * 256 + (lane ^ 2) * 8;
#pragma unroll
      for (int j = 9; j < 16; j++) { const float2 v = lds64f(a0 + (j - 8) * 256); pk[j - 8] = (pack2(E[j][0] + v.x, E[j][1] + v.y) & tm) | tb; }
      const float2 v = lds64f(scA + (dl ? 7 * 256 : 0) + (lane ^ 2) * 8);
      pk[0] = (pack2((dl ? 0.f : E[8][0]) + v.x, (dl ? 0.f : E[8][1]) + v.y) & tm) | tb;
      const uint32_t yb = yb0 + 32 * (127 - (92 + 8 * mi + col)) + 16 * w1;
      const uint32_t ya = (mi == 0 && col < 4) ? yb0 + 32 * (3 - col) + 16 * w1 : yb + 1024;
      stsm4t(ya, pk[0], pk[1], pk[2], pk[3]);
      stsm4t(yb, pk[4], pk[5], pk[6], pk[7]);
    }
    TR(37 + i * 10);
    fence_async_smem();
    if (ARV) { bar_arrive(NB_SV2(h), 160); if (i + 1 < n) bar_sync(nbar, 128); }
    else bar_sync(NB_SV + h, 160);
    TR(38 + i * 10);
    STAMPW((h ? 40 : 5) + i);
    if (i == 0 && h == 0) {
      const int tn = tid_now();
      {
        const int ln = tn & 31, t0 = (rb * 2 + (cb & 1)) * 32 + w * 8, c0 = (cb >> 1) * 320 + 192 + ln * 2;
        KvRegs q0, q1;
        uint32_t o[8];
        kv_load(q0, p.k + (size_t)(t0 - 3) * kD + c0, p.v + (size_t)t0 * kD + c0, p.shift + c0 * 4, t0 > 0);
        kv_load(q1, p.k + (size_t)(t0 - 3) * kD + c0 + 64, p.v + (size_t)t0 * kD + c0 + 64, p.shift + c0 * 4 + 256, t0 > 0);
        const uint32_t oa = sb + OFF_A + 8 * A_SLOT + kv_stage_addr(w, ln), km = w >= 2 ? ~1u : ~0u, kb = w >= 2 ? lds32<0>(sb + OFF_TAG) & 1 : 0;
        kv_calc(q0, o);
        kv_put(o, oa, km, kb);
        kv_calc(q1, o);
        kv_put(o, oa + 4096, km, kb);
        fence_async_smem();
        bar_arrive(NB_KL, 160);
      }
      STAMPW(56);
      const int u = (tn >> 3) % 5, kg = rb * 3 + (tn < 120 ? (tn >> 3) / 5 : 0), c = u < 4 ? (u >> 1) * 10 + (u & 1) * 4 : 8, o2 = u < 4 ? 2 : 10;
      const uint4* wp = (const uint4*)(p.wout + (size_t)(kg * 8 + (tn & 7)) * kD + cb * 160) + c;
      const uint4 w0 = ldg4(wp), w1 = ldg4(wp + 1), w2 = ldg4(wp + o2), w3 = ldg4(wp + o2 + 1);
      uint8_t* dst = p.scr->wo + (size_t)cb * (12 * W_SLOT) + kg * 2560 + c * 128 + (tn & 7) * 16;
      const bool f = u < 4, on = tn < 120;
      stg4_if(dst, w0.x, f ? w1.x : w0.z, f ? w2.x : w1.x, f ? w3.x : w1.z, on);
      stg4_if(dst + 128, w0.y, f ? w1.y : w0.w, f ? w2.y : w1.y, f ? w3.y : w1.w, on);
      stg4_if(dst + o2 * 128, f ? w0.z : w2.x, f ? w1.z : w2.z, f ? w2.z : w3.x, w3.z, on);
      stg4_if(dst + o2 * 128 + 128, f ? w0.w : w2.y, f ? w1.w : w2.w, f ? w2.w : w3.y, w3.w, on);
      bar_arrive(NB_WO, 160);
    }
  }
}

struct U6 { uint64_t a, b, c; };
__device__ __forceinline__ uint64_t ld_ll2(const void* p) { uint64_t a; asm volatile("ld.relaxed.gpu.global.u64 %0, [%1];" : "=l"(a) : "l"(p) : "memory"); return a; }
__device__ __forceinline__ void gather_colsum(const Params& p, uint32_t sb, int part, int cb, uint32_t tag8, int lane) {
  const uint32_t* src = p.scr->colsum + (uint32_t)((part ? 0 : 768) + cb * 192 + lane * 2);
  const uint64_t t2 = tag8 * 0x100000001ull;
  const U6 v = poll3<false, PP, U6>([&]() { return U6{ld_ll2(src), ld_ll2(src + 64), ld_ll2(src + 128)}; },
                                    [&](const U6& u) { return (((u.a ^ t2) | (u.b ^ t2) | (u.c ^ t2)) & 0xff000000ffull) == 0; });
  const uint32_t dst = sb + OFF_CS + (part ? 0 : 768) + lane * 8;
  asm volatile("st.shared.u64 [%0], %1;\nst.shared.u64 [%0+256], %2;\nst.shared.u64 [%0+512], %3;" ::"r"(dst), "l"(v.a), "l"(v.b), "l"(v.c) : "memory");
  __syncwarp();
  mbar_arrive_if(sb + BAR_ST + 8 * part, lane == 0);
}

__device__ __forceinline__ void helper_cta(const Params& p, uint32_t sb, int cb, int warp, int lane TSP) {
  constexpr int NS = 9, ONES = NS * B_SLOT, BF = ONES + 256, BE = BF + 8 * NS;
  if (warp < NS && elect_one()) {
    mbar_init(sb + BF + 8 * warp, 1); mbar_init(sb + BE + 8 * warp, 1);
    fence_async_smem();
    if (warp == 0) { mbar_expect(sb + BF, B_SLOT); tma3d(sb, &p.tmW, 0, 0, 12 + cb * 3, sb + BF); }
  }
  if (warp == 15) { sts32(sb + ONES + lane * 4, 0x3f803f80u); sts32(sb + ONES + 128 + lane * 4, 0x3f803f80u); fence_async_smem(); }
  __syncthreads();
  if (warp == 4) {
    int s = 1, ph = 1;
    uint32_t tp = clock() + HP0;
#pragma unroll 1
    for (int it = 1; it < 20; it++) {
      if (HPD && it >= 10) pace(tp, HPD);
      mbar_wait(sb + BE + 8 * s, ph);
      if (elect_one()) { mbar_expect(sb + BF + 8 * s, B_SLOT); tma3d(sb + s * B_SLOT, &p.tmW, 0, (it < 10 ? it : it - 10) * 64, (it < 10 ? 12 : 0) + cb * 3, sb + BF + 8 * s); }
      if (++s == NS) { s = 0; ph ^= 1; }
    }
  } else if (warp < 4) {
    const uint32_t tag = load_epoch(p, 128 + cb, lane) + 1;
    const uint64_t db = mkdesc(sb + ONES, 128, 128, 0);
    uint32_t* dst = p.scr->colsum + cb * 192 + warp * 16 + (lane >> 2);
    if ((lane & 3) == 0) {
#pragma unroll 1
      for (int j = 0; j < 12; j++) st_relaxed(dst + (j < 6 ? 768 : 0) + ((j % 6) >> 1) * 64 + (j & 1) * 8, 0);
    }
    int s = 0, ph = 0;
#pragma unroll 1
    for (int part = 0; part < 2; part++) {
      float d[12];
#pragma unroll
      for (int i = 0; i < 12; i++) d[i] = 0.f;
#pragma unroll 1
      for (int it = 0; it < 10; it++) {
        mbar_wait(sb + BF + 8 * s, ph);
        const uint64_t da = mkdesc(sb + s * B_SLOT, 8192, 1024, 1);
        WG_FENCE();
#pragma unroll
        for (int j = 0; j < 12; j++) wgmma_colsum(d + 4 * (j % 3), da + (j % 3) * 512 + (j / 3) * 128, db);
        WG_COMMIT();
        WG_WAIT(1);
        mbar_arrive_if(sb + BE + 8 * (s == 0 ? NS - 1 : s - 1), threadIdx.x == 0 && (it | part) != 0);
        if (++s == NS) { s = 0; ph ^= 1; }
      }
      WG_WAIT(0);
      acc_fence<12>(d);
      if ((lane & 3) == 0) {
#pragma unroll
        for (int j = 0; j < 6; j++) st_relaxed(dst + (part ? 0 : 768) + (j >> 1) * 64 + (j & 1) * 8, tagged(d[2 * j], tag8(tag)));
      }
      STAMPW(1 + part);
    }
    if (threadIdx.x == 0) *(volatile uint32_t*)&p.scr->epoch[128 + cb] = tag;
  }
}

__global__ void __launch_bounds__(512, 1) fused_kernel(const __grid_constant__ Params p) {
  extern __shared__ __align__(1024) uint8_t smem[];
  const int warp = __shfl_sync(0xffffffff, (int)(threadIdx.x >> 5), 0);
  const int lane = threadIdx.x & 31;
  const uint32_t sb = __shfl_sync(0xffffffff, (uint32_t)__cvta_generic_to_shared(smem), 0);
  const uint32_t tstart = clock();
  int b = blockIdx.x;
  if (p.by_smid) asm volatile("mov.u32 %0, %%smid;" : "=r"(b));
  b = __shfl_sync(0xffffffff, b, 0);
  const int job = p.job[b], lin = job & 255, cb = job >> 8 & 3, rb = job >> 10;
  if (elect_one()) {
    mbar_init(sb + OFF_BAR + 8 * warp, 1);
    if (lin < 128) {
      if (warp < NPRE) { fence_async_smem(); mbar_expect(sb + BAR_AF + 8 * warp, A_SLOT); tma2d(sb + OFF_A + warp * A_SLOT, &p.tmX, warp * 64, rb * 64, sb + BAR_AF + 8 * warp); }
      if (warp >= 10 && warp < 10 + NPRE) { fence_async_smem(); mbar_expect(sb + OFF_BAR + 8 * warp, B_SLOT); tma3d(sb + OFF_B + (warp - 10) * B_SLOT, &p.tmW, 0, (warp - 10) * 64, 12 + cb * 3, sb + OFF_BAR + 8 * warp); }
    }
    if (warp >= 2 && warp < 5) asm volatile("prefetch.tensormap [%0];" ::"l"(&p.tmX + warp) : "memory");
    mbar_init(sb + OFF_BAR + 128 + 8 * warp, 1);
    if (warp != 3) mbar_init(sb + OFF_BAR + 256 + 8 * warp, (0x2224444444441111ull >> (4 * warp)) & 15);
    mbar_init(sb + OFF_BAR + 384 + 8 * warp, 2);
    if (warp < 2) mbar_init(sb + BAR_XL + 8 * warp, 1);
    asm volatile("fence.mbarrier_init.release.cluster;" ::: "memory");
  }
  if (lin >= 128) { helper_cta(p, sb, cb, warp, lane TSA); return; }
  const int rot = ROT ? (MAP ? rb & 24 : rb & 28) : 0;
  const int chb = (cb >> 1) * 320 + rb * 2 + (cb & 1);
  if (sb & 1023) die();
  __syncthreads();

  if (warp >= 12) {
    asm volatile("setmaxnreg.dec.sync.aligned.u32 32;");
    const uint8_t* z2s = p.scr->z2 + (size_t)cb * 32 * B_SLOT;
    const char* wq = (const char*)p.wsp + (rb * 64 + cb * 16 + (lane >> 1)) * (kS * 2) + (lane & 1) * 128;
    if (warp == 12) {
      int s = NPRE, ph = 1, nx = NPRE;
#pragma unroll 1
      for (int it = NPRE; it < 20; it++) {
        if (it >= 5) mbar_wait<true>(sb + BAR_BE + 8 * s, ph);
        const int xt = XL ? min(10, it + XL) : min(10, it + 1);
#pragma unroll 1
        for (; nx < xt; nx++)
          if (elect_one()) { mbar_expect(sb + BAR_AF + 8 * nx, A_SLOT); tma2d(sb + OFF_A + nx * A_SLOT, &p.tmX, nx * 64, rb * 64, sb + BAR_AF + 8 * nx); }
        if (elect_one()) {
          mbar_expect(sb + BAR_BF + 8 * s, B_SLOT);
          tma3d(sb + OFF_B + s * B_SLOT, &p.tmW, 0, (it < 10 ? it : it - 10) * 64, (it < 10 ? 12 : 0) + cb * 3, sb + BAR_BF + 8 * s);
        }
        if (XR && it == XR && elect_one()) { mbar_expect(sb + BAR_WO, 16 * kD * 2); bulk_g2s(sb + OFF_CV, p.x + (rb * 64 + cb * 16) * kD, 16 * kD * 2, sb + BAR_WO); }
        if (XL && it == 4) bar_arrive(NB_KF, 160);
        if (XL == 0 && it == 4) {
#pragma unroll 1
          for (; nx < 10; nx++)
            if (elect_one()) { mbar_expect(sb + BAR_AF + 8 * nx, A_SLOT); tma2d(sb + OFF_A + nx * A_SLOT, &p.tmX, nx * 64, rb * 64, sb + BAR_AF + 8 * nx); }
          bar_arrive(NB_KF, 160);
        }
        STAMP2(32 + it);
        if (++s == 5) { s = 0; ph ^= 1; }
      }
      const uint32_t ztarget = (load_epoch(p, lin, lane) + 1) * 128;
#pragma unroll 1
      for (int i = 0; i < LEAD; i++) {
        mbar_wait<true>(sb + BAR_AE + 8 * (3 + i), 0);
        if (elect_one()) { mbar_expect(sb + BAR_AF + 8 * (3 + i), A_SLOT); tma2d(sb + OFF_A + (3 + i) * A_SLOT, &p.tmWsp, ((i + rot) & 31) * 64, rb * 64, sb + BAR_AF + 8 * (3 + i)); }
      }
      mbar_wait<true>(sb + BAR_ZP, 0);
      if (ZPD) { uint32_t tp = clock(); pace(tp, ZPD); }
      if (GO_D) wait_timed(p.scr->cnt, ztarget); else
      poll_counter<true>(p.scr->cnt + CNT_Z, ztarget);
      STAMP(24);
      uint32_t tg = clock() + 4 * GP - GO;
#pragma unroll 1
      for (int it = 0; it < 32; it++) {
        mbar_wait<true>(sb + BAR_BE + 8 * s, ph);
        if (GP && it >= 5) pace<false>(tg, GP);
        if (elect_one()) {
          mbar_expect(sb + BAR_BF + 8 * s, B_SLOT);
          bulk_g2s(sb + OFF_B + s * B_SLOT, z2s + ((it + rot) & 31) * B_SLOT, B_SLOT, sb + BAR_BF + 8 * s);
        }
        if (it == 0) STAMP(22);
        if (HE && it == HE - 1 && elect_one()) mbar_arrive(sb + BAR_ZG);
        const int ia = it + LEAD - 1, sa = (ia + 3) & 7;
        if (it >= 1 && ia < 32) {
          mbar_wait<true>(sb + BAR_AE + 8 * sa, (ia >> 3) & 1);
          if (elect_one()) { mbar_expect(sb + BAR_AF + 8 * sa, A_SLOT); tma2d(sb + OFF_A + sa * A_SLOT, &p.tmWsp, ((ia + rot) & 31) * 64, rb * 64, sb + BAR_AF + 8 * sa); }
        }
        if (HOLD < 27) mbar_arrive_if(sb + BAR_HOLD, it == HOLD + 5 && lane == 0);
        STAMP2(52 + it);
        if (++s == 5) { s = 0; ph ^= 1; }
      }
      mbar_wait<true>(sb + BAR_WO, XR > 0);
      acquire_fence();
      s = 0;
#pragma unroll 1
      for (int it = 0; it < 12; it++) {
        if (it < 6) mbar_wait<true>(sb + BAR_BE + 8 * ((0x110443 >> (4 * it)) & 7), it < 3 ? 1 : 0);
        else mbar_wait<true>(sb + BAR_WE + 8 * s, 0);
        if (HOLD >= 27 && HOLD < 32) mbar_arrive_if(sb + BAR_HOLD, it == (HOLD <= 28 ? 0 : (HOLD == 29 ? 1 : HOLD - 27)) && lane == 0);
        if (elect_one()) {
          mbar_expect(sb + BAR_WF + 8 * s, W_SLOT);
          bulk_g2s(sb + OFF_B + (s >= 3 ? s - 3 : s + 3) * W_SLOT, p.scr->wo + (size_t)(cb * 12 + g3_block(cb, it)) * W_SLOT, W_SLOT, sb + BAR_WF + 8 * s);
        }
        STAMP2(84 + it);
        if (++s == 6) s = 0;
      }
      mbar_wait<true>(sb + BAR_WE, 1);
    } else if (warp == 13) {
      const uint32_t tag = load_epoch(p, lin, lane) + 1;
      if (elect_one()) reset_sector(&p.scr->hflag[rb * 32 + cb * 8]);
      if (lane == 0) sts32(sb + OFF_TAG, tag8(tag));
      mbar_wait(sb + BAR_AF + 8 * CSI, 0);
      if (CSD) { uint32_t tp = clock(); pace(tp, CSD); }
      gather_colsum(p, sb, 0, cb, tag8(tag), lane);
      STAMP(27);
      bar_sync(NB_Z, 160);
      if (elect_one()) {
        mbar_arrive(sb + BAR_ZG);
        bulk_s2g((void*)(z2s + rb * B_SLOT), sb + OFF_A, B_SLOT);
        bulk_commit_wait();
        mbar_arrive(sb + BAR_ZP);
        STAMPE(58);
        if (GO_D) { if (!(XP & 16)) asm volatile("fence.acq_rel.gpu;" ::: "memory"); arrive_timed(p.scr->cnt); }
        else if (XP & 16) red_relaxed(p.scr->cnt + CNT_Z); else red_release(p.scr->cnt + CNT_Z);
      }
      __syncwarp();
      STAMP(28);
      {
        uint32_t tp = clock() + PF_W;
#pragma unroll 1
        for (int i = PF_N; i < 16; i++) {
          pace(tp, PF_D);
          prefetch_l2(wq + ((i + (rot >> 1)) & 15) * 256);
          if (i == LKI) bar_sync(NB_KL, 160);
          if ((i == LKI || i == LKI + 1) && elect_one()) {
            kv_store(p, sb + OFF_A + 8 * A_SLOT + (i - LKI) * 4096, rb * 2 + (cb & 1), (cb >> 1) * 5 + 3 + i - LKI);
            bulk_commit_wait();
            if (i > LKI) red_relaxed(p.scr->cnt + CNT_KV + 2 + (cb >> 1));
          }
          __syncwarp();
          if (i == LKI + 1) STAMP(59);
        }
      }
      if (!EARLY) poll_counter(p.scr->cnt + CNT_KV + 2 + (cb >> 1), tag * 64);
      if (elect_one()) mbar_arrive(sb + BAR_KV2);
      STAMP(34);
      const uint8_t* hs = p.scr->h + (size_t)rb * 12 * A_SLOT;
#pragma unroll 1
      for (int i = 0; i < 3; i++) {
        mbar_wait(sb + BAR_HR - 16 + 8 * i, 0);
        if (elect_one()) bulk_s2g((void*)(hs + (cb * 3 + i) * A_SLOT), sb + OFF_A + i * A_SLOT, A_SLOT);
      }
      if (elect_one()) {
        if (HA == 0) st_relaxed(&p.scr->hflag[rb * 32 + cb * 8], tag);
        bulk_commit_wait();
        if (HA == 1) st_relaxed(&p.scr->hflag[rb * 32 + cb * 8], tag);
        mbar_arrive(sb + BAR_ZP);
      }
      __syncwarp();
      STAMP(20);
      if (!EARLY && !HNF) poll_flags4(p.scr->hflag + rb * 32, tag, lane);
      if (HD) { uint32_t tp = clock(); pace<false>(tp, HD); }
      STAMP(37);
#pragma unroll 1
      for (int it = 3; it < 12; it++) {
        const int s = it < 9 ? it : it - 9;
        if (it == 9) { if (BPART) bar_sync(NB_PC, 288); else mbar_wait(sb + BAR_WE + 16, 0); }
        if (elect_one()) { mbar_expect(sb + BAR_AF + 8 * s, A_SLOT); bulk_g2s(sb + OFF_A + s * A_SLOT, hs + g3_block(cb, it) * A_SLOT, A_SLOT, sb + BAR_AF + 8 * s); }
      }
      STAMP(21);
    } else if (warp == 14) {
      const uint32_t tag = load_epoch(p, lin, lane) + 1;
      const int tb = rb * 2 + (cb & 1), u0 = (cb >> 1) * 5;
      const uint32_t ks = sb + OFF_CV + CV_SZ, par = __shfl_sync(0xffffffff, tag, 0);
      {
        uint32_t tp = tstart;
        pace(tp, TP_T);
        const char* q = (const char*)p.ssmk + chb * 4096 + lane * 128;
        prefetch_l2(q); prefetch_l2(q + 64 * 4096);
      }
      if (ST_YIELD) mbar_wait2(sb + BAR_XS, 0, sb + BAR_ST, 0);
      bar_sync(NB_KU, 160);
      if (elect_one()) { kv_store(p, ks, tb, u0); kv_store(p, ks + 4096, tb, u0 + 1); bulk_commit_wait(); red_relaxed(p.scr->cnt + CNT_KV + (cb >> 1)); }
      __syncwarp();
      STAMP(35);
      bar_sync(NB_KU2, 160);
      if (elect_one()) { kv_store(p, ks + 8192, tb, u0 + 2); bulk_commit_wait(); }
      __syncwarp();
      zero_pads(ks, lane);
      bar_arrive(NB_G1D, 64);
      STAMP(30);
      {
        uint32_t tp = clock();
        const size_t o = (size_t)(tb * 32 + lane) * (kD * 2) + (u0 + 3) * 128;
        const char* r = (const char*)p.wout + (rb * 24 + min(lane, 23)) * (kD * 2) + cb * 320;
        const char* q = (const char*)p.ssmk + (chb + 128) * 4096 + lane * 128;
#pragma unroll 1
        for (int i = 0; i < 10; i++) {
          pace(tp, PF2_D);
          if (i == PF2_Z) mbar_wait(sb + BAR_BF + 32, 0), mbar_wait(sb + BAR_ZP, 0), tp = clock() + PF2_W;
          prefetch_l2(i < 3 ? q + i * 64 * 4096 : (i < 7 ? (const char*)((i & 1) ? p.k : p.v) + o + ((i - 3) >> 1) * 128 : r + (i - 7) * 128));
        }
      }
      mbar_wait(sb + BAR_YT, 0);
      conv_service(p, sb, 0, chb + 64, par, lane, NoHook());
      bar_sync(NB_CD, 64);
      if (elect_one()) { if (YTAG == 1) red_relaxed(p.scr->cnt + CNT_Y + (cb >> 1)); else if (!YTAG) red_release(p.scr->cnt + CNT_Y + (cb >> 1)); }
      STAMP(47);
      if (YTAG < 2) poll_counter(p.scr->cnt + CNT_Y + (cb >> 1), tag * 64);
      else if (!EARLY) mbar_wait(sb + BAR_WE + 40, 0);
      if (YD) { uint32_t tp = clock(); pace<false>(tp, YD); }
      if (elect_one()) {
        mbar_expect(sb + BAR_YT, 20480);
#pragma unroll 1
        for (int i = 0; i < 4; i++) tma2d(sb + OFF_CV + i * 5120, &p.tmY, rb * 64, cb * 160 + i * 40, sb + BAR_YT);
      }
      if (lane == 0) *(volatile uint32_t*)&p.scr->epoch[lin] = tag;
      STAMP(23);
    } else {
      const uint32_t tag = load_epoch(p, lin, lane) + 1;
      mbar_wait(sb + (XR ? BAR_WO : BAR_AF + 72), 0);
      if (XSD) { uint32_t tp = clock(); pace(tp, XSD); }
      {
        const uint32_t t8 = tag8(tag);
        const uint4 u = poll3<false, PP, uint4>([&]() { return ld_ll4(&p.scr->xstat[rb * 64 + lane * 2]); },
                                                [&](const uint4& v) { return (((v.x ^ t8) | (v.y ^ t8) | (v.z ^ t8) | (v.w ^ t8)) & 255u) == 0; });
        sts128(sb + OFF_XS + lane * 16, u.x, u.y, u.z, u.w);
      }
      __syncwarp();
      if (lane == 0) mbar_arrive(sb + BAR_XS);
      STAMP(25);
      const uint32_t par = __shfl_sync(0xffffffff, tag, 0);
      bar_sync(NB_G1D, 64);
      if (!EARLY) poll_counter(p.scr->cnt + CNT_KV + (cb >> 1), tag * 64);
      convx_issue(p, sb, 1, chb);
      convx_issue(p, sb, 0, chb + 64);
#pragma unroll 1
      for (int h = 1; h >= 0; h--) convx_finish(p, sb, h, chb + 64 - 64 * h, 0, par, lane);
      STAMP(48);
      gather_colsum(p, sb, 1, cb, tag8(tag), lane);
      STAMP(38);
      mbar_wait(sb + BAR_YT, 0);
      conv_service(p, sb, 1, chb, par, lane, [&]() {
        bar_sync(NB_WO, 160);
        if (elect_one()) red_release(p.scr->cnt + CNT_WO + cb);
        STAMP(49);
        poll_counter(p.scr->cnt + CNT_WO + cb, tag * 32);
        if (elect_one()) mbar_arrive(sb + BAR_WO);
        STAMP(46);
      });
      bar_arrive(NB_CD, 64);
    }
  } else if (warp >= 8) {
    const int w = warp & 3;
    {
      const int tid = tid_now();
      uint2* xs = &p.scr->xstat[rb * 64 + cb * 16 + (tid >> 3)];
      if ((tid & 7) == 0) st_ll2(xs, 0, 0);
      const uint32_t epoch = load_epoch(p, lin, lane);
      float sa[4] = {0.f, 0.f, 0.f, 0.f}, qa[4] = {0.f, 0.f, 0.f, 0.f};
      if (XR) mbar_wait(sb + BAR_WO, 0);
      constexpr int kUnroll = XR ? 5 : 1;
#pragma unroll kUnroll
      for (int i = 0; i < 10; i++) {
        if (!XR) mbar_wait(sb + BAR_AF + 8 * i, 0);
        const uint4 x4 = lds128(XR ? sb + OFF_CV + (tid >> 3) * (kD * 2) + (tid & 7) * 16 + i * 128 : sb + OFF_A + i * A_SLOT + cb * 2048 + tid * 16);
        const uint32_t u[4] = {x4.x, x4.y, x4.z, x4.w};
#pragma unroll
        for (int e = 0; e < 4; e++) { const float a = bf_lo(u[e]), c = bf_hi(u[e]); sa[e] += a + c; qa[e] = fmaf(a, a, fmaf(c, c, qa[e])); }
      }
      float s = (sa[0] + sa[1]) + (sa[2] + sa[3]), q = (qa[0] + qa[1]) + (qa[2] + qa[3]);
#pragma unroll
      for (int o = 1; o <= 4; o <<= 1) { s += __shfl_xor_sync(0xffffffff, s, o); q += __shfl_xor_sync(0xffffffff, q, o); }
      const float m = s * (1.f / kD);
      const float r = rsqrtf(fmaxf(fmaf(-m, m, q * (1.f / kD)), 0.f) + 1e-5f);
      if ((tid & 7) == 0) st_ll2(xs, tagged(m, tag8(epoch + 1)), tagged(r, tag8(epoch + 1)));
      STAMPW(12); TR(70);
      fence_async_smem();
      if (XR) bar_arrive(NB_C, 256);
    }
    asm volatile("setmaxnreg.inc.sync.aligned.u32 160;");
    const unsigned short* bp = (const unsigned short*)p.bsp + rb * 64 + w * 16 + (lane >> 2);
    const uint32_t bias = bp[0] | ((uint32_t)bp[8] << 16);
    float d[96];
    uint32_t z[48];
    {
      const uint64_t db = mkdesc(sb + OFF_B, 8192, 1024, 1);
#pragma unroll
      for (int i = 0; i < 96; i++) d[i] = 0.f;
      bar_sync(NB_G1, 256);
      if (GDL) { uint32_t tp = clock(); pace<false>(tp, GDL); }
      TR(71);
      if (PAUSE) {
        gemm_seg<192, 3>(d, sb, db, 0, SEG1, 0, 0, tid_now() == 0, 0 TSA);
        STAMPW(54); TR(72);
        mbar_wait(sb + (PAUSE == 1 ? BAR_ZG : BAR_ZP), 0);
        gemm_seg<192, 3>(d, sb, db, SEG1, 10, SEG1 % 5, SEG1 == 5, tid_now() == 0, 1 TSA);
      } else {
        gemm_seg<192, 3>(d, sb, db, 0, 10, 0, 0, tid_now() == 0, 0 TSA);
      }
      mbar_arrive_if(sb + BAR_YT, tid_now() == 0);
      STAMPW(14); TR(74);
      mbar_wait2(sb + BAR_XS, 0, sb + BAR_ST + 8, 0);
      const uint32_t xa1 = sb + OFF_XS + (w * 16 + (lane >> 2)) * 8;
      gelu_tile<false>(d, z, nullptr, sb + OFF_CS + (lane & 3) * 8, lds64f(xa1), lds64f(xa1 + 64), sb + BAR_XS);
    }
#pragma unroll
    for (int j = 0; j < 96; j++) d[j] = (j & 2) ? bf_hi(bias) : bf_lo(bias);
    STAMPW(15); TR(76);
    gemm_seg<192, 1>(d, sb, mkdesc(sb + OFF_B, 8192, 1024, 1), 0, 32, 0, 0, tid_now() == 0, 1 TSA);
    STAMPW(16); TR(77);
    {
      const int l2 = tid_now() & 31;
      const uint32_t ha = swz_base(sb + OFF_A, w, l2);
      const bool tg = (l2 & 3) == (l2 >> 3);
      const uint32_t tm = tg ? ~1u : ~0u, tb = tg ? lds32<0>(sb + OFF_TAG) & 1 : 0;
#pragma unroll
      for (int j = 0; j < 24; j += 2) {
#pragma unroll
        for (int e = 0; e < 4; e++) z[2 * j + e] = hmul2(z[2 * j + e], pack2(d[4 * j + 2 * e], d[4 * j + 2 * e + 1]));
        stsm4((ha ^ ((j & 7) * 16)) + (j >> 3) * A_SLOT, (z[2 * j] & tm) | tb, (z[2 * j + 1] & tm) | tb, z[2 * j + 2], z[2 * j + 3]);
        if ((j & 7) == 6 && (HPC || j == 22)) {
          fence_async_smem();
          __syncwarp();
          if (!HPC) { mbar_arrive_if(sb + BAR_HR - 16, l2 == 0); mbar_arrive_if(sb + BAR_HR - 8, l2 == 0); }
          mbar_arrive_if(sb + BAR_HR - 16 + (j >> 3) * 8, l2 == 0);
        }
      }
    }
    STAMPW(17); TR(78);
    const int t3 = tid_now();
    if (BPART) {
      mbar_wait(sb + BAR_HR, 0);
      gemm_seg<160, 4>(d, sb, mkdesc(sb + OFF_B, 2560, 128, 0), 0, 3, 0, 0, t3 == 0, 0 TSA);
      TR(79);
      bar_sync(NB_C, 128);
      mbar_wait(sb + BAR_ZP, 1);
#pragma unroll
      for (int j = 0; j < 10; j++)
        sts128(sb + OFF_A + j * 2048 + t3 * 16, pack2(d[8 * j], d[8 * j + 1]), pack2(d[8 * j + 2], d[8 * j + 3]), pack2(d[8 * j + 4], d[8 * j + 5]),
               pack2(d[8 * j + 6], d[8 * j + 7]));
      bar_sync(NB_C, 128);
      mbar_arrive_if(sb + BAR_PART, t3 == 0);
      STAMPW(45); TR(80);
    }
    {
      const uint32_t par = __shfl_sync(0xffffffff, lds32<0>(sb + OFF_TAG), 0), a = sb + OFF_A + w * 2048 + val_off(t3 & 31);
      const uint8_t* hs = p.scr->h + (size_t)rb * 12 * A_SLOT + w * 2048;
      const uint32_t rt = sb + OFF_RT + 8 * w;
#pragma unroll 1
      for (int it = 3; it < 12; it++) {
        const int s = it < 9 ? it : it - 9;
        mbar_wait(sb + BAR_AF + 8 * s, 1);
        validate<2>(a + s * A_SLOT, par, rt, [&]() { bulk_g2s(sb + OFF_A + s * A_SLOT + w * 2048, hs + g3_block(cb, it) * A_SLOT, 2048, rt); });
        if (elect_one()) mbar_arrive(sb + BAR_HV + 8 * (it - 3));
        if (it == 3) STAMPW(26);
      }
      if (YTAG) {
        const int l = t3 & 31;
        mbar_wait(sb + BAR_YT, 1);
        validate<5>(sb + OFF_CV + w * 5120 + (l >> 2) * 128 + ((2 * (l & 3)) ^ (l >> 2)) * 16, par, rt, [&]() { tma2d(sb + OFF_CV + w * 5120, &p.tmY, rb * 64, cb * 160 + w * 40, rt); });
        bar_sync(NB_C, 128);
        mbar_arrive_if(sb + BAR_PART, t3 == 0);
        STAMPW(57);
      }
    }
  } else {
    const int h = warp >> 2, w = warp & 3;
    Taps k;
    asm volatile("setmaxnreg.inc.sync.aligned.u32 160;");
    if (h == 0) {
      uint4* zs = &p.scr->zstat[rb * 128 + w * 8 + (lane >> 2)];
      if ((lane & 3) == 0) st_ll4(zs + cb * 32, 0, 0, 0, 0);
      float d[96];
      uint32_t z[48];
#pragma unroll
      for (int i = 0; i < 96; i++) d[i] = 0.f;
      gemm_seg<192, 0>(d, sb, mkdesc(sb + OFF_B, 8192, 1024, 1), 0, 10, 0, 0, tid_now() == 0, 0 TSA, [&]() { if (!GATE) bar_arrive(NB_G1, 256); });
      STAMPW(1); TR(0);
      const int tid = tid_now(), lane = tid & 31, g = lane >> 2, t = lane & 3;
      mbar_wait2(sb + BAR_XS, 0, sb + BAR_ST, 0);
      STAMPW(52); TR(1);
      const uint32_t xa1 = sb + OFF_XS + (w * 16 + g) * 8;
      const uint32_t tag = lds32<0>(sb + OFF_TAG);
      const float2 s0 = lds64f(xa1), s1 = lds64f(xa1 + 64);
      float st[4];
      gelu_tile<true>(d, z, st, sb + OFF_CS + 768 + t * 8, s0, s1, 0);
      TR(2);
      float2 sq = quad_sum(st, t);
      if (t < 2) st_ll2((uint2*)(zs + cb * 32) + t, tagged(sq.x, tag), __float_as_uint(sq.y));
      if (GATE) bar_arrive(NB_G1, 256);
      STAMPW(2); TR(3);
      if (ZW) { uint32_t tp = clock(); pace<false>(tp, ZW); }
      const uint4 u = poll3<false, PP, uint4>([&]() { return ld_ll4(zs + t * 32); }, [&](const uint4& v) { return (((v.x ^ tag) | (v.z ^ tag)) & 255u) == 0; });
      STAMPW(3); TR(10);
      st[0] = __uint_as_float(u.x); st[1] = __uint_as_float(u.y); st[2] = __uint_as_float(u.z); st[3] = __uint_as_float(u.w);
      sq = quad_sum(st, t);
      const float ca = 0.5f * ((t & 1) ? s1.y : s0.y), ma = sq.x * (1.f / 768.f);
      const float ra = ca * rsqrtf(fmaf(fmaxf(fmaf(-ma, ma, sq.y * (1.f / 768.f)), 0.f), ca * ca, 1e-5f));
      const uint32_t r2 = pack2(ra, ra);
      const float na = -ma * bf_lo(r2);
      const uint32_t n2 = pack2(na, na), r2o = __shfl_xor_sync(0xffffffff, r2, 1), n2o = __shfl_xor_sync(0xffffffff, n2, 1);
      const uint32_t fr[2] = {(t & 1) ? r2o : r2, (t & 1) ? r2 : r2o}, fn[2] = {(t & 1) ? n2o : n2, (t & 1) ? n2 : n2o};
      const uint32_t za = swz_base(sb + OFF_A, w, lane);
      TR(11);
      mbar_wait(sb + BAR_AE + 16, 0);
      TR(12);
#pragma unroll
      for (int j = 0; j < 24; j += 2)
        stsm4((za ^ ((j & 7) * 16)) + (j >> 3) * A_SLOT, hfma2(z[2 * j], fr[0], fn[0]), hfma2(z[2 * j + 1], fr[1], fn[1]), hfma2(z[2 * j + 2], fr[0], fn[0]), hfma2(z[2 * j + 3], fr[1], fn[1]));
      TR(14);
      fence_async_smem();
      bar_arrive(NB_Z, 160);
      STAMPW(4); TR(15);
      load_taps(k, p, chb + 64, tid);
    } else {
      if (!XR && w == 0) zero_pads(sb + OFF_CV, lane);
      const uint32_t epoch = load_epoch(p, lin, lane);
      const int t0 = (rb * 2 + (cb & 1)) * 32 + w * 8, c0 = (cb >> 1) * 320 + lane * 2;
      const __nv_bfloat16* kp = p.k + (size_t)(t0 - 3) * kD + c0;
      const __nv_bfloat16* vp = p.v + (size_t)t0 * kD + c0;
      const __nv_bfloat16* sp = p.shift + c0 * 4;
      const uint32_t oa = sb + OFF_CV + CV_SZ + kv_stage_addr(w, lane);
      bar_sync(NB_KF, 160);
      uint32_t tp = tstart;
      pace(tp, KV_T0);
      KvRegs n0, n1;
      uint32_t o[8];
      kv_load(n0, kp, vp, sp, t0 > 0);
      kv_load(n1, kp + 64, vp + 64, sp + 256, t0 > 0);
      const uint32_t tm = w >= 2 ? ~1u : ~0u, tb = w >= 2 ? (epoch + 1) & 1 : 0;
      if (XR) { bar_sync(NB_C, 256); if (w == 0) zero_pads(sb + OFF_CV, lane); }
      kv_calc(n0, o);
      kv_put(o, oa, tm, tb);
      kv_calc(n1, o);
      kv_put(o, oa + 4096, tm, tb);
      fence_async_smem();
      bar_arrive(NB_KU, 160);
      TR(0);
      if (KV2T) pace(tp, KV2T);
      kv_load(n0, kp + 128, vp + 128, sp + 512, t0 > 0);
      load_taps(k, p, chb, tid_now());
      kv_calc(n0, o);
      kv_put(o, oa + 8192, tm, tb);
      fence_async_smem();
      bar_arrive(NB_KU2, 160);
      STAMPW(13); TR(1);
    }
    {
      const int tid = tid_now();
      conv_worker(p, k, sb, h, chb + 64 - 64 * h, w, tid & 31, tid, rb, cb TSA);
    }
    float d[40];
    const int t3 = tid_now();
    const uint32_t o0 = (rb * 64 + w * 16 + ((t3 & 31) >> 2)) * kD + cb * 160 + h * 80;
    float cf[2];
    uint32_t xw[2][10], rn[4];
    const uint32_t xs_addr = sb + OFF_XS + (w * 16 + ((t3 & 31) >> 2)) * 8;
    TR(60);
    if (BPART) {
      mbar_wait(sb + BAR_PART, 0);
      TR(61);
#pragma unroll
      for (int j = 0; j < 5; j++) {
        const uint4 v = lds128(sb + OFF_A + (h * 5 + j) * 2048 + t3 * 16);
        d[8 * j] = bf_lo(v.x); d[8 * j + 1] = bf_hi(v.x); d[8 * j + 2] = bf_lo(v.y); d[8 * j + 3] = bf_hi(v.y);
        d[8 * j + 4] = bf_lo(v.z); d[8 * j + 5] = bf_hi(v.z); d[8 * j + 6] = bf_lo(v.w); d[8 * j + 7] = bf_hi(v.w);
      }
      fence_async_smem();
      bar_arrive(NB_PC, 288);
    } else {
#pragma unroll
      for (int j = 0; j < 40; j++) d[j] = 0.f;
    }
    TR(62);
    gemm_seg<80, 2>(d, sb, mkdesc(sb + OFF_B + h * 1280, 2560, 128, 0), BPART ? 3 : 0, 12, BPART ? 3 : 0, 0, t3 == 0, BPART TSA,
                    NoHook(), [&]() {
      final_load_x(xw, p.x + o0, t3 & 3);
      const float2 s0 = lds64f(xs_addr), s1 = lds64f(xs_addr + 64);
      cf[0] = 0.25f * s0.y; cf[1] = 0.25f * s1.y;
      rn[0] = pack2(s0.y, s0.y); rn[1] = pack2(s1.y, s1.y);
      rn[2] = pack2(-s0.x * bf_lo(rn[0]), -s0.x * bf_lo(rn[0])); rn[3] = pack2(-s1.x * bf_lo(rn[1]), -s1.x * bf_lo(rn[1]));
    });
    STAMPW(h ? 18 : 10);
    TR(63);
    const int l3 = tid_now() & 31;
    final_out(d, xw, rn, cf, sb + OFF_CV + h * 10240, p.out + o0, w, l3, [&]() {
      STAMPW(h ? 44 : 9);
      TR(64);
      if (YTAG) mbar_wait(sb + BAR_PART, BPART); else mbar_wait(sb + BAR_YT, 1);
      TR(65);
    });
    TR(66);
    mbar_arrive_if(sb + BAR_WE, t3 == 0);
  }
}

typedef CUresult (*EncodeFn)(CUtensorMap*, CUtensorMapDataType, cuuint32_t, void*, const cuuint64_t*, const cuuint64_t*, const cuuint32_t*,
                             const cuuint32_t*, CUtensorMapInterleave, CUtensorMapSwizzle, CUtensorMapL2promotion, CUtensorMapFloatOOBfill);

void encode(EncodeFn fn, CUtensorMap* m, const void* ptr, int rank, const cuuint64_t* dims, const cuuint64_t* strides, const cuuint32_t* box,
            CUtensorMapSwizzle swz = CU_TENSOR_MAP_SWIZZLE_128B) {
  const cuuint32_t es[3] = {1, 1, 1};
  fn(m, CU_TENSOR_MAP_DATA_TYPE_BFLOAT16, rank, const_cast<void*>(ptr), dims, strides, box, es, CU_TENSOR_MAP_INTERLEAVE_NONE,
     swz, CU_TENSOR_MAP_L2_PROMOTION_L2_128B, CU_TENSOR_MAP_FLOAT_OOB_FILL_NONE);
}

}

extern "C" void kernel_launch(void* const* d_in, const int* in_sizes, int n_in, void* d_out, int out_size) {
  (void)in_sizes; (void)n_in; (void)out_size;
  static EncodeFn enc = nullptr;
  static Scratch* scr = nullptr;
  static int sms = 0;
  if (!enc) {
    void* fn = nullptr;
    cudaDriverEntryPointQueryResult qr;
    cudaGetDriverEntryPoint("cuTensorMapEncodeTiled", &fn, cudaEnableDefault, &qr);
    enc = (EncodeFn)fn;
    cudaFuncSetAttribute(fused_kernel, cudaFuncAttributeMaxDynamicSharedMemorySize, SMEM_BYTES);
    cudaGetSymbolAddress((void**)&scr, g_scr);
    int dev = 0;
    cudaGetDevice(&dev);
    cudaDeviceGetAttribute(&sms, cudaDevAttrMultiProcessorCount, dev);
  }
  Params p;
  p.scr = scr;
  p.by_smid = sms == 132;
  for (int b = 0; b < 132; b++) {
    const int tp = b >> 1, t7 = (tp - 32) / 7;
    const int lin = tp < 32 ? ((tp & 7) ? (tp & 7) * 16 : 8) + (tp >> 3) * 2 + (b & 1)
                            : (tp < 60 ? (tp - 31 - t7 * 7) * 16 + 8 + t7 * 2 + (b & 1) : (tp < 62 ? 128 + (b & 3) : b - 124));
    const int cb = ((lin >> 4) & 1) * 2 + (lin & 1), rb = (lin >> 5) * 8 + ((lin >> 1) & 7);
    p.job[b] = lin < 128 ? lin | cb << 8 | rb << 10 : lin | (lin & 3) << 8;
  }
  p.x = (const __nv_bfloat16*)d_in[0];
  p.k = (const __nv_bfloat16*)d_in[1];
  p.v = (const __nv_bfloat16*)d_in[2];
  p.shift = (const __nv_bfloat16*)d_in[3];
  p.ssmk = (const __nv_bfloat16*)d_in[4];
  p.ssmD = (const __nv_bfloat16*)d_in[5];
  p.wsp = (const __nv_bfloat16*)d_in[8];
  p.bsp = (const __nv_bfloat16*)d_in[9];
  p.wout = (const __nv_bfloat16*)d_in[10];
  p.out = (__nv_bfloat16*)d_out;
  {
    const cuuint64_t dims[2] = {kD, kS}, st[1] = {kD * 2};
    const cuuint32_t box[2] = {64, 64};
    encode(enc, &p.tmX, d_in[0], 2, dims, st, box);
  }
  {
    const cuuint64_t dims[3] = {64, kD, kF / 64}, st[2] = {kF * 2, 128};
    const cuuint32_t box[3] = {64, 64, 3};
    encode(enc, &p.tmW, d_in[7], 3, dims, st, box);
  }
  {
    const cuuint64_t dims[2] = {kS, kS}, st[1] = {kS * 2};
    const cuuint32_t box[2] = {64, 64};
    encode(enc, &p.tmWsp, d_in[8], 2, dims, st, box);
  }
  {
    const cuuint64_t dims[2] = {kS, kD}, st[1] = {kS * 2};
    const cuuint32_t box[2] = {64, 40};
    encode(enc, &p.tmY, scr->y, 2, dims, st, box);
  }
  {
    const cuuint64_t dims[3] = {1024, kD / 2, 4}, st[2] = {8192, 2048};
    const cuuint32_t box[3] = {16, 32, 4};
    encode(enc, &p.tmKV, scr->kvx, 3, dims, st, box, CU_TENSOR_MAP_SWIZZLE_32B);
  }
  fused_kernel<<<132, 512, SMEM_BYTES, cudaStreamPerThread>>>(p);
}
```

```cpp
#include <cuda_runtime.h>
#include <cuda.h>
#include <cuda_bf16.h>
#include <stdint.h>

template <int N> struct WG;
template <> struct WG<16> {
  static __device__ __forceinline__ void rs(float* d, const uint32_t* a, uint64_t db) {
    asm volatile("{\n.reg .pred p;\nsetp.ne.b32 p, 1, 0;\nwgmma.mma_async.sync.aligned.m64n16k16.f32.bf16.bf16 {"
      "%0, %1, %2, %3, %4, %5, %6, %7"
      "}, {%8, %9, %10, %11}, %12, p, 1, 1, 0;\n}\n"
      :
      "+f"(d[0]), "+f"(d[1]), "+f"(d[2]), "+f"(d[3]), "+f"(d[4]), "+f"(d[5]), "+f"(d[6]), "+f"(d[7])
      : "r"(a[0]), "r"(a[1]), "r"(a[2]), "r"(a[3]), "l"(db));
  }
};
template <> struct WG<32> {
  static __device__ __forceinline__ void rs(float* d, const uint32_t* a, uint64_t db) {
    asm volatile("{\n.reg .pred p;\nsetp.ne.b32 p, 1, 0;\nwgmma.mma_async.sync.aligned.m64n32k16.f32.bf16.bf16 {"
      "%0, %1, %2, %3, %4, %5, %6, %7, %8, %9, %10, %11, %12, %13, %14, %15"
      "}, {%16, %17, %18, %19}, %20, p, 1, 1, 0;\n}\n"
      :
      "+f"(d[0]), "+f"(d[1]), "+f"(d[2]), "+f"(d[3]), "+f"(d[4]), "+f"(d[5]), "+f"(d[6]), "+f"(d[7]),
      "+f"(d[8]), "+f"(d[9]), "+f"(d[10]), "+f"(d[11]), "+f"(d[12]), "+f"(d[13]), "+f"(d[14]), "+f"(d[15])
      : "r"(a[0]), "r"(a[1]), "r"(a[2]), "r"(a[3]), "l"(db));
  }
};
template <> struct WG<48> {
  static __device__ __forceinline__ void rs(float* d, const uint32_t* a, uint64_t db) {
    asm volatile("{\n.reg .pred p;\nsetp.ne.b32 p, 1, 0;\nwgmma.mma_async.sync.aligned.m64n48k16.f32.bf16.bf16 {"
      "%0, %1, %2, %3, %4, %5, %6, %7, %8, %9, %10, %11, %12, %13, %14, %15, "
      "%16, %17, %18, %19, %20, %21, %22, %23"
      "}, {%24, %25, %26, %27}, %28, p, 1, 1, 0;\n}\n"
      :
      "+f"(d[0]), "+f"(d[1]), "+f"(d[2]), "+f"(d[3]), "+f"(d[4]), "+f"(d[5]), "+f"(d[6]), "+f"(d[7]),
      "+f"(d[8]), "+f"(d[9]), "+f"(d[10]), "+f"(d[11]), "+f"(d[12]), "+f"(d[13]), "+f"(d[14]), "+f"(d[15]),
      "+f"(d[16]), "+f"(d[17]), "+f"(d[18]), "+f"(d[19]), "+f"(d[20]), "+f"(d[21]), "+f"(d[22]), "+f"(d[23])
      : "r"(a[0]), "r"(a[1]), "r"(a[2]), "r"(a[3]), "l"(db));
  }
};
template <> struct WG<64> {
  static __device__ __forceinline__ void rs(float* d, const uint32_t* a, uint64_t db) {
    asm volatile("{\n.reg .pred p;\nsetp.ne.b32 p, 1, 0;\nwgmma.mma_async.sync.aligned.m64n64k16.f32.bf16.bf16 {"
      "%0, %1, %2, %3, %4, %5, %6, %7, %8, %9, %10, %11, %12, %13, %14, %15, "
      "%16, %17, %18, %19, %20, %21, %22, %23, %24, %25, %26, %27, %28, %29, %30, %31"
      "}, {%32, %33, %34, %35}, %36, p, 1, 1, 0;\n}\n"
      :
      "+f"(d[0]), "+f"(d[1]), "+f"(d[2]), "+f"(d[3]), "+f"(d[4]), "+f"(d[5]), "+f"(d[6]), "+f"(d[7]),
      "+f"(d[8]), "+f"(d[9]), "+f"(d[10]), "+f"(d[11]), "+f"(d[12]), "+f"(d[13]), "+f"(d[14]), "+f"(d[15]),
      "+f"(d[16]), "+f"(d[17]), "+f"(d[18]), "+f"(d[19]), "+f"(d[20]), "+f"(d[21]), "+f"(d[22]), "+f"(d[23]),
      "+f"(d[24]), "+f"(d[25]), "+f"(d[26]), "+f"(d[27]), "+f"(d[28]), "+f"(d[29]), "+f"(d[30]), "+f"(d[31])
      : "r"(a[0]), "r"(a[1]), "r"(a[2]), "r"(a[3]), "l"(db));
  }
};
template <> struct WG<80> {
  static __device__ __forceinline__ void rs(float* d, const uint32_t* a, uint64_t db) {
    asm volatile("{\n.reg .pred p;\nsetp.ne.b32 p, 1, 0;\nwgmma.mma_async.sync.aligned.m64n80k16.f32.bf16.bf16 {"
      "%0, %1, %2, %3, %4, %5, %6, %7, %8, %9, %10, %11, %12, %13, %14, %15, "
      "%16, %17, %18, %19, %20, %21, %22, %23, %24, %25, %26, %27, %28, %29, %30, %31, "
      "%32, %33, %34, %35, %36, %37, %38, %39"
      "}, {%40, %41, %42, %43}, %44, p, 1, 1, 0;\n}\n"
      :
      "+f"(d[0]), "+f"(d[1]), "+f"(d[2]), "+f"(d[3]), "+f"(d[4]), "+f"(d[5]), "+f"(d[6]), "+f"(d[7]),
      "+f"(d[8]), "+f"(d[9]), "+f"(d[10]), "+f"(d[11]), "+f"(d[12]), "+f"(d[13]), "+f"(d[14]), "+f"(d[15]),
      "+f"(d[16]), "+f"(d[17]), "+f"(d[18]), "+f"(d[19]), "+f"(d[20]), "+f"(d[21]), "+f"(d[22]), "+f"(d[23]),
      "+f"(d[24]), "+f"(d[25]), "+f"(d[26]), "+f"(d[27]), "+f"(d[28]), "+f"(d[29]), "+f"(d[30]), "+f"(d[31]),
      "+f"(d[32]), "+f"(d[33]), "+f"(d[34]), "+f"(d[35]), "+f"(d[36]), "+f"(d[37]), "+f"(d[38]), "+f"(d[39])
      : "r"(a[0]), "r"(a[1]), "r"(a[2]), "r"(a[3]), "l"(db));
  }
};
template <> struct WG<96> {
  static __device__ __forceinline__ void rs(float* d, const uint32_t* a, uint64_t db) {
    asm volatile("{\n.reg .pred p;\nsetp.ne.b32 p, 1, 0;\nwgmma.mma_async.sync.aligned.m64n96k16.f32.bf16.bf16 {"
      "%0, %1, %2, %3, %4, %5, %6, %7, %8, %9, %10, %11, %12, %13, %14, %15, "
      "%16, %17, %18, %19, %20, %21, %22, %23, %24, %25, %26, %27, %28, %29, %30, %31, "
      "%32, %33, %34, %35, %36, %37, %38, %39, %40, %41, %42, %43, %44, %45, %46, %47"
      "}, {%48, %49, %50, %51}, %52, p, 1, 1, 0;\n}\n"
      :
      "+f"(d[0]), "+f"(d[1]), "+f"(d[2]), "+f"(d[3]), "+f"(d[4]), "+f"(d[5]), "+f"(d[6]), "+f"(d[7]),
      "+f"(d[8]), "+f"(d[9]), "+f"(d[10]), "+f"(d[11]), "+f"(d[12]), "+f"(d[13]), "+f"(d[14]), "+f"(d[15]),
      "+f"(d[16]), "+f"(d[17]), "+f"(d[18]), "+f"(d[19]), "+f"(d[20]), "+f"(d[21]), "+f"(d[22]), "+f"(d[23]),
      "+f"(d[24]), "+f"(d[25]), "+f"(d[26]), "+f"(d[27]), "+f"(d[28]), "+f"(d[29]), "+f"(d[30]), "+f"(d[31]),
      "+f"(d[32]), "+f"(d[33]), "+f"(d[34]), "+f"(d[35]), "+f"(d[36]), "+f"(d[37]), "+f"(d[38]), "+f"(d[39]),
      "+f"(d[40]), "+f"(d[41]), "+f"(d[42]), "+f"(d[43]), "+f"(d[44]), "+f"(d[45]), "+f"(d[46]), "+f"(d[47])
      : "r"(a[0]), "r"(a[1]), "r"(a[2]), "r"(a[3]), "l"(db));
  }
};
template <> struct WG<112> {
  static __device__ __forceinline__ void rs(float* d, const uint32_t* a, uint64_t db) {
    asm volatile("{\n.reg .pred p;\nsetp.ne.b32 p, 1, 0;\nwgmma.mma_async.sync.aligned.m64n112k16.f32.bf16.bf16 {"
      "%0, %1, %2, %3, %4, %5, %6, %7, %8, %9, %10, %11, %12, %13, %14, %15, "
      "%16, %17, %18, %19, %20, %21, %22, %23, %24, %25, %26, %27, %28, %29, %30, %31, "
      "%32, %33, %34, %35, %36, %37, %38, %39, %40, %41, %42, %43, %44, %45, %46, %47, "
      "%48, %49, %50, %51, %52, %53, %54, %55"
      "}, {%56, %57, %58, %59}, %60, p, 1, 1, 0;\n}\n"
      :
      "+f"(d[0]), "+f"(d[1]), "+f"(d[2]), "+f"(d[3]), "+f"(d[4]), "+f"(d[5]), "+f"(d[6]), "+f"(d[7]),
      "+f"(d[8]), "+f"(d[9]), "+f"(d[10]), "+f"(d[11]), "+f"(d[12]), "+f"(d[13]), "+f"(d[14]), "+f"(d[15]),
      "+f"(d[16]), "+f"(d[17]), "+f"(d[18]), "+f"(d[19]), "+f"(d[20]), "+f"(d[21]), "+f"(d[22]), "+f"(d[23]),
      "+f"(d[24]), "+f"(d[25]), "+f"(d[26]), "+f"(d[27]), "+f"(d[28]), "+f"(d[29]), "+f"(d[30]), "+f"(d[31]),
      "+f"(d[32]), "+f"(d[33]), "+f"(d[34]), "+f"(d[35]), "+f"(d[36]), "+f"(d[37]), "+f"(d[38]), "+f"(d[39]),
      "+f"(d[40]), "+f"(d[41]), "+f"(d[42]), "+f"(d[43]), "+f"(d[44]), "+f"(d[45]), "+f"(d[46]), "+f"(d[47]),
      "+f"(d[48]), "+f"(d[49]), "+f"(d[50]), "+f"(d[51]), "+f"(d[52]), "+f"(d[53]), "+f"(d[54]), "+f"(d[55])
      : "r"(a[0]), "r"(a[1]), "r"(a[2]), "r"(a[3]), "l"(db));
  }
};
template <> struct WG<128> {
  static __device__ __forceinline__ void rs(float* d, const uint32_t* a, uint64_t db) {
    asm volatile("{\n.reg .pred p;\nsetp.ne.b32 p, 1, 0;\nwgmma.mma_async.sync.aligned.m64n128k16.f32.bf16.bf16 {"
      "%0, %1, %2, %3, %4, %5, %6, %7, %8, %9, %10, %11, %12, %13, %14, %15, "
      "%16, %17, %18, %19, %20, %21, %22, %23, %24, %25, %26, %27, %28, %29, %30, %31, "
      "%32, %33, %34, %35, %36, %37, %38, %39, %40, %41, %42, %43, %44, %45, %46, %47, "
      "%48, %49, %50, %51, %52, %53, %54, %55, %56, %57, %58, %59, %60, %61, %62, %63"
      "}, {%64, %65, %66, %67}, %68, p, 1, 1, 0;\n}\n"
      :
      "+f"(d[0]), "+f"(d[1]), "+f"(d[2]), "+f"(d[3]), "+f"(d[4]), "+f"(d[5]), "+f"(d[6]), "+f"(d[7]),
      "+f"(d[8]), "+f"(d[9]), "+f"(d[10]), "+f"(d[11]), "+f"(d[12]), "+f"(d[13]), "+f"(d[14]), "+f"(d[15]),
      "+f"(d[16]), "+f"(d[17]), "+f"(d[18]), "+f"(d[19]), "+f"(d[20]), "+f"(d[21]), "+f"(d[22]), "+f"(d[23]),
      "+f"(d[24]), "+f"(d[25]), "+f"(d[26]), "+f"(d[27]), "+f"(d[28]), "+f"(d[29]), "+f"(d[30]), "+f"(d[31]),
      "+f"(d[32]), "+f"(d[33]), "+f"(d[34]), "+f"(d[35]), "+f"(d[36]), "+f"(d[37]), "+f"(d[38]), "+f"(d[39]),
      "+f"(d[40]), "+f"(d[41]), "+f"(d[42]), "+f"(d[43]), "+f"(d[44]), "+f"(d[45]), "+f"(d[46]), "+f"(d[47]),
      "+f"(d[48]), "+f"(d[49]), "+f"(d[50]), "+f"(d[51]), "+f"(d[52]), "+f"(d[53]), "+f"(d[54]), "+f"(d[55]),
      "+f"(d[56]), "+f"(d[57]), "+f"(d[58]), "+f"(d[59]), "+f"(d[60]), "+f"(d[61]), "+f"(d[62]), "+f"(d[63])
      : "r"(a[0]), "r"(a[1]), "r"(a[2]), "r"(a[3]), "l"(db));
  }
};
template <int N> struct KB;
template <> struct KB<80> {
  template <int W, int RC, bool RA, int BSTEP> static __device__ __forceinline__ void run(float* d, uint64_t da, uint64_t db, uint32_t rel, uint32_t rela, uint32_t doR, uint32_t fa, uint32_t pa, uint32_t fb, uint32_t pb, uint32_t acc) {
    if constexpr (W == 0 && RC == 1 && RA == 0) asm volatile(
    "{\n.reg .pred p, q, r, t;\n.reg .b64 a, b;\n.reg .u32 n;\nsetp.ne.b32 t, 1, 0;\nsetp.ne.b32 r, %49, 0;\n"
    "wgmma.mma_async.sync.aligned.m64n80k16.f32.bf16.bf16 {"
      "%0, %1, %2, %3, %4, %5, %6, %7, %8, %9, %10, %11, %12, %13, %14, %15, "
      "%16, %17, %18, %19, %20, %21, %22, %23, %24, %25, %26, %27, %28, %29, %30, %31, "
      "%32, %33, %34, %35, %36, %37, %38, %39"
      "}, %40, %41, r, 1, 1, 0, 1;\n"
    "add.u64 a, %40, 2;\nadd.u64 b, %41, %48;\n"
    "wgmma.mma_async.sync.aligned.m64n80k16.f32.bf16.bf16 {"
      "%0, %1, %2, %3, %4, %5, %6, %7, %8, %9, %10, %11, %12, %13, %14, %15, "
      "%16, %17, %18, %19, %20, %21, %22, %23, %24, %25, %26, %27, %28, %29, %30, %31, "
      "%32, %33, %34, %35, %36, %37, %38, %39"
      "}, a, b, t, 1, 1, 0, 1;\n"
    "wgmma.commit_group.sync.aligned;\nwgmma.wait_group.sync.aligned 1;\n"
    "add.u64 a, %40, 4;\nadd.u64 b, %41, 2*%48;\n"
    "wgmma.mma_async.sync.aligned.m64n80k16.f32.bf16.bf16 {"
      "%0, %1, %2, %3, %4, %5, %6, %7, %8, %9, %10, %11, %12, %13, %14, %15, "
      "%16, %17, %18, %19, %20, %21, %22, %23, %24, %25, %26, %27, %28, %29, %30, %31, "
      "%32, %33, %34, %35, %36, %37, %38, %39"
      "}, a, b, t, 1, 1, 0, 1;\n"
    "setp.ne.u32 q, %43, 0;\n@q mbarrier.arrive.shared::cta.b64 _, [%42];\n"
    "add.u64 a, %40, 6;\nadd.u64 b, %41, 3*%48;\n"
    "wgmma.mma_async.sync.aligned.m64n80k16.f32.bf16.bf16 {"
      "%0, %1, %2, %3, %4, %5, %6, %7, %8, %9, %10, %11, %12, %13, %14, %15, "
      "%16, %17, %18, %19, %20, %21, %22, %23, %24, %25, %26, %27, %28, %29, %30, %31, "
      "%32, %33, %34, %35, %36, %37, %38, %39"
      "}, a, b, t, 1, 1, 0, 1;\n"
    "wgmma.commit_group.sync.aligned;\n"
    "}\n"
      :
      "+f"(d[0]), "+f"(d[1]), "+f"(d[2]), "+f"(d[3]), "+f"(d[4]), "+f"(d[5]), "+f"(d[6]), "+f"(d[7]),
      "+f"(d[8]), "+f"(d[9]), "+f"(d[10]), "+f"(d[11]), "+f"(d[12]), "+f"(d[13]), "+f"(d[14]), "+f"(d[15]),
      "+f"(d[16]), "+f"(d[17]), "+f"(d[18]), "+f"(d[19]), "+f"(d[20]), "+f"(d[21]), "+f"(d[22]), "+f"(d[23]),
      "+f"(d[24]), "+f"(d[25]), "+f"(d[26]), "+f"(d[27]), "+f"(d[28]), "+f"(d[29]), "+f"(d[30]), "+f"(d[31]),
      "+f"(d[32]), "+f"(d[33]), "+f"(d[34]), "+f"(d[35]), "+f"(d[36]), "+f"(d[37]), "+f"(d[38]), "+f"(d[39])
      : "l"(da), "l"(db), "r"(rel), "r"(doR), "r"(fa), "r"(pa), "r"(fb), "r"(pb), "n"(BSTEP), "r"(acc), "r"(rela) : "memory");
    else if constexpr (W == 2 && RC == 1 && RA == 0) asm volatile(
    "{\n.reg .pred p, q, r, t;\n.reg .b64 a, b;\n.reg .u32 n;\nsetp.ne.b32 t, 1, 0;\nsetp.ne.b32 r, %49, 0;\n"
    "wgmma.mma_async.sync.aligned.m64n80k16.f32.bf16.bf16 {"
      "%0, %1, %2, %3, %4, %5, %6, %7, %8, %9, %10, %11, %12, %13, %14, %15, "
      "%16, %17, %18, %19, %20, %21, %22, %23, %24, %25, %26, %27, %28, %29, %30, %31, "
      "%32, %33, %34, %35, %36, %37, %38, %39"
      "}, %40, %41, r, 1, 1, 0, 1;\n"
    "add.u64 a, %40, 2;\nadd.u64 b, %41, %48;\n"
    "wgmma.mma_async.sync.aligned.m64n80k16.f32.bf16.bf16 {"
      "%0, %1, %2, %3, %4, %5, %6, %7, %8, %9, %10, %11, %12, %13, %14, %15, "
      "%16, %17, %18, %19, %20, %21, %22, %23, %24, %25, %26, %27, %28, %29, %30, %31, "
      "%32, %33, %34, %35, %36, %37, %38, %39"
      "}, a, b, t, 1, 1, 0, 1;\n"
    "wgmma.commit_group.sync.aligned;\nwgmma.wait_group.sync.aligned 1;\n"
    "add.u64 a, %40, 4;\nadd.u64 b, %41, 2*%48;\n"
    "wgmma.mma_async.sync.aligned.m64n80k16.f32.bf16.bf16 {"
      "%0, %1, %2, %3, %4, %5, %6, %7, %8, %9, %10, %11, %12, %13, %14, %15, "
      "%16, %17, %18, %19, %20, %21, %22, %23, %24, %25, %26, %27, %28, %29, %30, %31, "
      "%32, %33, %34, %35, %36, %37, %38, %39"
      "}, a, b, t, 1, 1, 0, 1;\n"
    "setp.ne.u32 q, %43, 0;\n@q mbarrier.arrive.shared::cta.b64 _, [%42];\n"
    "mbarrier.test_wait.parity.shared::cta.b64 p, [%46], %47;\n"
    "mbarrier.test_wait.parity.shared::cta.b64 r, [%44], %45;\nand.pred p, p, r;\n"
    "add.u64 a, %40, 6;\nadd.u64 b, %41, 3*%48;\n"
    "wgmma.mma_async.sync.aligned.m64n80k16.f32.bf16.bf16 {"
      "%0, %1, %2, %3, %4, %5, %6, %7, %8, %9, %10, %11, %12, %13, %14, %15, "
      "%16, %17, %18, %19, %20, %21, %22, %23, %24, %25, %26, %27, %28, %29, %30, %31, "
      "%32, %33, %34, %35, %36, %37, %38, %39"
      "}, a, b, t, 1, 1, 0, 1;\n"
    "wgmma.commit_group.sync.aligned;\n"
    "@p bra.uni DN;\nmov.u32 n, 0;\nWT: mbarrier.try_wait.parity.shared::cta.b64 p, [%46], %47;\nmbarrier.try_wait.parity.shared::cta.b64 r, [%44], %45;\nand.pred p, p, r;\n@p bra.uni DN;\nadd.u32 n, n, 1;\nsetp.lt.u32 p, n, 0x100000;\n@p bra.uni WT;\nDN:\n"
    "}\n"
      :
      "+f"(d[0]), "+f"(d[1]), "+f"(d[2]), "+f"(d[3]), "+f"(d[4]), "+f"(d[5]), "+f"(d[6]), "+f"(d[7]),
      "+f"(d[8]), "+f"(d[9]), "+f"(d[10]), "+f"(d[11]), "+f"(d[12]), "+f"(d[13]), "+f"(d[14]), "+f"(d[15]),
      "+f"(d[16]), "+f"(d[17]), "+f"(d[18]), "+f"(d[19]), "+f"(d[20]), "+f"(d[21]), "+f"(d[22]), "+f"(d[23]),
      "+f"(d[24]), "+f"(d[25]), "+f"(d[26]), "+f"(d[27]), "+f"(d[28]), "+f"(d[29]), "+f"(d[30]), "+f"(d[31]),
      "+f"(d[32]), "+f"(d[33]), "+f"(d[34]), "+f"(d[35]), "+f"(d[36]), "+f"(d[37]), "+f"(d[38]), "+f"(d[39])
      : "l"(da), "l"(db), "r"(rel), "r"(doR), "r"(fa), "r"(pa), "r"(fb), "r"(pb), "n"(BSTEP), "r"(acc), "r"(rela) : "memory");
    else static_assert(W < 0, "variant not generated");
  }
};
template <> struct KB<160> {
  template <int W, int RC, bool RA, int BSTEP> static __device__ __forceinline__ void run(float* d, uint64_t da, uint64_t db, uint32_t rel, uint32_t rela, uint32_t doR, uint32_t fa, uint32_t pa, uint32_t fb, uint32_t pb, uint32_t acc) {
    if constexpr (W == 0 && RC == 2 && RA == 0) asm volatile(
    "{\n.reg .pred p, q, r, t;\n.reg .b64 a, b;\n.reg .u32 n;\nsetp.ne.b32 t, 1, 0;\nsetp.ne.b32 r, %89, 0;\n"
    "wgmma.mma_async.sync.aligned.m64n160k16.f32.bf16.bf16 {"
      "%0, %1, %2, %3, %4, %5, %6, %7, %8, %9, %10, %11, %12, %13, %14, %15, "
      "%16, %17, %18, %19, %20, %21, %22, %23, %24, %25, %26, %27, %28, %29, %30, %31, "
      "%32, %33, %34, %35, %36, %37, %38, %39, %40, %41, %42, %43, %44, %45, %46, %47, "
      "%48, %49, %50, %51, %52, %53, %54, %55, %56, %57, %58, %59, %60, %61, %62, %63, "
      "%64, %65, %66, %67, %68, %69, %70, %71, %72, %73, %74, %75, %76, %77, %78, %79"
      "}, %80, %81, r, 1, 1, 0, 1;\n"
    "add.u64 a, %80, 2;\nadd.u64 b, %81, %88;\n"
    "wgmma.mma_async.sync.aligned.m64n160k16.f32.bf16.bf16 {"
      "%0, %1, %2, %3, %4, %5, %6, %7, %8, %9, %10, %11, %12, %13, %14, %15, "
      "%16, %17, %18, %19, %20, %21, %22, %23, %24, %25, %26, %27, %28, %29, %30, %31, "
      "%32, %33, %34, %35, %36, %37, %38, %39, %40, %41, %42, %43, %44, %45, %46, %47, "
      "%48, %49, %50, %51, %52, %53, %54, %55, %56, %57, %58, %59, %60, %61, %62, %63, "
      "%64, %65, %66, %67, %68, %69, %70, %71, %72, %73, %74, %75, %76, %77, %78, %79"
      "}, a, b, t, 1, 1, 0, 1;\n"
    "wgmma.commit_group.sync.aligned;\nwgmma.wait_group.sync.aligned 1;\n"
    "add.u64 a, %80, 4;\nadd.u64 b, %81, 2*%88;\n"
    "wgmma.mma_async.sync.aligned.m64n160k16.f32.bf16.bf16 {"
      "%0, %1, %2, %3, %4, %5, %6, %7, %8, %9, %10, %11, %12, %13, %14, %15, "
      "%16, %17, %18, %19, %20, %21, %22, %23, %24, %25, %26, %27, %28, %29, %30, %31, "
      "%32, %33, %34, %35, %36, %37, %38, %39, %40, %41, %42, %43, %44, %45, %46, %47, "
      "%48, %49, %50, %51, %52, %53, %54, %55, %56, %57, %58, %59, %60, %61, %62, %63, "
      "%64, %65, %66, %67, %68, %69, %70, %71, %72, %73, %74, %75, %76, %77, %78, %79"
      "}, a, b, t, 1, 1, 0, 1;\n"
    "setp.ne.u32 q, %83, 0;\n@q mbarrier.arrive.shared::cta.b64 _, [%82];\n@q mbarrier.arrive.shared::cta.b64 _, [%82];\n"
    "add.u64 a, %80, 6;\nadd.u64 b, %81, 3*%88;\n"
    "wgmma.mma_async.sync.aligned.m64n160k16.f32.bf16.bf16 {"
      "%0, %1, %2, %3, %4, %5, %6, %7, %8, %9, %10, %11, %12, %13, %14, %15, "
      "%16, %17, %18, %19, %20, %21, %22, %23, %24, %25, %26, %27, %28, %29, %30, %31, "
      "%32, %33, %34, %35, %36, %37, %38, %39, %40, %41, %42, %43, %44, %45, %46, %47, "
      "%48, %49, %50, %51, %52, %53, %54, %55, %56, %57, %58, %59, %60, %61, %62, %63, "
      "%64, %65, %66, %67, %68, %69, %70, %71, %72, %73, %74, %75, %76, %77, %78, %79"
      "}, a, b, t, 1, 1, 0, 1;\n"
    "wgmma.commit_group.sync.aligned;\n"
    "}\n"
      :
      "+f"(d[0]), "+f"(d[1]), "+f"(d[2]), "+f"(d[3]), "+f"(d[4]), "+f"(d[5]), "+f"(d[6]), "+f"(d[7]),
      "+f"(d[8]), "+f"(d[9]), "+f"(d[10]), "+f"(d[11]), "+f"(d[12]), "+f"(d[13]), "+f"(d[14]), "+f"(d[15]),
      "+f"(d[16]), "+f"(d[17]), "+f"(d[18]), "+f"(d[19]), "+f"(d[20]), "+f"(d[21]), "+f"(d[22]), "+f"(d[23]),
      "+f"(d[24]), "+f"(d[25]), "+f"(d[26]), "+f"(d[27]), "+f"(d[28]), "+f"(d[29]), "+f"(d[30]), "+f"(d[31]),
      "+f"(d[32]), "+f"(d[33]), "+f"(d[34]), "+f"(d[35]), "+f"(d[36]), "+f"(d[37]), "+f"(d[38]), "+f"(d[39]),
      "+f"(d[40]), "+f"(d[41]), "+f"(d[42]), "+f"(d[43]), "+f"(d[44]), "+f"(d[45]), "+f"(d[46]), "+f"(d[47]),
      "+f"(d[48]), "+f"(d[49]), "+f"(d[50]), "+f"(d[51]), "+f"(d[52]), "+f"(d[53]), "+f"(d[54]), "+f"(d[55]),
      "+f"(d[56]), "+f"(d[57]), "+f"(d[58]), "+f"(d[59]), "+f"(d[60]), "+f"(d[61]), "+f"(d[62]), "+f"(d[63]),
      "+f"(d[64]), "+f"(d[65]), "+f"(d[66]), "+f"(d[67]), "+f"(d[68]), "+f"(d[69]), "+f"(d[70]), "+f"(d[71]),
      "+f"(d[72]), "+f"(d[73]), "+f"(d[74]), "+f"(d[75]), "+f"(d[76]), "+f"(d[77]), "+f"(d[78]), "+f"(d[79])
      : "l"(da), "l"(db), "r"(rel), "r"(doR), "r"(fa), "r"(pa), "r"(fb), "r"(pb), "n"(BSTEP), "r"(acc), "r"(rela) : "memory");
    else if constexpr (W == 1 && RC == 2 && RA == 0) asm volatile(
    "{\n.reg .pred p, q, r, t;\n.reg .b64 a, b;\n.reg .u32 n;\nsetp.ne.b32 t, 1, 0;\nsetp.ne.b32 r, %89, 0;\n"
    "wgmma.mma_async.sync.aligned.m64n160k16.f32.bf16.bf16 {"
      "%0, %1, %2, %3, %4, %5, %6, %7, %8, %9, %10, %11, %12, %13, %14, %15, "
      "%16, %17, %18, %19, %20, %21, %22, %23, %24, %25, %26, %27, %28, %29, %30, %31, "
      "%32, %33, %34, %35, %36, %37, %38, %39, %40, %41, %42, %43, %44, %45, %46, %47, "
      "%48, %49, %50, %51, %52, %53, %54, %55, %56, %57, %58, %59, %60, %61, %62, %63, "
      "%64, %65, %66, %67, %68, %69, %70, %71, %72, %73, %74, %75, %76, %77, %78, %79"
      "}, %80, %81, r, 1, 1, 0, 1;\n"
    "add.u64 a, %80, 2;\nadd.u64 b, %81, %88;\n"
    "wgmma.mma_async.sync.aligned.m64n160k16.f32.bf16.bf16 {"
      "%0, %1, %2, %3, %4, %5, %6, %7, %8, %9, %10, %11, %12, %13, %14, %15, "
      "%16, %17, %18, %19, %20, %21, %22, %23, %24, %25, %26, %27, %28, %29, %30, %31, "
      "%32, %33, %34, %35, %36, %37, %38, %39, %40, %41, %42, %43, %44, %45, %46, %47, "
      "%48, %49, %50, %51, %52, %53, %54, %55, %56, %57, %58, %59, %60, %61, %62, %63, "
      "%64, %65, %66, %67, %68, %69, %70, %71, %72, %73, %74, %75, %76, %77, %78, %79"
      "}, a, b, t, 1, 1, 0, 1;\n"
    "wgmma.commit_group.sync.aligned;\nwgmma.wait_group.sync.aligned 1;\n"
    "add.u64 a, %80, 4;\nadd.u64 b, %81, 2*%88;\n"
    "wgmma.mma_async.sync.aligned.m64n160k16.f32.bf16.bf16 {"
      "%0, %1, %2, %3, %4, %5, %6, %7, %8, %9, %10, %11, %12, %13, %14, %15, "
      "%16, %17, %18, %19, %20, %21, %22, %23, %24, %25, %26, %27, %28, %29, %30, %31, "
      "%32, %33, %34, %35, %36, %37, %38, %39, %40, %41, %42, %43, %44, %45, %46, %47, "
      "%48, %49, %50, %51, %52, %53, %54, %55, %56, %57, %58, %59, %60, %61, %62, %63, "
      "%64, %65, %66, %67, %68, %69, %70, %71, %72, %73, %74, %75, %76, %77, %78, %79"
      "}, a, b, t, 1, 1, 0, 1;\n"
    "setp.ne.u32 q, %83, 0;\n@q mbarrier.arrive.shared::cta.b64 _, [%82];\n@q mbarrier.arrive.shared::cta.b64 _, [%82];\n"
    "mbarrier.test_wait.parity.shared::cta.b64 p, [%86], %87;\n"
    "add.u64 a, %80, 6;\nadd.u64 b, %81, 3*%88;\n"
    "wgmma.mma_async.sync.aligned.m64n160k16.f32.bf16.bf16 {"
      "%0, %1, %2, %3, %4, %5, %6, %7, %8, %9, %10, %11, %12, %13, %14, %15, "
      "%16, %17, %18, %19, %20, %21, %22, %23, %24, %25, %26, %27, %28, %29, %30, %31, "
      "%32, %33, %34, %35, %36, %37, %38, %39, %40, %41, %42, %43, %44, %45, %46, %47, "
      "%48, %49, %50, %51, %52, %53, %54, %55, %56, %57, %58, %59, %60, %61, %62, %63, "
      "%64, %65, %66, %67, %68, %69, %70, %71, %72, %73, %74, %75, %76, %77, %78, %79"
      "}, a, b, t, 1, 1, 0, 1;\n"
    "wgmma.commit_group.sync.aligned;\n"
    "@p bra.uni DN;\nmov.u32 n, 0;\nWT: mbarrier.try_wait.parity.shared::cta.b64 p, [%86], %87;\n@p bra.uni DN;\nadd.u32 n, n, 1;\nsetp.lt.u32 p, n, 0x100000;\n@p bra.uni WT;\nDN:\n"
    "}\n"
      :
      "+f"(d[0]), "+f"(d[1]), "+f"(d[2]), "+f"(d[3]), "+f"(d[4]), "+f"(d[5]), "+f"(d[6]), "+f"(d[7]),
      "+f"(d[8]), "+f"(d[9]), "+f"(d[10]), "+f"(d[11]), "+f"(d[12]), "+f"(d[13]), "+f"(d[14]), "+f"(d[15]),
      "+f"(d[16]), "+f"(d[17]), "+f"(d[18]), "+f"(d[19]), "+f"(d[20]), "+f"(d[21]), "+f"(d[22]), "+f"(d[23]),
      "+f"(d[24]), "+f"(d[25]), "+f"(d[26]), "+f"(d[27]), "+f"(d[28]), "+f"(d[29]), "+f"(d[30]), "+f"(d[31]),
      "+f"(d[32]), "+f"(d[33]), "+f"(d[34]), "+f"(d[35]), "+f"(d[36]), "+f"(d[37]), "+f"(d[38]), "+f"(d[39]),
      "+f"(d[40]), "+f"(d[41]), "+f"(d[42]), "+f"(d[43]), "+f"(d[44]), "+f"(d[45]), "+f"(d[46]), "+f"(d[47]),
      "+f"(d[48]), "+f"(d[49]), "+f"(d[50]), "+f"(d[51]), "+f"(d[52]), "+f"(d[53]), "+f"(d[54]), "+f"(d[55]),
      "+f"(d[56]), "+f"(d[57]), "+f"(d[58]), "+f"(d[59]), "+f"(d[60]), "+f"(d[61]), "+f"(d[62]), "+f"(d[63]),
      "+f"(d[64]), "+f"(d[65]), "+f"(d[66]), "+f"(d[67]), "+f"(d[68]), "+f"(d[69]), "+f"(d[70]), "+f"(d[71]),
      "+f"(d[72]), "+f"(d[73]), "+f"(d[74]), "+f"(d[75]), "+f"(d[76]), "+f"(d[77]), "+f"(d[78]), "+f"(d[79])
      : "l"(da), "l"(db), "r"(rel), "r"(doR), "r"(fa), "r"(pa), "r"(fb), "r"(pb), "n"(BSTEP), "r"(acc), "r"(rela) : "memory");
    else static_assert(W < 0, "variant not generated");
  }
};
template <> struct KB<192> {
  template <int W, int RC, bool RA, int BSTEP> static __device__ __forceinline__ void run(float* d, uint64_t da, uint64_t db, uint32_t rel, uint32_t rela, uint32_t doR, uint32_t fa, uint32_t pa, uint32_t fb, uint32_t pb, uint32_t acc) {
    if constexpr (W == 0 && RC == 2 && RA == 0) asm volatile(
    "{\n.reg .pred p, q, r, t;\n.reg .b64 a, b;\n.reg .u32 n;\nsetp.ne.b32 t, 1, 0;\nsetp.ne.b32 r, %105, 0;\n"
    "wgmma.mma_async.sync.aligned.m64n192k16.f32.bf16.bf16 {"
      "%0, %1, %2, %3, %4, %5, %6, %7, %8, %9, %10, %11, %12, %13, %14, %15, "
      "%16, %17, %18, %19, %20, %21, %22, %23, %24, %25, %26, %27, %28, %29, %30, %31, "
      "%32, %33, %34, %35, %36, %37, %38, %39, %40, %41, %42, %43, %44, %45, %46, %47, "
      "%48, %49, %50, %51, %52, %53, %54, %55, %56, %57, %58, %59, %60, %61, %62, %63, "
      "%64, %65, %66, %67, %68, %69, %70, %71, %72, %73, %74, %75, %76, %77, %78, %79, "
      "%80, %81, %82, %83, %84, %85, %86, %87, %88, %89, %90, %91, %92, %93, %94, %95"
      "}, %96, %97, r, 1, 1, 0, 1;\n"
    "add.u64 a, %96, 2;\nadd.u64 b, %97, %104;\n"
    "wgmma.mma_async.sync.aligned.m64n192k16.f32.bf16.bf16 {"
      "%0, %1, %2, %3, %4, %5, %6, %7, %8, %9, %10, %11, %12, %13, %14, %15, "
      "%16, %17, %18, %19, %20, %21, %22, %23, %24, %25, %26, %27, %28, %29, %30, %31, "
      "%32, %33, %34, %35, %36, %37, %38, %39, %40, %41, %42, %43, %44, %45, %46, %47, "
      "%48, %49, %50, %51, %52, %53, %54, %55, %56, %57, %58, %59, %60, %61, %62, %63, "
      "%64, %65, %66, %67, %68, %69, %70, %71, %72, %73, %74, %75, %76, %77, %78, %79, "
      "%80, %81, %82, %83, %84, %85, %86, %87, %88, %89, %90, %91, %92, %93, %94, %95"
      "}, a, b, t, 1, 1, 0, 1;\n"
    "wgmma.commit_group.sync.aligned;\nwgmma.wait_group.sync.aligned 1;\n"
    "add.u64 a, %96, 4;\nadd.u64 b, %97, 2*%104;\n"
    "wgmma.mma_async.sync.aligned.m64n192k16.f32.bf16.bf16 {"
      "%0, %1, %2, %3, %4, %5, %6, %7, %8, %9, %10, %11, %12, %13, %14, %15, "
      "%16, %17, %18, %19, %20, %21, %22, %23, %24, %25, %26, %27, %28, %29, %30, %31, "
      "%32, %33, %34, %35, %36, %37, %38, %39, %40, %41, %42, %43, %44, %45, %46, %47, "
      "%48, %49, %50, %51, %52, %53, %54, %55, %56, %57, %58, %59, %60, %61, %62, %63, "
      "%64, %65, %66, %67, %68, %69, %70, %71, %72, %73, %74, %75, %76, %77, %78, %79, "
      "%80, %81, %82, %83, %84, %85, %86, %87, %88, %89, %90, %91, %92, %93, %94, %95"
      "}, a, b, t, 1, 1, 0, 1;\n"
    "setp.ne.u32 q, %99, 0;\n@q mbarrier.arrive.shared::cta.b64 _, [%98];\n@q mbarrier.arrive.shared::cta.b64 _, [%98];\n"
    "add.u64 a, %96, 6;\nadd.u64 b, %97, 3*%104;\n"
    "wgmma.mma_async.sync.aligned.m64n192k16.f32.bf16.bf16 {"
      "%0, %1, %2, %3, %4, %5, %6, %7, %8, %9, %10, %11, %12, %13, %14, %15, "
      "%16, %17, %18, %19, %20, %21, %22, %23, %24, %25, %26, %27, %28, %29, %30, %31, "
      "%32, %33, %34, %35, %36, %37, %38, %39, %40, %41, %42, %43, %44, %45, %46, %47, "
      "%48, %49, %50, %51, %52, %53, %54, %55, %56, %57, %58, %59, %60, %61, %62, %63, "
      "%64, %65, %66, %67, %68, %69, %70, %71, %72, %73, %74, %75, %76, %77, %78, %79, "
      "%80, %81, %82, %83, %84, %85, %86, %87, %88, %89, %90, %91, %92, %93, %94, %95"
      "}, a, b, t, 1, 1, 0, 1;\n"
    "wgmma.commit_group.sync.aligned;\n"
    "}\n"
      :
      "+f"(d[0]), "+f"(d[1]), "+f"(d[2]), "+f"(d[3]), "+f"(d[4]), "+f"(d[5]), "+f"(d[6]), "+f"(d[7]),
      "+f"(d[8]), "+f"(d[9]), "+f"(d[10]), "+f"(d[11]), "+f"(d[12]), "+f"(d[13]), "+f"(d[14]), "+f"(d[15]),
      "+f"(d[16]), "+f"(d[17]), "+f"(d[18]), "+f"(d[19]), "+f"(d[20]), "+f"(d[21]), "+f"(d[22]), "+f"(d[23]),
      "+f"(d[24]), "+f"(d[25]), "+f"(d[26]), "+f"(d[27]), "+f"(d[28]), "+f"(d[29]), "+f"(d[30]), "+f"(d[31]),
      "+f"(d[32]), "+f"(d[33]), "+f"(d[34]), "+f"(d[35]), "+f"(d[36]), "+f"(d[37]), "+f"(d[38]), "+f"(d[39]),
      "+f"(d[40]), "+f"(d[41]), "+f"(d[42]), "+f"(d[43]), "+f"(d[44]), "+f"(d[45]), "+f"(d[46]), "+f"(d[47]),
      "+f"(d[48]), "+f"(d[49]), "+f"(d[50]), "+f"(d[51]), "+f"(d[52]), "+f"(d[53]), "+f"(d[54]), "+f"(d[55]),
      "+f"(d[56]), "+f"(d[57]), "+f"(d[58]), "+f"(d[59]), "+f"(d[60]), "+f"(d[61]), "+f"(d[62]), "+f"(d[63]),
      "+f"(d[64]), "+f"(d[65]), "+f"(d[66]), "+f"(d[67]), "+f"(d[68]), "+f"(d[69]), "+f"(d[70]), "+f"(d[71]),
      "+f"(d[72]), "+f"(d[73]), "+f"(d[74]), "+f"(d[75]), "+f"(d[76]), "+f"(d[77]), "+f"(d[78]), "+f"(d[79]),
      "+f"(d[80]), "+f"(d[81]), "+f"(d[82]), "+f"(d[83]), "+f"(d[84]), "+f"(d[85]), "+f"(d[86]), "+f"(d[87]),
      "+f"(d[88]), "+f"(d[89]), "+f"(d[90]), "+f"(d[91]), "+f"(d[92]), "+f"(d[93]), "+f"(d[94]), "+f"(d[95])
      : "l"(da), "l"(db), "r"(rel), "r"(doR), "r"(fa), "r"(pa), "r"(fb), "r"(pb), "n"(BSTEP), "r"(acc), "r"(rela) : "memory");
    else if constexpr (W == 0 && RC == 2 && RA == 1) asm volatile(
    "{\n.reg .pred p, q, r, t;\n.reg .b64 a, b;\n.reg .u32 n;\nsetp.ne.b32 t, 1, 0;\nsetp.ne.b32 r, %105, 0;\n"
    "wgmma.mma_async.sync.aligned.m64n192k16.f32.bf16.bf16 {"
      "%0, %1, %2, %3, %4, %5, %6, %7, %8, %9, %10, %11, %12, %13, %14, %15, "
      "%16, %17, %18, %19, %20, %21, %22, %23, %24, %25, %26, %27, %28, %29, %30, %31, "
      "%32, %33, %34, %35, %36, %37, %38, %39, %40, %41, %42, %43, %44, %45, %46, %47, "
      "%48, %49, %50, %51, %52, %53, %54, %55, %56, %57, %58, %59, %60, %61, %62, %63, "
      "%64, %65, %66, %67, %68, %69, %70, %71, %72, %73, %74, %75, %76, %77, %78, %79, "
      "%80, %81, %82, %83, %84, %85, %86, %87, %88, %89, %90, %91, %92, %93, %94, %95"
      "}, %96, %97, r, 1, 1, 0, 1;\n"
    "add.u64 a, %96, 2;\nadd.u64 b, %97, %104;\n"
    "wgmma.mma_async.sync.aligned.m64n192k16.f32.bf16.bf16 {"
      "%0, %1, %2, %3, %4, %5, %6, %7, %8, %9, %10, %11, %12, %13, %14, %15, "
      "%16, %17, %18, %19, %20, %21, %22, %23, %24, %25, %26, %27, %28, %29, %30, %31, "
      "%32, %33, %34, %35, %36, %37, %38, %39, %40, %41, %42, %43, %44, %45, %46, %47, "
      "%48, %49, %50, %51, %52, %53, %54, %55, %56, %57, %58, %59, %60, %61, %62, %63, "
      "%64, %65, %66, %67, %68, %69, %70, %71, %72, %73, %74, %75, %76, %77, %78, %79, "
      "%80, %81, %82, %83, %84, %85, %86, %87, %88, %89, %90, %91, %92, %93, %94, %95"
      "}, a, b, t, 1, 1, 0, 1;\n"
    "wgmma.commit_group.sync.aligned;\nwgmma.wait_group.sync.aligned 1;\n"
    "add.u64 a, %96, 4;\nadd.u64 b, %97, 2*%104;\n"
    "wgmma.mma_async.sync.aligned.m64n192k16.f32.bf16.bf16 {"
      "%0, %1, %2, %3, %4, %5, %6, %7, %8, %9, %10, %11, %12, %13, %14, %15, "
      "%16, %17, %18, %19, %20, %21, %22, %23, %24, %25, %26, %27, %28, %29, %30, %31, "
      "%32, %33, %34, %35, %36, %37, %38, %39, %40, %41, %42, %43, %44, %45, %46, %47, "
      "%48, %49, %50, %51, %52, %53, %54, %55, %56, %57, %58, %59, %60, %61, %62, %63, "
      "%64, %65, %66, %67, %68, %69, %70, %71, %72, %73, %74, %75, %76, %77, %78, %79, "
      "%80, %81, %82, %83, %84, %85, %86, %87, %88, %89, %90, %91, %92, %93, %94, %95"
      "}, a, b, t, 1, 1, 0, 1;\n"
    "setp.ne.u32 q, %99, 0;\n@q mbarrier.arrive.shared::cta.b64 _, [%98];\n@q mbarrier.arrive.shared::cta.b64 _, [%98];\n@q mbarrier.arrive.shared::cta.b64 _, [%106];\n@q mbarrier.arrive.shared::cta.b64 _, [%106];\n"
    "add.u64 a, %96, 6;\nadd.u64 b, %97, 3*%104;\n"
    "wgmma.mma_async.sync.aligned.m64n192k16.f32.bf16.bf16 {"
      "%0, %1, %2, %3, %4, %5, %6, %7, %8, %9, %10, %11, %12, %13, %14, %15, "
      "%16, %17, %18, %19, %20, %21, %22, %23, %24, %25, %26, %27, %28, %29, %30, %31, "
      "%32, %33, %34, %35, %36, %37, %38, %39, %40, %41, %42, %43, %44, %45, %46, %47, "
      "%48, %49, %50, %51, %52, %53, %54, %55, %56, %57, %58, %59, %60, %61, %62, %63, "
      "%64, %65, %66, %67, %68, %69, %70, %71, %72, %73, %74, %75, %76, %77, %78, %79, "
      "%80, %81, %82, %83, %84, %85, %86, %87, %88, %89, %90, %91, %92, %93, %94, %95"
      "}, a, b, t, 1, 1, 0, 1;\n"
    "wgmma.commit_group.sync.aligned;\n"
    "}\n"
      :
      "+f"(d[0]), "+f"(d[1]), "+f"(d[2]), "+f"(d[3]), "+f"(d[4]), "+f"(d[5]), "+f"(d[6]), "+f"(d[7]),
      "+f"(d[8]), "+f"(d[9]), "+f"(d[10]), "+f"(d[11]), "+f"(d[12]), "+f"(d[13]), "+f"(d[14]), "+f"(d[15]),
      "+f"(d[16]), "+f"(d[17]), "+f"(d[18]), "+f"(d[19]), "+f"(d[20]), "+f"(d[21]), "+f"(d[22]), "+f"(d[23]),
      "+f"(d[24]), "+f"(d[25]), "+f"(d[26]), "+f"(d[27]), "+f"(d[28]), "+f"(d[29]), "+f"(d[30]), "+f"(d[31]),
      "+f"(d[32]), "+f"(d[33]), "+f"(d[34]), "+f"(d[35]), "+f"(d[36]), "+f"(d[37]), "+f"(d[38]), "+f"(d[39]),
      "+f"(d[40]), "+f"(d[41]), "+f"(d[42]), "+f"(d[43]), "+f"(d[44]), "+f"(d[45]), "+f"(d[46]), "+f"(d[47]),
      "+f"(d[48]), "+f"(d[49]), "+f"(d[50]), "+f"(d[51]), "+f"(d[52]), "+f"(d[53]), "+f"(d[54]), "+f"(d[55]),
      "+f"(d[56]), "+f"(d[57]), "+f"(d[58]), "+f"(d[59]), "+f"(d[60]), "+f"(d[61]), "+f"(d[62]), "+f"(d[63]),
      "+f"(d[64]), "+f"(d[65]), "+f"(d[66]), "+f"(d[67]), "+f"(d[68]), "+f"(d[69]), "+f"(d[70]), "+f"(d[71]),
      "+f"(d[72]), "+f"(d[73]), "+f"(d[74]), "+f"(d[75]), "+f"(d[76]), "+f"(d[77]), "+f"(d[78]), "+f"(d[79]),
      "+f"(d[80]), "+f"(d[81]), "+f"(d[82]), "+f"(d[83]), "+f"(d[84]), "+f"(d[85]), "+f"(d[86]), "+f"(d[87]),
      "+f"(d[88]), "+f"(d[89]), "+f"(d[90]), "+f"(d[91]), "+f"(d[92]), "+f"(d[93]), "+f"(d[94]), "+f"(d[95])
      : "l"(da), "l"(db), "r"(rel), "r"(doR), "r"(fa), "r"(pa), "r"(fb), "r"(pb), "n"(BSTEP), "r"(acc), "r"(rela) : "memory");
    else if constexpr (W == 1 && RC == 2 && RA == 1) asm volatile(
    "{\n.reg .pred p, q, r, t;\n.reg .b64 a, b;\n.reg .u32 n;\nsetp.ne.b32 t, 1, 0;\nsetp.ne.b32 r, %105, 0;\n"
    "wgmma.mma_async.sync.aligned.m64n192k16.f32.bf16.bf16 {"
      "%0, %1, %2, %3, %4, %5, %6, %7, %8, %9, %10, %11, %12, %13, %14, %15, "
      "%16, %17, %18, %19, %20, %21, %22, %23, %24, %25, %26, %27, %28, %29, %30, %31, "
      "%32, %33, %34, %35, %36, %37, %38, %39, %40, %41, %42, %43, %44, %45, %46, %47, "
      "%48, %49, %50, %51, %52, %53, %54, %55, %56, %57, %58, %59, %60, %61, %62, %63, "
      "%64, %65, %66, %67, %68, %69, %70, %71, %72, %73, %74, %75, %76, %77, %78, %79, "
      "%80, %81, %82, %83, %84, %85, %86, %87, %88, %89, %90, %91, %92, %93, %94, %95"
      "}, %96, %97, r, 1, 1, 0, 1;\n"
    "add.u64 a, %96, 2;\nadd.u64 b, %97, %104;\n"
    "wgmma.mma_async.sync.aligned.m64n192k16.f32.bf16.bf16 {"
      "%0, %1, %2, %3, %4, %5, %6, %7, %8, %9, %10, %11, %12, %13, %14, %15, "
      "%16, %17, %18, %19, %20, %21, %22, %23, %24, %25, %26, %27, %28, %29, %30, %31, "
      "%32, %33, %34, %35, %36, %37, %38, %39, %40, %41, %42, %43, %44, %45, %46, %47, "
      "%48, %49, %50, %51, %52, %53, %54, %55, %56, %57, %58, %59, %60, %61, %62, %63, "
      "%64, %65, %66, %67, %68, %69, %70, %71, %72, %73, %74, %75, %76, %77, %78, %79, "
      "%80, %81, %82, %83, %84, %85, %86, %87, %88, %89, %90, %91, %92, %93, %94, %95"
      "}, a, b, t, 1, 1, 0, 1;\n"
    "wgmma.commit_group.sync.aligned;\nwgmma.wait_group.sync.aligned 1;\n"
    "add.u64 a, %96, 4;\nadd.u64 b, %97, 2*%104;\n"
    "wgmma.mma_async.sync.aligned.m64n192k16.f32.bf16.bf16 {"
      "%0, %1, %2, %3, %4, %5, %6, %7, %8, %9, %10, %11, %12, %13, %14, %15, "
      "%16, %17, %18, %19, %20, %21, %22, %23, %24, %25, %26, %27, %28, %29, %30, %31, "
      "%32, %33, %34, %35, %36, %37, %38, %39, %40, %41, %42, %43, %44, %45, %46, %47, "
      "%48, %49, %50, %51, %52, %53, %54, %55, %56, %57, %58, %59, %60, %61, %62, %63, "
      "%64, %65, %66, %67, %68, %69, %70, %71, %72, %73, %74, %75, %76, %77, %78, %79, "
      "%80, %81, %82, %83, %84, %85, %86, %87, %88, %89, %90, %91, %92, %93, %94, %95"
      "}, a, b, t, 1, 1, 0, 1;\n"
    "setp.ne.u32 q, %99, 0;\n@q mbarrier.arrive.shared::cta.b64 _, [%98];\n@q mbarrier.arrive.shared::cta.b64 _, [%98];\n@q mbarrier.arrive.shared::cta.b64 _, [%106];\n@q mbarrier.arrive.shared::cta.b64 _, [%106];\n"
    "mbarrier.test_wait.parity.shared::cta.b64 p, [%102], %103;\n"
    "add.u64 a, %96, 6;\nadd.u64 b, %97, 3*%104;\n"
    "wgmma.mma_async.sync.aligned.m64n192k16.f32.bf16.bf16 {"
      "%0, %1, %2, %3, %4, %5, %6, %7, %8, %9, %10, %11, %12, %13, %14, %15, "
      "%16, %17, %18, %19, %20, %21, %22, %23, %24, %25, %26, %27, %28, %29, %30, %31, "
      "%32, %33, %34, %35, %36, %37, %38, %39, %40, %41, %42, %43, %44, %45, %46, %47, "
      "%48, %49, %50, %51, %52, %53, %54, %55, %56, %57, %58, %59, %60, %61, %62, %63, "
      "%64, %65, %66, %67, %68, %69, %70, %71, %72, %73, %74, %75, %76, %77, %78, %79, "
      "%80, %81, %82, %83, %84, %85, %86, %87, %88, %89, %90, %91, %92, %93, %94, %95"
      "}, a, b, t, 1, 1, 0, 1;\n"
    "wgmma.commit_group.sync.aligned;\n"
    "@p bra.uni DN;\nmov.u32 n, 0;\nWT: mbarrier.try_wait.parity.shared::cta.b64 p, [%102], %103;\n@p bra.uni DN;\nadd.u32 n, n, 1;\nsetp.lt.u32 p, n, 0x100000;\n@p bra.uni WT;\nDN:\n"
    "}\n"
      :
      "+f"(d[0]), "+f"(d[1]), "+f"(d[2]), "+f"(d[3]), "+f"(d[4]), "+f"(d[5]), "+f"(d[6]), "+f"(d[7]),
      "+f"(d[8]), "+f"(d[9]), "+f"(d[10]), "+f"(d[11]), "+f"(d[12]), "+f"(d[13]), "+f"(d[14]), "+f"(d[15]),
      "+f"(d[16]), "+f"(d[17]), "+f"(d[18]), "+f"(d[19]), "+f"(d[20]), "+f"(d[21]), "+f"(d[22]), "+f"(d[23]),
      "+f"(d[24]), "+f"(d[25]), "+f"(d[26]), "+f"(d[27]), "+f"(d[28]), "+f"(d[29]), "+f"(d[30]), "+f"(d[31]),
      "+f"(d[32]), "+f"(d[33]), "+f"(d[34]), "+f"(d[35]), "+f"(d[36]), "+f"(d[37]), "+f"(d[38]), "+f"(d[39]),
      "+f"(d[40]), "+f"(d[41]), "+f"(d[42]), "+f"(d[43]), "+f"(d[44]), "+f"(d[45]), "+f"(d[46]), "+f"(d[47]),
      "+f"(d[48]), "+f"(d[49]), "+f"(d[50]), "+f"(d[51]), "+f"(d[52]), "+f"(d[53]), "+f"(d[54]), "+f"(d[55]),
      "+f"(d[56]), "+f"(d[57]), "+f"(d[58]), "+f"(d[59]), "+f"(d[60]), "+f"(d[61]), "+f"(d[62]), "+f"(d[63]),
      "+f"(d[64]), "+f"(d[65]), "+f"(d[66]), "+f"(d[67]), "+f"(d[68]), "+f"(d[69]), "+f"(d[70]), "+f"(d[71]),
      "+f"(d[72]), "+f"(d[73]), "+f"(d[74]), "+f"(d[75]), "+f"(d[76]), "+f"(d[77]), "+f"(d[78]), "+f"(d[79]),
      "+f"(d[80]), "+f"(d[81]), "+f"(d[82]), "+f"(d[83]), "+f"(d[84]), "+f"(d[85]), "+f"(d[86]), "+f"(d[87]),
      "+f"(d[88]), "+f"(d[89]), "+f"(d[90]), "+f"(d[91]), "+f"(d[92]), "+f"(d[93]), "+f"(d[94]), "+f"(d[95])
      : "l"(da), "l"(db), "r"(rel), "r"(doR), "r"(fa), "r"(pa), "r"(fb), "r"(pb), "n"(BSTEP), "r"(acc), "r"(rela) : "memory");
    else if constexpr (W == 2 && RC == 2 && RA == 0) asm volatile(
    "{\n.reg .pred p, q, r, t;\n.reg .b64 a, b;\n.reg .u32 n;\nsetp.ne.b32 t, 1, 0;\nsetp.ne.b32 r, %105, 0;\n"
    "wgmma.mma_async.sync.aligned.m64n192k16.f32.bf16.bf16 {"
      "%0, %1, %2, %3, %4, %5, %6, %7, %8, %9, %10, %11, %12, %13, %14, %15, "
      "%16, %17, %18, %19, %20, %21, %22, %23, %24, %25, %26, %27, %28, %29, %30, %31, "
      "%32, %33, %34, %35, %36, %37, %38, %39, %40, %41, %42, %43, %44, %45, %46, %47, "
      "%48, %49, %50, %51, %52, %53, %54, %55, %56, %57, %58, %59, %60, %61, %62, %63, "
      "%64, %65, %66, %67, %68, %69, %70, %71, %72, %73, %74, %75, %76, %77, %78, %79, "
      "%80, %81, %82, %83, %84, %85, %86, %87, %88, %89, %90, %91, %92, %93, %94, %95"
      "}, %96, %97, r, 1, 1, 0, 1;\n"
    "add.u64 a, %96, 2;\nadd.u64 b, %97, %104;\n"
    "wgmma.mma_async.sync.aligned.m64n192k16.f32.bf16.bf16 {"
      "%0, %1, %2, %3, %4, %5, %6, %7, %8, %9, %10, %11, %12, %13, %14, %15, "
      "%16, %17, %18, %19, %20, %21, %22, %23, %24, %25, %26, %27, %28, %29, %30, %31, "
      "%32, %33, %34, %35, %36, %37, %38, %39, %40, %41, %42, %43, %44, %45, %46, %47, "
      "%48, %49, %50, %51, %52, %53, %54, %55, %56, %57, %58, %59, %60, %61, %62, %63, "
      "%64, %65, %66, %67, %68, %69, %70, %71, %72, %73, %74, %75, %76, %77, %78, %79, "
      "%80, %81, %82, %83, %84, %85, %86, %87, %88, %89, %90, %91, %92, %93, %94, %95"
      "}, a, b, t, 1, 1, 0, 1;\n"
    "wgmma.commit_group.sync.aligned;\nwgmma.wait_group.sync.aligned 1;\n"
    "add.u64 a, %96, 4;\nadd.u64 b, %97, 2*%104;\n"
    "wgmma.mma_async.sync.aligned.m64n192k16.f32.bf16.bf16 {"
      "%0, %1, %2, %3, %4, %5, %6, %7, %8, %9, %10, %11, %12, %13, %14, %15, "
      "%16, %17, %18, %19, %20, %21, %22, %23, %24, %25, %26, %27, %28, %29, %30, %31, "
      "%32, %33, %34, %35, %36, %37, %38, %39, %40, %41, %42, %43, %44, %45, %46, %47, "
      "%48, %49, %50, %51, %52, %53, %54, %55, %56, %57, %58, %59, %60, %61, %62, %63, "
      "%64, %65, %66, %67, %68, %69, %70, %71, %72, %73, %74, %75, %76, %77, %78, %79, "
      "%80, %81, %82, %83, %84, %85, %86, %87, %88, %89, %90, %91, %92, %93, %94, %95"
      "}, a, b, t, 1, 1, 0, 1;\n"
    "setp.ne.u32 q, %99, 0;\n@q mbarrier.arrive.shared::cta.b64 _, [%98];\n@q mbarrier.arrive.shared::cta.b64 _, [%98];\n"
    "mbarrier.test_wait.parity.shared::cta.b64 p, [%102], %103;\n"
    "mbarrier.test_wait.parity.shared::cta.b64 r, [%100], %101;\nand.pred p, p, r;\n"
    "add.u64 a, %96, 6;\nadd.u64 b, %97, 3*%104;\n"
    "wgmma.mma_async.sync.aligned.m64n192k16.f32.bf16.bf16 {"
      "%0, %1, %2, %3, %4, %5, %6, %7, %8, %9, %10, %11, %12, %13, %14, %15, "
      "%16, %17, %18, %19, %20, %21, %22, %23, %24, %25, %26, %27, %28, %29, %30, %31, "
      "%32, %33, %34, %35, %36, %37, %38, %39, %40, %41, %42, %43, %44, %45, %46, %47, "
      "%48, %49, %50, %51, %52, %53, %54, %55, %56, %57, %58, %59, %60, %61, %62, %63, "
      "%64, %65, %66, %67, %68, %69, %70, %71, %72, %73, %74, %75, %76, %77, %78, %79, "
      "%80, %81, %82, %83, %84, %85, %86, %87, %88, %89, %90, %91, %92, %93, %94, %95"
      "}, a, b, t, 1, 1, 0, 1;\n"
    "wgmma.commit_group.sync.aligned;\n"
    "@p bra.uni DN;\nmov.u32 n, 0;\nWT: mbarrier.try_wait.parity.shared::cta.b64 p, [%102], %103;\nmbarrier.try_wait.parity.shared::cta.b64 r, [%100], %101;\nand.pred p, p, r;\n@p bra.uni DN;\nadd.u32 n, n, 1;\nsetp.lt.u32 p, n, 0x100000;\n@p bra.uni WT;\nDN:\n"
    "}\n"
      :
      "+f"(d[0]), "+f"(d[1]), "+f"(d[2]), "+f"(d[3]), "+f"(d[4]), "+f"(d[5]), "+f"(d[6]), "+f"(d[7]),
      "+f"(d[8]), "+f"(d[9]), "+f"(d[10]), "+f"(d[11]), "+f"(d[12]), "+f"(d[13]), "+f"(d[14]), "+f"(d[15]),
      "+f"(d[16]), "+f"(d[17]), "+f"(d[18]), "+f"(d[19]), "+f"(d[20]), "+f"(d[21]), "+f"(d[22]), "+f"(d[23]),
      "+f"(d[24]), "+f"(d[25]), "+f"(d[26]), "+f"(d[27]), "+f"(d[28]), "+f"(d[29]), "+f"(d[30]), "+f"(d[31]),
      "+f"(d[32]), "+f"(d[33]), "+f"(d[34]), "+f"(d[35]), "+f"(d[36]), "+f"(d[37]), "+f"(d[38]), "+f"(d[39]),
      "+f"(d[40]), "+f"(d[41]), "+f"(d[42]), "+f"(d[43]), "+f"(d[44]), "+f"(d[45]), "+f"(d[46]), "+f"(d[47]),
      "+f"(d[48]), "+f"(d[49]), "+f"(d[50]), "+f"(d[51]), "+f"(d[52]), "+f"(d[53]), "+f"(d[54]), "+f"(d[55]),
      "+f"(d[56]), "+f"(d[57]), "+f"(d[58]), "+f"(d[59]), "+f"(d[60]), "+f"(d[61]), "+f"(d[62]), "+f"(d[63]),
      "+f"(d[64]), "+f"(d[65]), "+f"(d[66]), "+f"(d[67]), "+f"(d[68]), "+f"(d[69]), "+f"(d[70]), "+f"(d[71]),
      "+f"(d[72]), "+f"(d[73]), "+f"(d[74]), "+f"(d[75]), "+f"(d[76]), "+f"(d[77]), "+f"(d[78]), "+f"(d[79]),
      "+f"(d[80]), "+f"(d[81]), "+f"(d[82]), "+f"(d[83]), "+f"(d[84]), "+f"(d[85]), "+f"(d[86]), "+f"(d[87]),
      "+f"(d[88]), "+f"(d[89]), "+f"(d[90]), "+f"(d[91]), "+f"(d[92]), "+f"(d[93]), "+f"(d[94]), "+f"(d[95])
      : "l"(da), "l"(db), "r"(rel), "r"(doR), "r"(fa), "r"(pa), "r"(fb), "r"(pb), "n"(BSTEP), "r"(acc), "r"(rela) : "memory");
    else if constexpr (W == 2 && RC == 2 && RA == 1) asm volatile(
    "{\n.reg .pred p, q, r, t;\n.reg .b64 a, b;\n.reg .u32 n;\nsetp.ne.b32 t, 1, 0;\nsetp.ne.b32 r, %105, 0;\n"
    "wgmma.mma_async.sync.aligned.m64n192k16.f32.bf16.bf16 {"
      "%0, %1, %2, %3, %4, %5, %6, %7, %8, %9, %10, %11, %12, %13, %14, %15, "
      "%16, %17, %18, %19, %20, %21, %22, %23, %24, %25, %26, %27, %28, %29, %30, %31, "
      "%32, %33, %34, %35, %36, %37, %38, %39, %40, %41, %42, %43, %44, %45, %46, %47, "
      "%48, %49, %50, %51, %52, %53, %54, %55, %56, %57, %58, %59, %60, %61, %62, %63, "
      "%64, %65, %66, %67, %68, %69, %70, %71, %72, %73, %74, %75, %76, %77, %78, %79, "
      "%80, %81, %82, %83, %84, %85, %86, %87, %88, %89, %90, %91, %92, %93, %94, %95"
      "}, %96, %97, r, 1, 1, 0, 1;\n"
    "add.u64 a, %96, 2;\nadd.u64 b, %97, %104;\n"
    "wgmma.mma_async.sync.aligned.m64n192k16.f32.bf16.bf16 {"
      "%0, %1, %2, %3, %4, %5, %6, %7, %8, %9, %10, %11, %12, %13, %14, %15, "
      "%16, %17, %18, %19, %20, %21, %22, %23, %24, %25, %26, %27, %28, %29, %30, %31, "
      "%32, %33, %34, %35, %36, %37, %38, %39, %40, %41, %42, %43, %44, %45, %46, %47, "
      "%48, %49, %50, %51, %52, %53, %54, %55, %56, %57, %58, %59, %60, %61, %62, %63, "
      "%64, %65, %66, %67, %68, %69, %70, %71, %72, %73, %74, %75, %76, %77, %78, %79, "
      "%80, %81, %82, %83, %84, %85, %86, %87, %88, %89, %90, %91, %92, %93, %94, %95"
      "}, a, b, t, 1, 1, 0, 1;\n"
    "wgmma.commit_group.sync.aligned;\nwgmma.wait_group.sync.aligned 1;\n"
    "add.u64 a, %96, 4;\nadd.u64 b, %97, 2*%104;\n"
    "wgmma.mma_async.sync.aligned.m64n192k16.f32.bf16.bf16 {"
      "%0, %1, %2, %3, %4, %5, %6, %7, %8, %9, %10, %11, %12, %13, %14, %15, "
      "%16, %17, %18, %19, %20, %21, %22, %23, %24, %25, %26, %27, %28, %29, %30, %31, "
      "%32, %33, %34, %35, %36, %37, %38, %39, %40, %41, %42, %43, %44, %45, %46, %47, "
      "%48, %49, %50, %51, %52, %53, %54, %55, %56, %57, %58, %59, %60, %61, %62, %63, "
      "%64, %65, %66, %67, %68, %69, %70, %71, %72, %73, %74, %75, %76, %77, %78, %79, "
      "%80, %81, %82, %83, %84, %85, %86, %87, %88, %89, %90, %91, %92, %93, %94, %95"
      "}, a, b, t, 1, 1, 0, 1;\n"
    "setp.ne.u32 q, %99, 0;\n@q mbarrier.arrive.shared::cta.b64 _, [%98];\n@q mbarrier.arrive.shared::cta.b64 _, [%98];\n@q mbarrier.arrive.shared::cta.b64 _, [%106];\n@q mbarrier.arrive.shared::cta.b64 _, [%106];\n"
    "mbarrier.test_wait.parity.shared::cta.b64 p, [%102], %103;\n"
    "mbarrier.test_wait.parity.shared::cta.b64 r, [%100], %101;\nand.pred p, p, r;\n"
    "add.u64 a, %96, 6;\nadd.u64 b, %97, 3*%104;\n"
    "wgmma.mma_async.sync.aligned.m64n192k16.f32.bf16.bf16 {"
      "%0, %1, %2, %3, %4, %5, %6, %7, %8, %9, %10, %11, %12, %13, %14, %15, "
      "%16, %17, %18, %19, %20, %21, %22, %23, %24, %25, %26, %27, %28, %29, %30, %31, "
      "%32, %33, %34, %35, %36, %37, %38, %39, %40, %41, %42, %43, %44, %45, %46, %47, "
      "%48, %49, %50, %51, %52, %53, %54, %55, %56, %57, %58, %59, %60, %61, %62, %63, "
      "%64, %65, %66, %67, %68, %69, %70, %71, %72, %73, %74, %75, %76, %77, %78, %79, "
      "%80, %81, %82, %83, %84, %85, %86, %87, %88, %89, %90, %91, %92, %93, %94, %95"
      "}, a, b, t, 1, 1, 0, 1;\n"
    "wgmma.commit_group.sync.aligned;\n"
    "@p bra.uni DN;\nmov.u32 n, 0;\nWT: mbarrier.try_wait.parity.shared::cta.b64 p, [%102], %103;\nmbarrier.try_wait.parity.shared::cta.b64 r, [%100], %101;\nand.pred p, p, r;\n@p bra.uni DN;\nadd.u32 n, n, 1;\nsetp.lt.u32 p, n, 0x100000;\n@p bra.uni WT;\nDN:\n"
    "}\n"
      :
      "+f"(d[0]), "+f"(d[1]), "+f"(d[2]), "+f"(d[3]), "+f"(d[4]), "+f"(d[5]), "+f"(d[6]), "+f"(d[7]),
      "+f"(d[8]), "+f"(d[9]), "+f"(d[10]), "+f"(d[11]), "+f"(d[12]), "+f"(d[13]), "+f"(d[14]), "+f"(d[15]),
      "+f"(d[16]), "+f"(d[17]), "+f"(d[18]), "+f"(d[19]), "+f"(d[20]), "+f"(d[21]), "+f"(d[22]), "+f"(d[23]),
      "+f"(d[24]), "+f"(d[25]), "+f"(d[26]), "+f"(d[27]), "+f"(d[28]), "+f"(d[29]), "+f"(d[30]), "+f"(d[31]),
      "+f"(d[32]), "+f"(d[33]), "+f"(d[34]), "+f"(d[35]), "+f"(d[36]), "+f"(d[37]), "+f"(d[38]), "+f"(d[39]),
      "+f"(d[40]), "+f"(d[41]), "+f"(d[42]), "+f"(d[43]), "+f"(d[44]), "+f"(d[45]), "+f"(d[46]), "+f"(d[47]),
      "+f"(d[48]), "+f"(d[49]), "+f"(d[50]), "+f"(d[51]), "+f"(d[52]), "+f"(d[53]), "+f"(d[54]), "+f"(d[55]),
      "+f"(d[56]), "+f"(d[57]), "+f"(d[58]), "+f"(d[59]), "+f"(d[60]), "+f"(d[61]), "+f"(d[62]), "+f"(d[63]),
      "+f"(d[64]), "+f"(d[65]), "+f"(d[66]), "+f"(d[67]), "+f"(d[68]), "+f"(d[69]), "+f"(d[70]), "+f"(d[71]),
      "+f"(d[72]), "+f"(d[73]), "+f"(d[74]), "+f"(d[75]), "+f"(d[76]), "+f"(d[77]), "+f"(d[78]), "+f"(d[79]),
      "+f"(d[80]), "+f"(d[81]), "+f"(d[82]), "+f"(d[83]), "+f"(d[84]), "+f"(d[85]), "+f"(d[86]), "+f"(d[87]),
      "+f"(d[88]), "+f"(d[89]), "+f"(d[90]), "+f"(d[91]), "+f"(d[92]), "+f"(d[93]), "+f"(d[94]), "+f"(d[95])
      : "l"(da), "l"(db), "r"(rel), "r"(doR), "r"(fa), "r"(pa), "r"(fb), "r"(pb), "n"(BSTEP), "r"(acc), "r"(rela) : "memory");
    else static_assert(W < 0, "variant not generated");
  }
};

#define NPRE 2
#define KV_T0 4000
#define KV2T 2000
#define XSD 400
#define CSD 600
#define ZW 300
#define TP_T 5000
#define PF2_D 200
#define PF_D 600
#define LKI 14
#define LEAD 4
#define YSA -1
#define YSB -1
#define HD 300
#define YD 600
#define HP0 3500
#define HPD 450
#define NSLEEP 100
#define MAP 4
#define EARLY 0

namespace {

constexpr int kS = 2048, kD = 640, kF = 1536;
constexpr int A_SLOT = 8192, B_SLOT = 24576, W_SLOT = 20480;
constexpr int OFF_A = 0;
constexpr int OFF_B = OFF_A + 10 * A_SLOT;
constexpr int XB_PL = 2112;
constexpr int CV_KE = 4224, CV_KO = CV_KE + 4160;
constexpr int CV_SZ = CV_KO + 4160;
constexpr int OFF_CV = OFF_B + 5 * B_SLOT;
constexpr int OFF_CS = OFF_CV + 2 * CV_SZ;
constexpr int OFF_XS = OFF_CS + 1536;
constexpr int OFF_BAR = OFF_XS + 512;
constexpr int SMEM_BYTES = OFF_BAR + 512;
static_assert(SMEM_BYTES <= 232448, "smem");
constexpr int OFF_RT = OFF_CS + 768;
constexpr int BAR_AF = OFF_BAR, BAR_BF = OFF_BAR + 8 * 10, BAR_WF = OFF_BAR + 8 * 15, BAR_ST = OFF_BAR + 8 * 21, BAR_XF = OFF_BAR + 8 * 23;
constexpr int BAR_ZP = OFF_BAR + 8 * 25, BAR_DUMMY = OFF_BAR + 8 * 27, BAR_PART = OFF_BAR + 8 * 28, BAR_WO = OFF_BAR + 8 * 29;
constexpr int BAR_YT = OFF_BAR + 8 * 30, BAR_KV2 = OFF_BAR + 8 * 31, BAR_XS = OFF_BAR + 8 * 32, BAR_HOLD = OFF_BAR + 8 * 33, BAR_ZG = OFF_BAR + 8 * 34;
constexpr int OFF_TAG = OFF_BAR + 8 * 35;
constexpr int BAR_HV = OFF_BAR + 8 * 36;
constexpr int BAR_HR = BAR_HV + 64, BAR_YS = OFF_BAR + 8 * 26;
constexpr int BAR_XL = OFF_CS - 16;
constexpr int BAR_AE = OFF_BAR + 8 * 45, BAR_BE = OFF_BAR + 8 * 53, BAR_WE = OFF_BAR + 8 * 58;
constexpr int NB_WG = 1, NB_G1 = 3, NB_WO = 4, NB_CD = 5, NB_Z = 6, NB_C = 7, NB_KU = 8, NB_SV = 9, NB_PC = 11, NB_KF = 12, NB_G1D = 13, NB_KU2 = 14, NB_KL = 15;

#define NB_SV2(h) ((h) ? NB_KU2 : NB_KU)

constexpr int CNT_KV = 0, CNT_WO = 4, CNT_Z = 8;
struct Scratch {
  uint8_t kvx[kD * 4096];
  uint8_t z2[4 * 32 * 24576];
  uint8_t h[32 * 12 * 8192];
  uint8_t wo[4 * 12 * 20480];
  uint8_t y[kD * 4096];
  uint4 zstat[32 * 128];
  uint2 xstat[kS];
  uint32_t colsum[kF];
  uint32_t cnt[32];
  uint32_t hflag[32 * 32];
  uint32_t epoch[136];

};
__device__ __align__(1024) Scratch g_scr;
#define TSP
#define TSA
#define TR(i)
#define STAMP(i)
#define STAMPE(i)
#define STAMP2(i)
#define STAMPW(i)

struct Params {
  Scratch* scr;
  int by_smid;
  const __nv_bfloat16 *x, *k, *v, *shift, *ssmk, *ssmD, *wsp, *bsp, *wout;
  __nv_bfloat16* out;
  CUtensorMap tmX, tmW, tmWsp, tmY, tmKV;
  uint16_t job[132];
};

__device__ __forceinline__ uint64_t mkdesc(uint32_t addr, uint32_t lbo, uint32_t sbo, uint32_t swz) {
  return (uint64_t)((addr & 0x3FFFF) >> 4) | ((uint64_t)(lbo >> 4) << 16) | ((uint64_t)(sbo >> 4) << 32) | ((uint64_t)swz << 62);
}
#define WG_FENCE() asm volatile("wgmma.fence.sync.aligned;" ::: "memory")
#define WG_COMMIT() asm volatile("wgmma.commit_group.sync.aligned;" ::: "memory")
#define WG_WAIT(n) asm volatile("wgmma.wait_group.sync.aligned %0;" ::"n"(n) : "memory")
template <int N> __device__ __forceinline__ void acc_fence(float* d) {
#pragma unroll
  for (int i = 0; i < N; i++) asm volatile("" : "+f"(d[i])::"memory");
}
__device__ __forceinline__ void mbar_init(uint32_t bar, int cnt) { asm volatile("mbarrier.init.shared::cta.b64 [%0], %1;" ::"r"(bar), "r"(cnt) : "memory"); }
__device__ __forceinline__ void mbar_expect(uint32_t bar, uint32_t bytes) { asm volatile("mbarrier.arrive.expect_tx.shared::cta.b64 _, [%0], %1;" ::"r"(bar), "r"(bytes) : "memory"); }
__device__ __forceinline__ void mbar_arrive(uint32_t bar) { asm volatile("mbarrier.arrive.shared::cta.b64 _, [%0];" ::"r"(bar) : "memory"); }
__device__ __forceinline__ void mbar_arrive_if(uint32_t bar, bool c) {
  asm volatile("{\n.reg .pred p;\nsetp.ne.u32 p, %1, 0;\n@p mbarrier.arrive.shared::cta.b64 _, [%0];\n}\n" ::"r"(bar), "r"((uint32_t)c) : "memory");
}
__device__ __forceinline__ bool mbar_try(uint32_t bar, uint32_t parity) {
  uint32_t ok;
  asm volatile("{\n.reg .pred p;\nmbarrier.try_wait.parity.shared::cta.b64 p, [%1], %2;\nselp.u32 %0, 1, 0, p;\n}\n" : "=r"(ok) : "r"(bar), "r"(parity) : "memory");
  return ok;
}
__device__ __forceinline__ void die() { asm volatile("st.volatile.global.u32 [%0], %1;" ::"l"(0ull), "r"(0) : "memory"); }
template <bool G = false> __device__ __forceinline__ void spin_guard(uint32_t& n, uint32_t = 0) { if (G && ++n == (1u << 20)) die(); }
template <bool G = false> __device__ __forceinline__ void mbar_wait(uint32_t bar, uint32_t parity) {
  uint32_t t0 = 0;
#pragma unroll 1
  while (!mbar_try(bar, parity)) spin_guard<G>(t0, bar);
}
__device__ __forceinline__ void mbar_wait2(uint32_t b0, uint32_t p0, uint32_t b1, uint32_t p1) { mbar_wait(b0, p0); mbar_wait(b1, p1); }
__device__ __forceinline__ int tid_now() { int v; asm volatile("mov.u32 %0, %%tid.x;" : "=r"(v)); return v & 127; }
__device__ __forceinline__ bool elect_one() {
  uint32_t p;
  asm volatile("{\n.reg .pred P;\nelect.sync _|P, 0xffffffff;\nselp.u32 %0, 1, 0, P;\n}\n" : "=r"(p));
  return p;
}
__device__ __forceinline__ void bar_sync(int id, int n) { asm volatile("bar.sync %0, %1;" ::"r"(id), "r"(n) : "memory"); }
__device__ __forceinline__ void bar_arrive(int id, int n) { asm volatile("bar.arrive %0, %1;" ::"r"(id), "r"(n) : "memory"); }
__device__ __forceinline__ void fence_async_smem() { asm volatile("fence.proxy.async.shared::cta;" ::: "memory"); }
__device__ __forceinline__ void bulk_g2s(uint32_t dst, const void* src, uint32_t bytes, uint32_t bar) {
  asm volatile("cp.async.bulk.shared::cluster.global.mbarrier::complete_tx::bytes [%0], [%1], %2, [%3];" ::"r"(dst), "l"(src), "r"(bytes), "r"(bar) : "memory");
}
__device__ __forceinline__ void bulk_s2g(void* dst, uint32_t src, uint32_t bytes) {
  asm volatile("cp.async.bulk.global.shared::cta.bulk_group [%0], [%1], %2;" ::"l"(dst), "r"(src), "r"(bytes) : "memory");
}
__device__ __forceinline__ void tma2d(uint32_t dst, const CUtensorMap* m, int c0, int c1, uint32_t bar) {
  asm volatile("cp.async.bulk.tensor.2d.shared::cluster.global.mbarrier::complete_tx::bytes [%0], [%1, {%3, %4}], [%2];" ::"r"(dst), "l"(m), "r"(bar), "r"(c0), "r"(c1) : "memory");
}
__device__ __forceinline__ void tma3d(uint32_t dst, const CUtensorMap* m, int c0, int c1, int c2, uint32_t bar) {
  asm volatile("cp.async.bulk.tensor.3d.shared::cluster.global.mbarrier::complete_tx::bytes [%0], [%1, {%3, %4, %5}], [%2];" ::"r"(dst), "l"(m), "r"(bar), "r"(c0), "r"(c1), "r"(c2) : "memory");
}
__device__ __forceinline__ uint4 ld_ll4(const void* p) {
  uint64_t a, b;
  asm volatile("ld.relaxed.gpu.global.v2.u64 {%0,%1}, [%2];" : "=l"(a), "=l"(b) : "l"(p) : "memory");
  return make_uint4((uint32_t)a, (uint32_t)(a >> 32), (uint32_t)b, (uint32_t)(b >> 32));
}
__device__ __forceinline__ void st_ll4(void* p, uint32_t a, uint32_t b, uint32_t c, uint32_t d) {
  asm volatile("st.relaxed.gpu.global.v2.u64 [%0], {%1,%2};" ::"l"(p), "l"(a | ((uint64_t)b << 32)), "l"(c | ((uint64_t)d << 32)) : "memory");
}
__device__ __forceinline__ void st_ll2(void* p, uint32_t a, uint32_t b) { asm volatile("st.relaxed.gpu.global.u64 [%0], %1;" ::"l"(p), "l"(a | ((uint64_t)b << 32)) : "memory"); }
__device__ __forceinline__ void wgmma_colsum(float* d, uint64_t da, uint64_t db) {
  asm volatile("{\n.reg .pred p;\nsetp.ne.b32 p, 1, 0;\nwgmma.mma_async.sync.aligned.m64n8k16.f32.bf16.bf16 {%0, %1, %2, %3}, %4, %5, p, 1, 1, 1, 0;\n}\n"
               : "+f"(d[0]), "+f"(d[1]), "+f"(d[2]), "+f"(d[3]) : "l"(da), "l"(db));
}
__device__ __forceinline__ void prefetch_l2(const void* p) { asm volatile("prefetch.global.L2 [%0];" ::"l"(p)); }
template <bool SLEEP = true> __device__ __forceinline__ void pace(uint32_t& t, uint32_t dt) {
  t += dt;
  while ((int32_t)((uint32_t)clock() - t) < 0) { if (SLEEP) __nanosleep(NSLEEP); }
}
__device__ __forceinline__ void red_release(uint32_t* p) { asm volatile("red.release.gpu.global.add.u32 [%0], 1;" ::"l"(p) : "memory"); }
__device__ __forceinline__ uint4 ldg4(const void* p) { uint4 v; asm volatile("ld.global.v4.u32 {%0,%1,%2,%3}, [%4];" : "=r"(v.x), "=r"(v.y), "=r"(v.z), "=r"(v.w) : "l"(p) : "memory"); return v; }
__device__ __forceinline__ uint32_t ldg1(const void* p) { uint32_t v; asm volatile("ld.global.u32 %0, [%1];" : "=r"(v) : "l"(p) : "memory"); return v; }
__device__ __forceinline__ void stg4_if(void* p, uint32_t a, uint32_t b, uint32_t c, uint32_t d, bool on) {
  asm volatile("{\n.reg .pred p;\nsetp.ne.u32 p, %5, 0;\n@p st.global.v4.u32 [%0], {%1,%2,%3,%4};\n}\n" ::"l"(p), "r"(a), "r"(b), "r"(c), "r"(d), "r"((uint32_t)on) : "memory");
}
template <int OFF> __device__ __forceinline__ uint32_t lds32(uint32_t a) { uint32_t v; asm volatile("ld.shared.u32 %0, [%1+%2];" : "=r"(v) : "r"(a), "n"(OFF)); return v; }
__device__ __forceinline__ uint4 lds128(uint32_t a) { uint4 v; asm volatile("ld.shared.v4.u32 {%0,%1,%2,%3}, [%4];" : "=r"(v.x), "=r"(v.y), "=r"(v.z), "=r"(v.w) : "r"(a) : "memory"); return v; }
__device__ __forceinline__ float2 lds64f(uint32_t a) { float2 v; asm volatile("ld.shared.v2.f32 {%0,%1}, [%2];" : "=f"(v.x), "=f"(v.y) : "r"(a) : "memory"); return v; }
__device__ __forceinline__ void sts64f(uint32_t a, float x, float y) { asm volatile("st.shared.v2.f32 [%0], {%1,%2};" ::"r"(a), "f"(x), "f"(y) : "memory"); }
__device__ __forceinline__ void sts32(uint32_t a, uint32_t x) { asm volatile("st.shared.u32 [%0], %1;" ::"r"(a), "r"(x) : "memory"); }
__device__ __forceinline__ void sts128(uint32_t a, uint32_t x, uint32_t y, uint32_t z, uint32_t w) { asm volatile("st.shared.v4.u32 [%0], {%1,%2,%3,%4};" ::"r"(a), "r"(x), "r"(y), "r"(z), "r"(w) : "memory"); }
__device__ __forceinline__ void stsm4(uint32_t a, uint32_t r0, uint32_t r1, uint32_t r2, uint32_t r3) {
  asm volatile("stmatrix.sync.aligned.m8n8.x4.shared.b16 [%0], {%1,%2,%3,%4};" ::"r"(a), "r"(r0), "r"(r1), "r"(r2), "r"(r3) : "memory");
}
__device__ __forceinline__ void stsm4t(uint32_t a, uint32_t r0, uint32_t r1, uint32_t r2, uint32_t r3) {
  asm volatile("stmatrix.sync.aligned.m8n8.x4.trans.shared.b16 [%0], {%1,%2,%3,%4};" ::"r"(a), "r"(r0), "r"(r1), "r"(r2), "r"(r3) : "memory");
}
__device__ __forceinline__ void ldsm4t(uint32_t* r, uint32_t a) {
  asm volatile("ldmatrix.sync.aligned.m8n8.x4.trans.shared.b16 {%0,%1,%2,%3}, [%4];" : "=r"(r[0]), "=r"(r[1]), "=r"(r[2]), "=r"(r[3]) : "r"(a) : "memory");
}
__device__ __forceinline__ uint32_t pack2(float lo, float hi) { uint32_t r; asm("cvt.rn.bf16x2.f32 %0, %1, %2;" : "=r"(r) : "f"(hi), "f"(lo)); return r; }
__device__ __forceinline__ float bf_lo(uint32_t u) { return __uint_as_float(u << 16); }
__device__ __forceinline__ float bf_hi(uint32_t u) { return __uint_as_float(u & 0xffff0000u); }
__device__ __forceinline__ uint32_t hmul2(uint32_t a, uint32_t b) { uint32_t r; asm("mul.rn.bf16x2 %0, %1, %2;" : "=r"(r) : "r"(a), "r"(b)); return r; }
__device__ __forceinline__ uint32_t hfma2(uint32_t a, uint32_t b, uint32_t c) { uint32_t r; asm("fma.rn.bf16x2 %0, %1, %2, %3;" : "=r"(r) : "r"(a), "r"(b), "r"(c)); return r; }
__device__ __forceinline__ uint32_t prmt(uint32_t a, uint32_t b, uint32_t s) { return __byte_perm(a, b, s); }

__device__ __forceinline__ uint32_t ld_relaxed(const uint32_t* p) { uint32_t v; asm volatile("ld.relaxed.gpu.global.u32 %0, [%1];" : "=r"(v) : "l"(p) : "memory"); return v; }
__device__ __forceinline__ void acquire_fence() { asm volatile("fence.acquire.gpu;\nfence.proxy.async.global;" ::: "memory"); }
__device__ __forceinline__ uint32_t load_epoch(const Params& p, int idx, int lane) { return ld_relaxed(&p.scr->epoch[idx + (((lane * lane) & 3) == 2 ? 1 : 0)]); }
template <bool G, class L, class C>
__device__ __forceinline__ auto poll(L load, C ok) {
  uint32_t t0 = 0;
  auto a = load();
#pragma unroll 1
  while (!__all_sync(0xffffffff, ok(a))) { spin_guard<G>(t0); a = load(); }
  return a;
}
__device__ __forceinline__ void poll_flags4(const uint32_t* flags, uint32_t tag, int lane) {
  poll<false>([&]() { return ld_relaxed(flags + (lane & 3) * 8); }, [&](uint32_t v) { return v == tag; });
  acquire_fence();
}
__device__ __forceinline__ void st_relaxed(uint32_t* p, uint32_t v) { asm volatile("st.relaxed.gpu.global.u32 [%0], %1;" ::"l"(p), "r"(v) : "memory"); }
__device__ __forceinline__ uint32_t tag8(uint32_t tag) { return (tag & 127) | 128; }
__device__ __forceinline__ uint32_t tagged(float v, uint32_t t8) { return (__float_as_uint(v) & ~255u) | t8; }
__device__ __forceinline__ void reset_sector(uint32_t* f) { st_ll4(f, 0, 0, 0, 0); st_ll4(f + 4, 0, 0, 0, 0); }
template <bool G = false> __device__ __forceinline__ void poll_counter(const uint32_t* cnt, uint32_t target) {
  poll<G>([&]() { return ld_relaxed(cnt); }, [&](uint32_t v) { return v == target; });
  acquire_fence();
}

__device__ __forceinline__ uint32_t hadd2(uint32_t a, uint32_t b) { uint32_t r; asm("add.rn.bf16x2 %0, %1, %2;" : "=r"(r) : "r"(a), "r"(b)); return r; }
__device__ __forceinline__ uint32_t htanh2(uint32_t a) { uint32_t r; asm("tanh.approx.bf16x2 %0, %1;" : "=r"(r) : "r"(a)); return r; }
__device__ __forceinline__ void red_relaxed(uint32_t* p) { asm volatile("red.relaxed.gpu.global.add.u32 [%0], 1;" ::"l"(p) : "memory"); }
__device__ __forceinline__ void bulk_commit_wait() { asm volatile("cp.async.bulk.commit_group;\ncp.async.bulk.wait_group 0;" ::: "memory"); }

__device__ __forceinline__ int g3_block(int cb, int it) { return it < 3 ? cb * 3 + it : (it - 3 < cb * 3 ? it - 3 : it); }

#define GSTAMP(m, i)
struct NoHook { __device__ __forceinline__ void operator()(int = 0) const {} };
template <int N, int MODE, class F = NoHook, class F0 = NoHook>
__device__ __forceinline__ void gemm_seg(float* d, uint32_t sb, uint64_t db0, int i0, int i1, int s, uint32_t pb, uint32_t doR, uint32_t acc TSP, F hook = F(), F0 pre = F0()) {
  constexpr bool G3 = MODE == 2 || MODE == 4, RA = MODE == 1 || MODE == 3;
  constexpr int W = MODE <= 2 ? 2 : 1, RC = MODE == 2 ? 1 : 2, NS = G3 ? 6 : 5, BSTEP = G3 ? 320 : 128;
  const uint64_t da0 = mkdesc(sb + OFF_A, 16, 1024, 1);
  auto sa = [](int i) { return MODE == 1 ? (i + 3) & 7 : (G3 && i >= 9 ? i - 9 : i); };
  auto fa = [&](int i) { return sb + (MODE == 2 ? BAR_HV + 8 * (i - 3) : BAR_AF + 8 * sa(i)); };
  auto pa = [](int i) { return MODE == 1 ? ((i >> 3) & 1) ^ 1 : MODE == 2 && i >= 9; };
  auto fb = [&](int s_) { return sb + (G3 ? BAR_WF : BAR_BF) + 8 * s_; };
  auto db = [&](int s_) { return db0 + (G3 ? (s_ >= 3 ? s_ - 3 : s_ + 3) * (W_SLOT >> 4) : s_ * (B_SLOT >> 4)); };
  const uint32_t dummy = sb + BAR_DUMMY;
  auto ea = [&](int i) { return MODE == 3 && i >= 8 ? dummy : sb + BAR_AE + 8 * sa(i); };
  uint32_t rel = dummy, rela = dummy;
  acc_fence<N / 2>(d);
  pre();
  if (W == 2) mbar_wait(fa(i0), pa(i0));
  mbar_wait(fb(s), pb);
  WG_FENCE();
#pragma unroll 1
  for (int i = i0; i < i1 - 1; i++) {
    GSTAMP(MODE, i);
    const int n = s + 1 == NS ? 0 : s + 1;
    if (n == 0) pb ^= 1;
    KB<N>::template run<W, RC, RA, BSTEP>(d, da0 + sa(i) * (A_SLOT >> 4), db(s), rel, rela, doR, fa(i + 1), pa(i + 1), fb(n), pb, acc);
    rel = G3 ? (i < 6 ? sb + BAR_WE + 8 * s : dummy) : sb + BAR_BE + 8 * s;
    rela = ea(i);
    s = n;
    acc = 1;
  }
  hook();
  GSTAMP(MODE, i1 - 1);
  KB<N>::template run<0, RC, RA, BSTEP>(d, da0 + sa(i1 - 1) * (A_SLOT >> 4), db(s), rel, rela, doR, 0, 0, 0, 0, 1);
  WG_WAIT(0);
  GSTAMP(MODE, i1);
  acc_fence<N / 2>(d);
  if (MODE != 2) {
    rel = sb + (G3 ? BAR_WE : BAR_BE) + 8 * s;
    mbar_arrive_if(rel, doR);
    mbar_arrive_if(rel, doR);
    if (RA) { mbar_arrive_if(ea(i1 - 1), doR); mbar_arrive_if(ea(i1 - 1), doR); }
  }
}

__device__ __forceinline__ uint32_t val_off(int lane) { return lane * 32 + ((lane >> 2) & 1) * 16 + (lane >> 3) * 4; }
template <int NK, int PAD = 0, class F>
__device__ __forceinline__ void validate(uint32_t a, uint32_t par, uint32_t rt, F reload) {
  uint32_t t0 = 0;
#pragma unroll 1
  while (true) {
    uint32_t v[NK], any = 0;
#pragma unroll
    for (int i = 0; i < NK; i++) asm volatile("ld.shared.u32 %0, [%1];" : "=r"(v[i]) : "r"(a + i * 1024 + (i >> 1) * PAD) : "memory");
#pragma unroll
    for (int i = 0; i < NK; i++) any |= v[i] ^ par;
    if (!__any_sync(0xffffffff, any & 1)) break;
    spin_guard(t0);
    fence_async_smem();
    __syncwarp();
    if (elect_one()) { mbar_init(rt, 1); fence_async_smem(); mbar_expect(rt, NK * 1024); reload(); }
    __syncwarp();
    mbar_wait(rt, 0);
    __syncwarp();
    if (elect_one()) asm volatile("mbarrier.inval.shared::cta.b64 [%0];" ::"r"(rt) : "memory");
  }
}
__device__ __forceinline__ uint32_t swz_base(uint32_t img, int w, int lane) { return img + (w * 16 + (lane & 15)) * 128 + (((lane >> 4) ^ lane) & 7) * 16; }

template <bool STATS>
__device__ __forceinline__ void gelu_tile(const float* d, uint32_t* z, float* st, uint32_t cs0, float2 s0, float2 s1, uint32_t done) {
  const float kA = 0.7978845608028654f, kB = 0.7978845608028654f * 0.044715f;
  const float ra = s0.y, rb = s1.y;
  const float a1 = kA * ra, a3 = kB * ra * ra * ra, b1 = kA * rb, b3 = kB * rb * rb * rb;
  const uint32_t c1[2] = {pack2(a1, a1), pack2(b1, b1)}, c3[2] = {pack2(a3, a3), pack2(b3, b3)};
  const float m[2] = {-s0.x, -s1.x};
  uint32_t S[2][2], Q[2][2];
#pragma unroll
  for (int j = 0; j < 24; j++) {
    if (!STATS && j && j % 6 == 0) mbar_wait(done, 0);
    const float2 cs = lds64f(cs0 + j * 32);
#pragma unroll
    for (int r = 0; r < 2; r++) {
      const uint32_t v = pack2(fmaf(m[r], cs.x, d[4 * j + 2 * r]), fmaf(m[r], cs.y, d[4 * j + 2 * r + 1]));
      uint32_t y = hfma2(v, htanh2(hmul2(v, hfma2(hmul2(v, v), c3[r], c1[r]))), v);
      asm volatile("" : "+r"(y));
      z[2 * j + r] = y;
      if (STATS) {
        S[r][j & 1] = j < 2 ? y : hadd2(S[r][j & 1], y);
        Q[r][j & 1] = j < 2 ? hmul2(y, y) : hfma2(y, y, Q[r][j & 1]);
      }
    }
  }
  if (STATS) {
#pragma unroll
    for (int r = 0; r < 2; r++) {
      st[2 * r] = (bf_lo(S[r][0]) + bf_hi(S[r][0])) + (bf_lo(S[r][1]) + bf_hi(S[r][1]));
      st[2 * r + 1] = (bf_lo(Q[r][0]) + bf_hi(Q[r][0])) + (bf_lo(Q[r][1]) + bf_hi(Q[r][1]));
    }
  }
}

__device__ __forceinline__ float2 quad_sum(const float* st, int t) {
  const bool o = t & 1;
  float s = (o ? st[2] : st[0]) + __shfl_xor_sync(0xffffffff, o ? st[0] : st[2], 1);
  float q = (o ? st[3] : st[1]) + __shfl_xor_sync(0xffffffff, o ? st[1] : st[3], 1);
  s += __shfl_xor_sync(0xffffffff, s, 2);
  q += __shfl_xor_sync(0xffffffff, q, 2);
  return make_float2(s, q);
}
template <int Q> __device__ __forceinline__ void conv_load(uint32_t* a, uint32_t ab) {
  a[0] = lds32<512 * Q>(ab);       a[1] = lds32<512 * Q + 256>(ab);  a[2] = lds32<512 * Q + 16>(ab);   a[3] = lds32<512 * Q + 272>(ab);
  a[4] = lds32<512 * Q + 32>(ab);  a[5] = lds32<512 * Q + 288>(ab);  a[6] = lds32<512 * Q + 48>(ab);   a[7] = lds32<512 * Q + 304>(ab);
  a[8] = lds32<512 * Q + 64>(ab);  a[9] = lds32<512 * Q + 320>(ab);  a[10] = lds32<512 * Q + 80>(ab);  a[11] = lds32<512 * Q + 336>(ab);
  a[12] = lds32<512 * Q + 96>(ab); a[13] = lds32<512 * Q + 352>(ab); a[14] = lds32<512 * Q + 112>(ab); a[15] = lds32<512 * Q + 368>(ab);
}
template <int Q, int L> __device__ __forceinline__ void conv_step(float* d, uint32_t (*a)[16], uint32_t ab, uint64_t db) {
  WG_FENCE();
#pragma unroll
  for (int s = 0; s < 4; s++) WG<128 - 16 * Q>::rs(d, a[Q] + 4 * s, db + s + 16 * Q);
  WG_COMMIT();
  WG_WAIT(1);
  if (L >= 0) conv_load<(L >= 0 ? L : 0)>(a[L >= 0 ? L : 0], ab);
  if (Q == 0) WG_WAIT(0);
}

__device__ __forceinline__ void final_load_x(uint32_t (*xw)[10], const __nv_bfloat16* x0, int t) {
#pragma unroll
  for (int r = 0; r < 2; r++) {
    const __nv_bfloat16* q = x0 + r * 8 * kD;
    const uint4 u = ldg4(q + t * 8), v = ldg4(q + 32 + t * 8);
    asm volatile("ld.global.v2.u32 {%0,%1}, [%2];" : "=r"(xw[r][8]), "=r"(xw[r][9]) : "l"(q + 64 + t * 4) : "memory");
    xw[r][0] = u.x; xw[r][1] = u.y; xw[r][2] = u.z; xw[r][3] = u.w;
    xw[r][4] = v.x; xw[r][5] = v.y; xw[r][6] = v.z; xw[r][7] = v.w;
  }
}
template <class F>
__device__ __forceinline__ void final_out(const float* d, const uint32_t (*xw)[10], const uint32_t* rn, const float* c, uint32_t yt, __nv_bfloat16* o0, int w, int lane, F wait_y) {
  const int r8 = lane & 7, mi = lane >> 3, t = lane & 3;
  const uint32_t ya = yt + ((mi >> 1) * 8 + r8) * 128 + (((2 * w + (mi & 1)) ^ r8) << 4);
#pragma unroll
  for (int q = 0; q < 3; q++) {
    const int n = q < 2 ? 8 : 4;
    uint32_t gt[8], y[8];
#pragma unroll
    for (int e = 0; e < n; e++) {
      const int i = q * 8 + e;
      const uint32_t h = pack2(d[2 * i] * c[i & 1], d[2 * i + 1] * c[i & 1]);
      gt[e] = hmul2(hfma2(h, htanh2(h), h), hfma2(xw[i & 1][i >> 1], rn[i & 1], rn[2 + (i & 1)]));
      if (q == 0) asm volatile("" : "+r"(gt[e]));
    }
    if (q == 0) wait_y();
    ldsm4t(y, ya + q * 4096);
    if (q < 2) ldsm4t(y + 4, ya + q * 4096 + 2048);
#pragma unroll
    for (int e = 0; e < n; e++) y[e] = hfma2(gt[e], y[e], xw[e & 1][q * 4 + (e >> 1)]);
#pragma unroll
    for (int r = 0; r < 2; r++) {
      __nv_bfloat16* o = o0 + r * 8 * kD;
      if (q < 2) stg4_if(o + q * 32 + t * 8, y[r], y[2 + r], y[4 + r], y[6 + r], true);
      else asm volatile("st.global.v2.u32 [%0], {%1,%2};" ::"l"(o + 64 + t * 4), "r"(y[r]), "r"(y[2 + r]) : "memory");
    }
  }
}

struct Taps { uint4 r0, r1; uint32_t n0, n1, dd; };
__device__ __forceinline__ void load_taps(Taps& k, const Params& p, int ch, int tid) {
  const uint4* kp = (const uint4*)(p.ssmk + (size_t)ch * kS);
  k.r0 = ldg4(kp + tid); k.r1 = ldg4(kp + 128 + tid);
  k.n0 = ldg1(kp + tid + 1); k.n1 = tid < 127 ? ldg1(kp + 129 + tid) : 0u;
  k.dd = __bfloat16_as_ushort(p.ssmD[ch]);
}
__device__ __forceinline__ void convx_copy(const Params& p, uint32_t cv, uint32_t bar, int ch) {
  bulk_g2s(cv, p.scr->kvx + (size_t)ch * 4096, 2048, bar);
  bulk_g2s(cv + XB_PL, p.scr->kvx + (size_t)ch * 4096 + 2048, 2048, bar);
}
__device__ __forceinline__ void convx_issue(const Params& p, uint32_t sb, int h, int ch) {
  if (elect_one()) { mbar_expect(sb + BAR_XL + 8 * h, 4096); convx_copy(p, sb + OFF_CV + (1 - h) * CV_SZ, sb + BAR_XL + 8 * h, ch); }
}
__device__ __forceinline__ void convx_finish(const Params& p, uint32_t sb, int h, int ch, int i, uint32_t par, int lane) {
  const uint32_t cv = sb + OFF_CV + (1 - h) * CV_SZ, rt = sb + BAR_XL - 16 + 8 * h;
  mbar_wait(sb + BAR_XL + 8 * h, i & 1);
  validate<4, XB_PL - 2048>(cv + lane * 32, par, rt, [&]() { convx_copy(p, cv, rt, ch); });
  if (elect_one()) mbar_arrive(sb + BAR_XF + 8 * h);
}
__device__ __forceinline__ void zero_pads(uint32_t cv, int lane) {
  if (lane < 8) sts128(cv + (lane >> 2) * XB_PL + 2048 + (lane & 3) * 16, 0, 0, 0, 0);
  else if (lane < 12) sts128(cv + ((lane & 2) ? CV_KO : CV_KE) + (lane & 1) * 16, 0, 0, 0, 0);
  fence_async_smem();
  __syncwarp();
}
__device__ __forceinline__ int y_row(int c) {
  const int cc = c % 80;
  return c - cc + (cc & 1) + (cc < 64 ? (cc & 32) + ((cc >> 1) & 3) * 8 + ((cc >> 3) & 3) * 2 : 64 + ((cc >> 1) & 1) * 8 + ((cc >> 2) & 3) * 2);
}
struct KvRegs { uint32_t k[11], v[8]; uint4 sh; };
__device__ __forceinline__ void kv_load(KvRegs& q, const __nv_bfloat16* kp, const __nv_bfloat16* vp, const __nv_bfloat16* sp, bool halo) {
#pragma unroll
  for (int i = 0; i < 11; i++) q.k[i] = (i >= 3 || halo) ? ldg1(kp + i * kD) : 0u;
#pragma unroll
  for (int i = 0; i < 8; i++) q.v[i] = ldg1(vp + i * kD);
  q.sh = ldg4(sp);
}
__device__ __forceinline__ void kv_calc(const KvRegs& q, uint32_t* o) {
  const uint32_t w0 = prmt(q.sh.x, q.sh.z, 0x5410), w1 = prmt(q.sh.x, q.sh.z, 0x7632), w2 = prmt(q.sh.y, q.sh.w, 0x5410), w3 = prmt(q.sh.y, q.sh.w, 0x7632);
  uint32_t r[8];
#pragma unroll
  for (int i = 0; i < 8; i++) r[i] = hmul2(hfma2(q.k[i + 3], w0, hfma2(q.k[i + 2], w1, hfma2(q.k[i + 1], w2, hmul2(q.k[i], w3)))), q.v[i]);
#pragma unroll
  for (int i = 0; i < 4; i++) { o[i] = prmt(r[7 - 2 * i], r[6 - 2 * i], 0x5410); o[4 + i] = prmt(r[7 - 2 * i], r[6 - 2 * i], 0x7632); }
}
__device__ __forceinline__ void kv_put(const uint32_t* o, uint32_t oa, uint32_t tm, uint32_t tb) {
  sts128(oa, (o[0] & tm) | tb, o[1], o[2], o[3]);
  sts128(oa + 2048, (o[4] & tm) | tb, o[5], o[6], o[7]);
}

__device__ __forceinline__ void kv_store(const Params& p, uint32_t src, int tb, int unit) {
  asm volatile("cp.async.bulk.tensor.3d.global.shared::cta.bulk_group [%0, {%2, %3, %4}], [%1];" ::"l"(&p.tmKV), "r"(src), "r"((63 - tb) * 16), "r"(unit * 32), "r"(0) : "memory");
}
__device__ __forceinline__ uint32_t kv_stage_addr(int w, int lane) { return ((3 - w) & 1) * 1024 + lane * 32 + ((((3 - w) >> 1) ^ (lane >> 2)) & 1) * 16; }

template <class F>
__device__ __forceinline__ void conv_service(const Params& p, uint32_t sb, int h, int ch, uint32_t par, int lane, F mid) {
#pragma unroll 1
  for (int i = 0; i < 2 + h; i++, ch += 128) {
    bar_sync(NB_SV + h, 160);
    if (i < h) convx_issue(p, sb, h, ch + 128);
    uint8_t* dst = p.scr->y + (size_t)y_row(ch) * 4096;
    bar_sync(NB_SV2(h), 160);
    if (i == h && (h ? YSB : YSA) >= 0) mbar_wait(sb + (h ? BAR_YS : BAR_ST), !h);
    if (elect_one()) {
      bulk_s2g(dst, sb + OFF_A + 9 * A_SLOT + h * 4096, 4096);
      bulk_commit_wait();
    }
    __syncwarp();
    if (i > h) break;
    if (i == h) { mid(); mbar_wait(sb + BAR_KV2, 0); convx_issue(p, sb, h, ch + 128); }
    convx_finish(p, sb, h, ch + 128, i + 1, par, lane);
  }
}
__device__ __forceinline__ void conv_worker(const Params& p, Taps& k, uint32_t sb, int h, int ch0, int w, int lane, int tid, int rb, int cb TSP) {
  const uint32_t cv = sb + OFF_CV + (1 - h) * CV_SZ, yb0 = sb + OFF_A + 9 * A_SLOT + h * 4096, xbar = sb + BAR_XF + 8 * h;
  const int n = 2 + h, nbar = NB_WG + h;
  const int g = lane >> 2, t = lane & 3, w0 = w & 1, w1 = w >> 1;
  const uint32_t ab = cv + ((g & 1) ? CV_KE : CV_KO) + 32 + 2 * (64 * w0 + 8 * w1 + ((g - 15) & ~1) + 2 * t);
  const uint32_t scA = cv + (w1 ? CV_KO : CV_KE) + 32, scB = scA + 2048;
  const int dl = (t >> 1) ^ 1, col = lane & 7, mi = lane >> 3;
  if (h == 0) mbar_wait(xbar, 0);
  TR(26);
#pragma unroll 1
  for (int i = 0; i < n; i++) {
    if (tid == 0) {
      k.r0.x = (k.r0.x & 0xffff0000u) | (pack2(bf_lo(k.r0.x) + bf_lo(k.dd), 0.f) & 0xffffu);
      sts32(cv + CV_KO + 28, k.r0.x << 16);
    }
    sts128(cv + CV_KE + 32 + tid * 16, k.r0.x, k.r0.y, k.r0.z, k.r0.w);
    sts128(cv + CV_KO + 32 + tid * 16, prmt(k.r0.x, k.r0.y, 0x5432), prmt(k.r0.y, k.r0.z, 0x5432), prmt(k.r0.z, k.r0.w, 0x5432), prmt(k.r0.w, k.n0, 0x5432));
    sts128(cv + CV_KE + 2080 + tid * 16, k.r1.x, k.r1.y, k.r1.z, k.r1.w);
    sts128(cv + CV_KO + 2080 + tid * 16, prmt(k.r1.x, k.r1.y, 0x5432), prmt(k.r1.y, k.r1.z, 0x5432), prmt(k.r1.z, k.r1.w, 0x5432), prmt(k.r1.w, k.n1, 0x5432));
    TR(30 + i * 10);
    if (i + 1 < n) load_taps(k, p, ch0 + (i + 1) * 128, tid);
    bar_sync(nbar, 128);
    TR(31 + i * 10);
    const uint64_t db = mkdesc(cv + (i & 0x1000), XB_PL, 128, 0);
    float d[64];
    uint32_t a[8][16];
    conv_load<7>(a[7], ab);
    conv_load<6>(a[6], ab);
    conv_load<5>(a[5], ab);
    conv_load<4>(a[4], ab);
#pragma unroll
    for (int j = 0; j < 64; j++) d[j] = 0.f;
    if (i == 0) STAMPW(h ? 43 : 8);
    TR(32 + i * 10);
    mbar_wait2(xbar, i & 1, sb + (i + 1 < n ? BAR_ZG : (h ? BAR_HOLD : BAR_HR)), 0);
    if (i == 0) STAMPW(h ? 51 : 7);
    TR(33 + i * 10);
    conv_step<7, -1>(d, a, ab, db); conv_step<6, -1>(d, a, ab, db); conv_step<5, -1>(d, a, ab, db); conv_step<4, 3>(d, a, ab, db);
    conv_step<3, 2>(d, a, ab, db); conv_step<2, 1>(d, a, ab, db); conv_step<1, 0>(d, a, ab, db); conv_step<0, -1>(d, a, ab, db);
    acc_fence<64>(d);
    TR(34 + i * 10);
    bar_arrive(NB_SV + h, 160);
    if (i == 0) mbar_wait(sb + BAR_YT, 0);
    const uint32_t par = lds32<0>(sb + OFF_TAG);
    TR(35 + i * 10);
    float E[16][2];
#pragma unroll
    for (int j = 0; j < 15; j++) { E[j][0] = d[4 * j] + d[4 * j + 6]; E[j][1] = d[4 * j + 1] + d[4 * j + 7]; }
    E[15][0] = d[60]; E[15][1] = d[61];
    if (w0 == 0) {
#pragma unroll
      for (int j = 8; j < 16; j++) sts64f(scA + (j - 8) * 256 + lane * 8, E[j][0], E[j][1]);
    } else {
      const uint32_t a = scB - dl * 256 + (lane ^ 2) * 8;
#pragma unroll
      for (int j = 1; j < 8; j++) sts64f(a + j * 256, E[j][0], E[j][1]);
      sts64f(scB + (dl ? 7 * 256 : 0) + (lane ^ 2) * 8, dl ? E[8][0] : E[0][0], dl ? E[8][1] : E[0][1]);
    }
    TR(36 + i * 10);
    bar_sync(nbar, 128);
    uint32_t pk[8];
    const bool tg = w1 == 0 && g == 0;
    const uint32_t tm = tg ? ~0x10001u : ~0u, tb = tg && (par & 1) ? 0x10001u : 0;
    if (w0 == 0) {
#pragma unroll
      for (int j = 0; j < 8; j++) { const float2 v = lds64f(scB + j * 256 + lane * 8); pk[j] = (pack2(E[j][0] + v.x, E[j][1] + v.y) & tm) | tb; }
      const uint32_t ya = yb0 + 32 * (127 - (8 * mi + col)) + 16 * w1;
      stsm4t(ya, pk[0], pk[1], pk[2], pk[3]);
      stsm4t(ya - 1024, pk[4], pk[5], pk[6], pk[7]);
    } else {
      const uint32_t a0 = scA - dl * 256 + (lane ^ 2) * 8;
#pragma unroll
      for (int j = 9; j < 16; j++) { const float2 v = lds64f(a0 + (j - 8) * 256); pk[j - 8] = (pack2(E[j][0] + v.x, E[j][1] + v.y) & tm) | tb; }
      const float2 v = lds64f(scA + (dl ? 7 * 256 : 0) + (lane ^ 2) * 8);
      pk[0] = (pack2((dl ? 0.f : E[8][0]) + v.x, (dl ? 0.f : E[8][1]) + v.y) & tm) | tb;
      const uint32_t yb = yb0 + 32 * (127 - (92 + 8 * mi + col)) + 16 * w1;
      const uint32_t ya = (mi == 0 && col < 4) ? yb0 + 32 * (3 - col) + 16 * w1 : yb + 1024;
      stsm4t(ya, pk[0], pk[1], pk[2], pk[3]);
      stsm4t(yb, pk[4], pk[5], pk[6], pk[7]);
    }
    TR(37 + i * 10);
    fence_async_smem();
    bar_arrive(NB_SV2(h), 160);
    if (i + 1 < n) bar_sync(nbar, 128);
    TR(38 + i * 10);
    STAMPW((h ? 40 : 5) + i);
    if (i == 0 && h == 0) {
      const int tn = tid_now();
      {
        const int ln = tn & 31, t0 = (rb * 2 + (cb & 1)) * 32 + w * 8, c0 = (cb >> 1) * 320 + 192 + ln * 2;
        KvRegs q0, q1;
        uint32_t o[8];
        kv_load(q0, p.k + (size_t)(t0 - 3) * kD + c0, p.v + (size_t)t0 * kD + c0, p.shift + c0 * 4, t0 > 0);
        kv_load(q1, p.k + (size_t)(t0 - 3) * kD + c0 + 64, p.v + (size_t)t0 * kD + c0 + 64, p.shift + c0 * 4 + 256, t0 > 0);
        const uint32_t oa = sb + OFF_A + 8 * A_SLOT + kv_stage_addr(w, ln), km = w >= 2 ? ~1u : ~0u, kb = w >= 2 ? lds32<0>(sb + OFF_TAG) & 1 : 0;
        kv_calc(q0, o);
        kv_put(o, oa, km, kb);
        kv_calc(q1, o);
        kv_put(o, oa + 4096, km, kb);
        fence_async_smem();
        bar_arrive(NB_KL, 160);
      }
      STAMPW(56);
      const int u = (tn >> 3) % 5, kg = rb * 3 + (tn < 120 ? (tn >> 3) / 5 : 0), c = u < 4 ? (u >> 1) * 10 + (u & 1) * 4 : 8, o2 = u < 4 ? 2 : 10;
      const uint4* wp = (const uint4*)(p.wout + (size_t)(kg * 8 + (tn & 7)) * kD + cb * 160) + c;
      const uint4 w0 = ldg4(wp), w1 = ldg4(wp + 1), w2 = ldg4(wp + o2), w3 = ldg4(wp + o2 + 1);
      uint8_t* dst = p.scr->wo + (size_t)cb * (12 * W_SLOT) + kg * 2560 + c * 128 + (tn & 7) * 16;
      const bool f = u < 4, on = tn < 120;
      stg4_if(dst, w0.x, f ? w1.x : w0.z, f ? w2.x : w1.x, f ? w3.x : w1.z, on);
      stg4_if(dst + 128, w0.y, f ? w1.y : w0.w, f ? w2.y : w1.y, f ? w3.y : w1.w, on);
      stg4_if(dst + o2 * 128, f ? w0.z : w2.x, f ? w1.z : w2.z, f ? w2.z : w3.x, w3.z, on);
      stg4_if(dst + o2 * 128 + 128, f ? w0.w : w2.y, f ? w1.w : w2.w, f ? w2.w : w3.y, w3.w, on);
      bar_arrive(NB_WO, 160);
    }
  }
}

struct U6 { uint64_t a, b, c; };
__device__ __forceinline__ uint64_t ld_ll2(const void* p) { uint64_t a; asm volatile("ld.relaxed.gpu.global.u64 %0, [%1];" : "=l"(a) : "l"(p) : "memory"); return a; }
__device__ __forceinline__ void gather_colsum(const Params& p, uint32_t sb, int part, int cb, uint32_t tag8, int lane) {
  const uint32_t* src = p.scr->colsum + (uint32_t)((part ? 0 : 768) + cb * 192 + lane * 2);
  const uint64_t t2 = tag8 * 0x100000001ull;
  const U6 v = poll<false>([&]() { return U6{ld_ll2(src), ld_ll2(src + 64), ld_ll2(src + 128)}; },
                                    [&](const U6& u) { return (((u.a ^ t2) | (u.b ^ t2) | (u.c ^ t2)) & 0xff000000ffull) == 0; });
  const uint32_t dst = sb + OFF_CS + (part ? 0 : 768) + lane * 8;
  asm volatile("st.shared.u64 [%0], %1;\nst.shared.u64 [%0+256], %2;\nst.shared.u64 [%0+512], %3;" ::"r"(dst), "l"(v.a), "l"(v.b), "l"(v.c) : "memory");
  __syncwarp();
  mbar_arrive_if(sb + BAR_ST + 8 * part, lane == 0);
}

__device__ __forceinline__ void helper_cta(const Params& p, uint32_t sb, int cb, int warp, int lane TSP) {
  constexpr int NS = 9, ONES = NS * B_SLOT, BF = ONES + 256, BE = BF + 8 * NS;
  if (warp < NS && elect_one()) {
    mbar_init(sb + BF + 8 * warp, 1); mbar_init(sb + BE + 8 * warp, 1);
    fence_async_smem();
    if (warp == 0) { mbar_expect(sb + BF, B_SLOT); tma3d(sb, &p.tmW, 0, 0, 12 + cb * 3, sb + BF); }
  }
  if (warp == 15) { sts32(sb + ONES + lane * 4, 0x3f803f80u); sts32(sb + ONES + 128 + lane * 4, 0x3f803f80u); fence_async_smem(); }
  __syncthreads();
  if (warp == 4) {
    int s = 1, ph = 1;
    uint32_t tp = clock() + HP0;
#pragma unroll 1
    for (int it = 1; it < 20; it++) {
      if (it >= 10) pace(tp, HPD);
      mbar_wait(sb + BE + 8 * s, ph);
      if (elect_one()) { mbar_expect(sb + BF + 8 * s, B_SLOT); tma3d(sb + s * B_SLOT, &p.tmW, 0, (it < 10 ? it : it - 10) * 64, (it < 10 ? 12 : 0) + cb * 3, sb + BF + 8 * s); }
      if (++s == NS) { s = 0; ph ^= 1; }
    }
  } else if (warp < 4) {
    const uint32_t tag = load_epoch(p, 128 + cb, lane) + 1;
    const uint64_t db = mkdesc(sb + ONES, 128, 128, 0);
    uint32_t* dst = p.scr->colsum + cb * 192 + warp * 16 + (lane >> 2);
    if ((lane & 3) == 0) {
#pragma unroll 1
      for (int j = 0; j < 12; j++) st_relaxed(dst + (j < 6 ? 768 : 0) + ((j % 6) >> 1) * 64 + (j & 1) * 8, 0);
    }
    int s = 0, ph = 0;
#pragma unroll 1
    for (int part = 0; part < 2; part++) {
      float d[12];
#pragma unroll
      for (int i = 0; i < 12; i++) d[i] = 0.f;
#pragma unroll 1
      for (int it = 0; it < 10; it++) {
        mbar_wait(sb + BF + 8 * s, ph);
        const uint64_t da = mkdesc(sb + s * B_SLOT, 8192, 1024, 1);
        WG_FENCE();
#pragma unroll
        for (int j = 0; j < 12; j++) wgmma_colsum(d + 4 * (j % 3), da + (j % 3) * 512 + (j / 3) * 128, db);
        WG_COMMIT();
        WG_WAIT(1);
        mbar_arrive_if(sb + BE + 8 * (s == 0 ? NS - 1 : s - 1), threadIdx.x == 0 && (it | part) != 0);
        if (++s == NS) { s = 0; ph ^= 1; }
      }
      WG_WAIT(0);
      acc_fence<12>(d);
      if ((lane & 3) == 0) {
#pragma unroll
        for (int j = 0; j < 6; j++) st_relaxed(dst + (part ? 0 : 768) + (j >> 1) * 64 + (j & 1) * 8, tagged(d[2 * j], tag8(tag)));
      }
      STAMPW(1 + part);
    }
    if (threadIdx.x == 0) *(volatile uint32_t*)&p.scr->epoch[128 + cb] = tag;
  }
}

__global__ void __launch_bounds__(512, 1) fused_kernel(const __grid_constant__ Params p) {
  extern __shared__ __align__(1024) uint8_t smem[];
  const int warp = __shfl_sync(0xffffffff, (int)(threadIdx.x >> 5), 0);
  const int lane = threadIdx.x & 31;
  const uint32_t sb = __shfl_sync(0xffffffff, (uint32_t)__cvta_generic_to_shared(smem), 0);
  const uint32_t tstart = clock();
  int b = blockIdx.x;
  if (p.by_smid) asm volatile("mov.u32 %0, %%smid;" : "=r"(b));
  b = __shfl_sync(0xffffffff, b, 0);
  const int job = p.job[b], lin = job & 255, cb = job >> 8 & 3, rb = job >> 10;
  if (elect_one()) {
    mbar_init(sb + OFF_BAR + 8 * warp, 1);
    if (lin < 128) {
      if (warp < NPRE) { fence_async_smem(); mbar_expect(sb + BAR_AF + 8 * warp, A_SLOT); tma2d(sb + OFF_A + warp * A_SLOT, &p.tmX, warp * 64, rb * 64, sb + BAR_AF + 8 * warp); }
      if (warp >= 10 && warp < 10 + NPRE) { fence_async_smem(); mbar_expect(sb + OFF_BAR + 8 * warp, B_SLOT); tma3d(sb + OFF_B + (warp - 10) * B_SLOT, &p.tmW, 0, (warp - 10) * 64, 12 + cb * 3, sb + OFF_BAR + 8 * warp); }
    }
    if (warp >= 2 && warp < 5) asm volatile("prefetch.tensormap [%0];" ::"l"(&p.tmX + warp) : "memory");
    mbar_init(sb + OFF_BAR + 128 + 8 * warp, 1);
    if (warp != 3) mbar_init(sb + OFF_BAR + 256 + 8 * warp, (0x2224444444441111ull >> (4 * warp)) & 15);
    mbar_init(sb + OFF_BAR + 384 + 8 * warp, 2);
    if (warp < 2) mbar_init(sb + BAR_XL + 8 * warp, 1);
    asm volatile("fence.mbarrier_init.release.cluster;" ::: "memory");
  }
  if (lin >= 128) { helper_cta(p, sb, cb, warp, lane TSA); return; }
  const int chb = (cb >> 1) * 320 + rb * 2 + (cb & 1);
  if (sb & 1023) die();
  __syncthreads();

  if (warp >= 12) {
    asm volatile("setmaxnreg.dec.sync.aligned.u32 32;");
    const uint8_t* z2s = p.scr->z2 + (size_t)cb * 32 * B_SLOT;
    const char* wq = (const char*)p.wsp + (rb * 64 + cb * 16 + (lane >> 1)) * (kS * 2) + (lane & 1) * 128;
    if (warp == 12) {
      int s = NPRE, ph = 1;
#pragma unroll 1
      for (int it = NPRE; it < 20; it++) {
        if (it >= 5) mbar_wait<true>(sb + BAR_BE + 8 * s, ph);
        if (it < 5 && elect_one()) { mbar_expect(sb + BAR_AF + 8 * it, A_SLOT); tma2d(sb + OFF_A + it * A_SLOT, &p.tmX, it * 64, rb * 64, sb + BAR_AF + 8 * it); }
        if (elect_one()) {
          mbar_expect(sb + BAR_BF + 8 * s, B_SLOT);
          tma3d(sb + OFF_B + s * B_SLOT, &p.tmW, 0, (it < 10 ? it : it - 10) * 64, (it < 10 ? 12 : 0) + cb * 3, sb + BAR_BF + 8 * s);
        }
        if (it == 4) {
#pragma unroll 1
          for (int i = 5; i < 10; i++)
            if (elect_one()) { mbar_expect(sb + BAR_AF + 8 * i, A_SLOT); tma2d(sb + OFF_A + i * A_SLOT, &p.tmX, i * 64, rb * 64, sb + BAR_AF + 8 * i); }
          bar_arrive(NB_KF, 160);
        }
        STAMP2(32 + it);
        if (++s == 5) { s = 0; ph ^= 1; }
      }
      const uint32_t ztarget = (load_epoch(p, lin, lane) + 1) * 128;
#pragma unroll 1
      for (int i = 0; i < LEAD; i++) {
        mbar_wait<true>(sb + BAR_AE + 8 * (3 + i), 0);
        if (elect_one()) { mbar_expect(sb + BAR_AF + 8 * (3 + i), A_SLOT); tma2d(sb + OFF_A + (3 + i) * A_SLOT, &p.tmWsp, i * 64, rb * 64, sb + BAR_AF + 8 * (3 + i)); }
      }
      mbar_wait<true>(sb + BAR_ZP, 0);
      poll_counter<true>(p.scr->cnt + CNT_Z, ztarget);
      STAMP(24);
#pragma unroll 1
      for (int it = 0; it < 32; it++) {
        mbar_wait<true>(sb + BAR_BE + 8 * s, ph);
        if (elect_one()) {
          mbar_expect(sb + BAR_BF + 8 * s, B_SLOT);
          bulk_g2s(sb + OFF_B + s * B_SLOT, z2s + it * B_SLOT, B_SLOT, sb + BAR_BF + 8 * s);
        }
        if (it == 0) STAMP(22);
        if (YSA >= 0 && it == YSA && elect_one()) mbar_arrive(sb + BAR_ST);
        if (YSB >= 0 && it == YSB && elect_one()) mbar_arrive(sb + BAR_YS);
        const int ia = it + LEAD - 1, sa = (ia + 3) & 7;
        if (it >= 1 && ia < 32) {
          mbar_wait<true>(sb + BAR_AE + 8 * sa, (ia >> 3) & 1);
          if (elect_one()) { mbar_expect(sb + BAR_AF + 8 * sa, A_SLOT); tma2d(sb + OFF_A + sa * A_SLOT, &p.tmWsp, ia * 64, rb * 64, sb + BAR_AF + 8 * sa); }
        }
        STAMP2(52 + it);
        if (++s == 5) { s = 0; ph ^= 1; }
      }
      mbar_wait<true>(sb + BAR_WO, 0);
      acquire_fence();
      s = 0;
#pragma unroll 1
      for (int it = 0; it < 12; it++) {
        if (it < 6) mbar_wait<true>(sb + BAR_BE + 8 * ((0x110443 >> (4 * it)) & 7), it < 3 ? 1 : 0);
        else mbar_wait<true>(sb + BAR_WE + 8 * s, 0);
        mbar_arrive_if(sb + BAR_HOLD, it == 0 && lane == 0);
        if (elect_one()) {
          mbar_expect(sb + BAR_WF + 8 * s, W_SLOT);
          bulk_g2s(sb + OFF_B + (s >= 3 ? s - 3 : s + 3) * W_SLOT, p.scr->wo + (size_t)(cb * 12 + g3_block(cb, it)) * W_SLOT, W_SLOT, sb + BAR_WF + 8 * s);
        }
        STAMP2(84 + it);
        if (++s == 6) s = 0;
      }
      mbar_wait<true>(sb + BAR_WE, 1);
    } else if (warp == 13) {
      const uint32_t tag = load_epoch(p, lin, lane) + 1;
      if (elect_one()) reset_sector(&p.scr->hflag[rb * 32 + cb * 8]);
      if (lane == 0) sts32(sb + OFF_TAG, tag8(tag));
      mbar_wait(sb + BAR_AF + 72, 0);
      { uint32_t tp = clock(); pace(tp, CSD); }
      gather_colsum(p, sb, 0, cb, tag8(tag), lane);
      STAMP(27);
      bar_sync(NB_Z, 160);
      if (elect_one()) {
        mbar_arrive(sb + BAR_ZG);
        bulk_s2g((void*)(z2s + rb * B_SLOT), sb + OFF_A, B_SLOT);
        bulk_commit_wait();
        mbar_arrive(sb + BAR_ZP);
        STAMPE(58);
        red_release(p.scr->cnt + CNT_Z);
      }
      __syncwarp();
      STAMP(28);
      {
        uint32_t tp = clock();
#pragma unroll 1
        for (int i = 1; i < 16; i++) {
          pace(tp, PF_D);
          prefetch_l2(wq + i * 256);
          if (i == LKI) bar_sync(NB_KL, 160);
          if ((i == LKI || i == LKI + 1) && elect_one()) {
            kv_store(p, sb + OFF_A + 8 * A_SLOT + (i - LKI) * 4096, rb * 2 + (cb & 1), (cb >> 1) * 5 + 3 + i - LKI);
            bulk_commit_wait();
            if (i > LKI) red_relaxed(p.scr->cnt + CNT_KV + 2 + (cb >> 1));
          }
          __syncwarp();
          if (i == LKI + 1) STAMP(59);
        }
      }
      if (!EARLY) poll_counter(p.scr->cnt + CNT_KV + 2 + (cb >> 1), tag * 64);
      if (elect_one()) mbar_arrive(sb + BAR_KV2);
      STAMP(34);
      const uint8_t* hs = p.scr->h + (size_t)rb * 12 * A_SLOT;
#pragma unroll 1
      for (int i = 0; i < 3; i++) {
        mbar_wait(sb + BAR_HR - 16 + 8 * i, 0);
        if (elect_one()) bulk_s2g((void*)(hs + (cb * 3 + i) * A_SLOT), sb + OFF_A + i * A_SLOT, A_SLOT);
      }
      if (elect_one()) {
        st_relaxed(&p.scr->hflag[rb * 32 + cb * 8], tag);
        bulk_commit_wait();
        mbar_arrive(sb + BAR_ZP);
      }
      __syncwarp();
      STAMP(20);
      if (!EARLY) poll_flags4(p.scr->hflag + rb * 32, tag, lane);
      { uint32_t tp = clock(); pace<false>(tp, HD); }
      STAMP(37);
#pragma unroll 1
      for (int it = 3; it < 12; it++) {
        const int s = it < 9 ? it : it - 9;
        if (it == 9) bar_sync(NB_PC, 288);
        if (elect_one()) { mbar_expect(sb + BAR_AF + 8 * s, A_SLOT); bulk_g2s(sb + OFF_A + s * A_SLOT, hs + g3_block(cb, it) * A_SLOT, A_SLOT, sb + BAR_AF + 8 * s); }
      }
      STAMP(21);
    } else if (warp == 14) {
      const uint32_t tag = load_epoch(p, lin, lane) + 1;
      const int tb = rb * 2 + (cb & 1), u0 = (cb >> 1) * 5;
      const uint32_t ks = sb + OFF_CV + CV_SZ, par = __shfl_sync(0xffffffff, tag, 0);
      {
        uint32_t tp = tstart;
        pace(tp, TP_T);
        const char* q = (const char*)p.ssmk + chb * 4096 + lane * 128;
        prefetch_l2(q); prefetch_l2(q + 64 * 4096);
      }
      mbar_wait2(sb + BAR_XS, 0, sb + BAR_ST, 0);
      bar_sync(NB_KU, 160);
      if (elect_one()) { kv_store(p, ks, tb, u0); kv_store(p, ks + 4096, tb, u0 + 1); bulk_commit_wait(); red_relaxed(p.scr->cnt + CNT_KV + (cb >> 1)); }
      __syncwarp();
      STAMP(35);
      bar_sync(NB_KU2, 160);
      if (elect_one()) { kv_store(p, ks + 8192, tb, u0 + 2); bulk_commit_wait(); }
      __syncwarp();
      zero_pads(ks, lane);
      bar_arrive(NB_G1D, 64);
      STAMP(30);
      {
        uint32_t tp = clock();
        const size_t o = (size_t)(tb * 32 + lane) * (kD * 2) + (u0 + 3) * 128;
        const char* r = (const char*)p.wout + (rb * 24 + min(lane, 23)) * (kD * 2) + cb * 320;
        const char* q = (const char*)p.ssmk + (chb + 128) * 4096 + lane * 128;
#pragma unroll 1
        for (int i = 0; i < 10; i++) {
          pace(tp, PF2_D);
          prefetch_l2(i < 3 ? q + i * 64 * 4096 : (i < 7 ? (const char*)((i & 1) ? p.k : p.v) + o + ((i - 3) >> 1) * 128 : r + (i - 7) * 128));
        }
      }
      conv_service(p, sb, 0, chb + 64, par, lane, NoHook());
      bar_sync(NB_CD, 64);
      STAMP(47);
      if (!EARLY) mbar_wait(sb + BAR_WE + 40, 0);
      { uint32_t tp = clock(); pace<false>(tp, YD); }
      if (elect_one()) {
        mbar_expect(sb + BAR_YT, 20480);
#pragma unroll 1
        for (int i = 0; i < 4; i++) tma2d(sb + OFF_CV + i * 5120, &p.tmY, rb * 64, cb * 160 + i * 40, sb + BAR_YT);
      }
      if (lane == 0) *(volatile uint32_t*)&p.scr->epoch[lin] = tag;
      STAMP(23);
    } else {
      const uint32_t tag = load_epoch(p, lin, lane) + 1;
      mbar_wait(sb + BAR_AF + 72, 0);
      { uint32_t tp = clock(); pace(tp, XSD); }
      {
        const uint32_t t8 = tag8(tag);
        const uint4 u = poll<false>([&]() { return ld_ll4(&p.scr->xstat[rb * 64 + lane * 2]); },
                                                [&](const uint4& v) { return (((v.x ^ t8) | (v.y ^ t8) | (v.z ^ t8) | (v.w ^ t8)) & 255u) == 0; });
        sts128(sb + OFF_XS + lane * 16, u.x, u.y, u.z, u.w);
      }
      __syncwarp();
      if (lane == 0) mbar_arrive(sb + BAR_XS);
      STAMP(25);
      const uint32_t par = __shfl_sync(0xffffffff, tag, 0);
      bar_sync(NB_G1D, 64);
      if (!EARLY) poll_counter(p.scr->cnt + CNT_KV + (cb >> 1), tag * 64);
      convx_issue(p, sb, 1, chb);
      convx_issue(p, sb, 0, chb + 64);
#pragma unroll 1
      for (int h = 1; h >= 0; h--) convx_finish(p, sb, h, chb + 64 - 64 * h, 0, par, lane);
      STAMP(48);
      gather_colsum(p, sb, 1, cb, tag8(tag), lane);
      STAMP(38);
      conv_service(p, sb, 1, chb, par, lane, [&]() {
        bar_sync(NB_WO, 160);
        if (elect_one()) red_release(p.scr->cnt + CNT_WO + cb);
        STAMP(49);
        poll_counter(p.scr->cnt + CNT_WO + cb, tag * 32);
        if (elect_one()) mbar_arrive(sb + BAR_WO);
        STAMP(46);
      });
      bar_arrive(NB_CD, 64);
    }
  } else if (warp >= 8) {
    const int w = warp & 3;
    {
      const int tid = tid_now();
      uint2* xs = &p.scr->xstat[rb * 64 + cb * 16 + (tid >> 3)];
      if ((tid & 7) == 0) st_ll2(xs, 0, 0);
      const uint32_t epoch = load_epoch(p, lin, lane);
      float sa[4] = {0.f, 0.f, 0.f, 0.f}, qa[4] = {0.f, 0.f, 0.f, 0.f};
#pragma unroll 1
      for (int i = 0; i < 10; i++) {
        mbar_wait(sb + BAR_AF + 8 * i, 0);
        const uint4 x4 = lds128(sb + OFF_A + i * A_SLOT + cb * 2048 + tid * 16);
        const uint32_t u[4] = {x4.x, x4.y, x4.z, x4.w};
#pragma unroll
        for (int e = 0; e < 4; e++) { const float a = bf_lo(u[e]), c = bf_hi(u[e]); sa[e] += a + c; qa[e] = fmaf(a, a, fmaf(c, c, qa[e])); }
      }
      float s = (sa[0] + sa[1]) + (sa[2] + sa[3]), q = (qa[0] + qa[1]) + (qa[2] + qa[3]);
#pragma unroll
      for (int o = 1; o <= 4; o <<= 1) { s += __shfl_xor_sync(0xffffffff, s, o); q += __shfl_xor_sync(0xffffffff, q, o); }
      const float m = s * (1.f / kD);
      const float r = rsqrtf(fmaxf(fmaf(-m, m, q * (1.f / kD)), 0.f) + 1e-5f);
      if ((tid & 7) == 0) st_ll2(xs, tagged(m, tag8(epoch + 1)), tagged(r, tag8(epoch + 1)));
      STAMPW(12); TR(70);
      fence_async_smem();
    }
    asm volatile("setmaxnreg.inc.sync.aligned.u32 160;");
    const unsigned short* bp = (const unsigned short*)p.bsp + rb * 64 + w * 16 + (lane >> 2);
    const uint32_t bias = bp[0] | ((uint32_t)bp[8] << 16);
    float d[96];
    uint32_t z[48];
    {
      const uint64_t db = mkdesc(sb + OFF_B, 8192, 1024, 1);
#pragma unroll
      for (int i = 0; i < 96; i++) d[i] = 0.f;
      bar_sync(NB_G1, 256);
      TR(71);
      gemm_seg<192, 3>(d, sb, db, 0, 10, 0, 0, tid_now() == 0, 0 TSA);
      mbar_arrive_if(sb + BAR_YT, tid_now() == 0);
      STAMPW(14); TR(74);
      mbar_wait2(sb + BAR_XS, 0, sb + BAR_ST + 8, 0);
      const uint32_t xa1 = sb + OFF_XS + (w * 16 + (lane >> 2)) * 8;
      gelu_tile<false>(d, z, nullptr, sb + OFF_CS + (lane & 3) * 8, lds64f(xa1), lds64f(xa1 + 64), sb + BAR_XS);
    }
#pragma unroll
    for (int j = 0; j < 96; j++) d[j] = (j & 2) ? bf_hi(bias) : bf_lo(bias);
    STAMPW(15); TR(76);
    gemm_seg<192, 1>(d, sb, mkdesc(sb + OFF_B, 8192, 1024, 1), 0, 32, 0, 0, tid_now() == 0, 1 TSA);
    STAMPW(16); TR(77);
    {
      const int l2 = tid_now() & 31;
      const uint32_t ha = swz_base(sb + OFF_A, w, l2);
      const bool tg = (l2 & 3) == (l2 >> 3);
      const uint32_t tm = tg ? ~1u : ~0u, tb = tg ? lds32<0>(sb + OFF_TAG) & 1 : 0;
#pragma unroll
      for (int j = 0; j < 24; j += 2) {
#pragma unroll
        for (int e = 0; e < 4; e++) z[2 * j + e] = hmul2(z[2 * j + e], pack2(d[4 * j + 2 * e], d[4 * j + 2 * e + 1]));
        stsm4((ha ^ ((j & 7) * 16)) + (j >> 3) * A_SLOT, (z[2 * j] & tm) | tb, (z[2 * j + 1] & tm) | tb, z[2 * j + 2], z[2 * j + 3]);
        if ((j & 7) == 6) {
          fence_async_smem();
          __syncwarp();
          mbar_arrive_if(sb + BAR_HR - 16 + (j >> 3) * 8, l2 == 0);
        }
      }
    }
    STAMPW(17); TR(78);
    const int t3 = tid_now();
    {
      mbar_wait(sb + BAR_HR, 0);
      gemm_seg<160, 4>(d, sb, mkdesc(sb + OFF_B, 2560, 128, 0), 0, 3, 0, 0, t3 == 0, 0 TSA);
      TR(79);
      bar_sync(NB_C, 128);
      mbar_wait(sb + BAR_ZP, 1);
#pragma unroll
      for (int j = 0; j < 10; j++)
        sts128(sb + OFF_A + j * 2048 + t3 * 16, pack2(d[8 * j], d[8 * j + 1]), pack2(d[8 * j + 2], d[8 * j + 3]), pack2(d[8 * j + 4], d[8 * j + 5]),
               pack2(d[8 * j + 6], d[8 * j + 7]));
      bar_sync(NB_C, 128);
      mbar_arrive_if(sb + BAR_PART, t3 == 0);
      STAMPW(45); TR(80);
    }
    {
      const uint32_t par = __shfl_sync(0xffffffff, lds32<0>(sb + OFF_TAG), 0), a = sb + OFF_A + w * 2048 + val_off(t3 & 31);
      const uint8_t* hs = p.scr->h + (size_t)rb * 12 * A_SLOT + w * 2048;
      const uint32_t rt = sb + OFF_RT + 8 * w;
#pragma unroll 1
      for (int it = 3; it < 12; it++) {
        const int s = it < 9 ? it : it - 9;
        mbar_wait(sb + BAR_AF + 8 * s, 1);
        validate<2>(a + s * A_SLOT, par, rt, [&]() { bulk_g2s(sb + OFF_A + s * A_SLOT + w * 2048, hs + g3_block(cb, it) * A_SLOT, 2048, rt); });
        if (elect_one()) mbar_arrive(sb + BAR_HV + 8 * (it - 3));
        if (it == 3) STAMPW(26);
      }
      {
        const int l = t3 & 31;
        mbar_wait(sb + BAR_YT, 1);
        validate<5>(sb + OFF_CV + w * 5120 + (l >> 2) * 128 + ((2 * (l & 3)) ^ (l >> 2)) * 16, par, rt, [&]() { tma2d(sb + OFF_CV + w * 5120, &p.tmY, rb * 64, cb * 160 + w * 40, rt); });
        bar_sync(NB_C, 128);
        mbar_arrive_if(sb + BAR_PART, t3 == 0);
        STAMPW(57);
      }
    }
  } else {
    const int h = warp >> 2, w = warp & 3;
    Taps k;
    asm volatile("setmaxnreg.inc.sync.aligned.u32 160;");
    if (h == 0) {
      uint4* zs = &p.scr->zstat[rb * 128 + w * 8 + (lane >> 2)];
      if ((lane & 3) == 0) st_ll4(zs + cb * 32, 0, 0, 0, 0);
      float d[96];
      uint32_t z[48];
#pragma unroll
      for (int i = 0; i < 96; i++) d[i] = 0.f;
      gemm_seg<192, 0>(d, sb, mkdesc(sb + OFF_B, 8192, 1024, 1), 0, 10, 0, 0, tid_now() == 0, 0 TSA, [&]() { bar_arrive(NB_G1, 256); });
      STAMPW(1); TR(0);
      const int tid = tid_now(), lane = tid & 31, g = lane >> 2, t = lane & 3;
      mbar_wait2(sb + BAR_XS, 0, sb + BAR_ST, 0);
      STAMPW(52); TR(1);
      const uint32_t xa1 = sb + OFF_XS + (w * 16 + g) * 8;
      const uint32_t tag = lds32<0>(sb + OFF_TAG);
      const float2 s0 = lds64f(xa1), s1 = lds64f(xa1 + 64);
      float st[4];
      gelu_tile<true>(d, z, st, sb + OFF_CS + 768 + t * 8, s0, s1, 0);
      TR(2);
      float2 sq = quad_sum(st, t);
      if (t < 2) st_ll2((uint2*)(zs + cb * 32) + t, tagged(sq.x, tag), __float_as_uint(sq.y));
      STAMPW(2); TR(3);
      { uint32_t tp = clock(); pace<false>(tp, ZW); }
      const uint4 u = poll<false>([&]() { return ld_ll4(zs + t * 32); }, [&](const uint4& v) { return (((v.x ^ tag) | (v.z ^ tag)) & 255u) == 0; });
      STAMPW(3); TR(10);
      st[0] = __uint_as_float(u.x); st[1] = __uint_as_float(u.y); st[2] = __uint_as_float(u.z); st[3] = __uint_as_float(u.w);
      sq = quad_sum(st, t);
      const float ca = 0.5f * ((t & 1) ? s1.y : s0.y), ma = sq.x * (1.f / 768.f);
      const float ra = ca * rsqrtf(fmaf(fmaxf(fmaf(-ma, ma, sq.y * (1.f / 768.f)), 0.f), ca * ca, 1e-5f));
      const uint32_t r2 = pack2(ra, ra);
      const float na = -ma * bf_lo(r2);
      const uint32_t n2 = pack2(na, na), r2o = __shfl_xor_sync(0xffffffff, r2, 1), n2o = __shfl_xor_sync(0xffffffff, n2, 1);
      const uint32_t fr[2] = {(t & 1) ? r2o : r2, (t & 1) ? r2 : r2o}, fn[2] = {(t & 1) ? n2o : n2, (t & 1) ? n2 : n2o};
      const uint32_t za = swz_base(sb + OFF_A, w, lane);
      TR(11);
      mbar_wait(sb + BAR_AE + 16, 0);
      TR(12);
#pragma unroll
      for (int j = 0; j < 24; j += 2)
        stsm4((za ^ ((j & 7) * 16)) + (j >> 3) * A_SLOT, hfma2(z[2 * j], fr[0], fn[0]), hfma2(z[2 * j + 1], fr[1], fn[1]), hfma2(z[2 * j + 2], fr[0], fn[0]), hfma2(z[2 * j + 3], fr[1], fn[1]));
      TR(14);
      fence_async_smem();
      bar_arrive(NB_Z, 160);
      STAMPW(4); TR(15);
      load_taps(k, p, chb + 64, tid);
    } else {
      if (w == 0) zero_pads(sb + OFF_CV, lane);
      const uint32_t epoch = load_epoch(p, lin, lane);
      const int t0 = (rb * 2 + (cb & 1)) * 32 + w * 8, c0 = (cb >> 1) * 320 + lane * 2;
      const __nv_bfloat16* kp = p.k + (size_t)(t0 - 3) * kD + c0;
      const __nv_bfloat16* vp = p.v + (size_t)t0 * kD + c0;
      const __nv_bfloat16* sp = p.shift + c0 * 4;
      const uint32_t oa = sb + OFF_CV + CV_SZ + kv_stage_addr(w, lane);
      bar_sync(NB_KF, 160);
      uint32_t tp = tstart;
      pace(tp, KV_T0);
      KvRegs n0, n1;
      uint32_t o[8];
      kv_load(n0, kp, vp, sp, t0 > 0);
      kv_load(n1, kp + 64, vp + 64, sp + 256, t0 > 0);
      const uint32_t tm = w >= 2 ? ~1u : ~0u, tb = w >= 2 ? (epoch + 1) & 1 : 0;
      kv_calc(n0, o);
      kv_put(o, oa, tm, tb);
      kv_calc(n1, o);
      kv_put(o, oa + 4096, tm, tb);
      fence_async_smem();
      bar_arrive(NB_KU, 160);
      TR(0);
      pace(tp, KV2T);
      kv_load(n0, kp + 128, vp + 128, sp + 512, t0 > 0);
      load_taps(k, p, chb, tid_now());
      kv_calc(n0, o);
      kv_put(o, oa + 8192, tm, tb);
      fence_async_smem();
      bar_arrive(NB_KU2, 160);
      STAMPW(13); TR(1);
    }
    {
      const int tid = tid_now();
      conv_worker(p, k, sb, h, chb + 64 - 64 * h, w, tid & 31, tid, rb, cb TSA);
    }
    float d[40];
    const int t3 = tid_now();
    const uint32_t o0 = (rb * 64 + w * 16 + ((t3 & 31) >> 2)) * kD + cb * 160 + h * 80;
    float cf[2];
    uint32_t xw[2][10], rn[4];
    const uint32_t xs_addr = sb + OFF_XS + (w * 16 + ((t3 & 31) >> 2)) * 8;
    TR(60);
    mbar_wait(sb + BAR_PART, 0);
    TR(61);
#pragma unroll
    for (int j = 0; j < 5; j++) {
      const uint4 v = lds128(sb + OFF_A + (h * 5 + j) * 2048 + t3 * 16);
      d[8 * j] = bf_lo(v.x); d[8 * j + 1] = bf_hi(v.x); d[8 * j + 2] = bf_lo(v.y); d[8 * j + 3] = bf_hi(v.y);
      d[8 * j + 4] = bf_lo(v.z); d[8 * j + 5] = bf_hi(v.z); d[8 * j + 6] = bf_lo(v.w); d[8 * j + 7] = bf_hi(v.w);
    }
    fence_async_smem();
    bar_arrive(NB_PC, 288);
    TR(62);
    gemm_seg<80, 2>(d, sb, mkdesc(sb + OFF_B + h * 1280, 2560, 128, 0), 3, 12, 3, 0, t3 == 0, 1 TSA, NoHook(), [&]() {
      final_load_x(xw, p.x + o0, t3 & 3);
      const float2 s0 = lds64f(xs_addr), s1 = lds64f(xs_addr + 64);
      cf[0] = 0.25f * s0.y; cf[1] = 0.25f * s1.y;
      rn[0] = pack2(s0.y, s0.y); rn[1] = pack2(s1.y, s1.y);
      rn[2] = pack2(-s0.x * bf_lo(rn[0]), -s0.x * bf_lo(rn[0])); rn[3] = pack2(-s1.x * bf_lo(rn[1]), -s1.x * bf_lo(rn[1]));
    });
    STAMPW(h ? 18 : 10);
    TR(63);
    const int l3 = tid_now() & 31;
    final_out(d, xw, rn, cf, sb + OFF_CV + h * 10240, p.out + o0, w, l3, [&]() {
      STAMPW(h ? 44 : 9);
      TR(64);
      mbar_wait(sb + BAR_PART, 1);
      TR(65);
    });
    TR(66);
    mbar_arrive_if(sb + BAR_WE, t3 == 0);
  }
}

typedef CUresult (*EncodeFn)(CUtensorMap*, CUtensorMapDataType, cuuint32_t, void*, const cuuint64_t*, const cuuint64_t*, const cuuint32_t*,
                             const cuuint32_t*, CUtensorMapInterleave, CUtensorMapSwizzle, CUtensorMapL2promotion, CUtensorMapFloatOOBfill);

void encode(EncodeFn fn, CUtensorMap* m, const void* ptr, int rank, const cuuint64_t* dims, const cuuint64_t* strides, const cuuint32_t* box,
            CUtensorMapSwizzle swz = CU_TENSOR_MAP_SWIZZLE_128B) {
  const cuuint32_t es[3] = {1, 1, 1};
  fn(m, CU_TENSOR_MAP_DATA_TYPE_BFLOAT16, rank, const_cast<void*>(ptr), dims, strides, box, es, CU_TENSOR_MAP_INTERLEAVE_NONE,
     swz, CU_TENSOR_MAP_L2_PROMOTION_L2_128B, CU_TENSOR_MAP_FLOAT_OOB_FILL_NONE);
}

}

extern "C" void kernel_launch(void* const* d_in, const int* in_sizes, int n_in, void* d_out, int out_size) {
  (void)in_sizes; (void)n_in; (void)out_size;
  static EncodeFn enc = nullptr;
  static Scratch* scr = nullptr;
  static int sms = 0;
  if (!enc) {
    void* fn = nullptr;
    cudaDriverEntryPointQueryResult qr;
    cudaGetDriverEntryPoint("cuTensorMapEncodeTiled", &fn, cudaEnableDefault, &qr);
    enc = (EncodeFn)fn;
    cudaFuncSetAttribute(fused_kernel, cudaFuncAttributeMaxDynamicSharedMemorySize, SMEM_BYTES);
    cudaGetSymbolAddress((void**)&scr, g_scr);
    int dev = 0;
    cudaGetDevice(&dev);
    cudaDeviceGetAttribute(&sms, cudaDevAttrMultiProcessorCount, dev);
  }
  Params p;
  p.scr = scr;
  p.by_smid = sms == 132;
  for (int b = 0; b < 132; b++) {
    const int tp = b >> 1, t7 = (tp - 32) / 7;
    const int lin = tp < 32 ? ((tp & 7) ? (tp & 7) * 16 : 8) + (tp >> 3) * 2 + (b & 1)
                            : (tp < 60 ? (tp - 31 - t7 * 7) * 16 + 8 + t7 * 2 + (b & 1) : (tp < 62 ? 128 + (b & 3) : b - 124));
    const int cb = ((lin >> 4) & 1) * 2 + (lin & 1), rb = (lin >> 5) * 8 + ((lin >> 1) & 7);
    p.job[b] = lin < 128 ? lin | cb << 8 | rb << 10 : lin | (lin & 3) << 8;
  }
  p.x = (const __nv_bfloat16*)d_in[0];
  p.k = (const __nv_bfloat16*)d_in[1];
  p.v = (const __nv_bfloat16*)d_in[2];
  p.shift = (const __nv_bfloat16*)d_in[3];
  p.ssmk = (const __nv_bfloat16*)d_in[4];
  p.ssmD = (const __nv_bfloat16*)d_in[5];
  p.wsp = (const __nv_bfloat16*)d_in[8];
  p.bsp = (const __nv_bfloat16*)d_in[9];
  p.wout = (const __nv_bfloat16*)d_in[10];
  p.out = (__nv_bfloat16*)d_out;
  {
    const cuuint64_t dims[2] = {kD, kS}, st[1] = {kD * 2};
    const cuuint32_t box[2] = {64, 64};
    encode(enc, &p.tmX, d_in[0], 2, dims, st, box);
  }
  {
    const cuuint64_t dims[3] = {64, kD, kF / 64}, st[2] = {kF * 2, 128};
    const cuuint32_t box[3] = {64, 64, 3};
    encode(enc, &p.tmW, d_in[7], 3, dims, st, box);
  }
  {
    const cuuint64_t dims[2] = {kS, kS}, st[1] = {kS * 2};
    const cuuint32_t box[2] = {64, 64};
    encode(enc, &p.tmWsp, d_in[8], 2, dims, st, box);
  }
  {
    const cuuint64_t dims[2] = {kS, kD}, st[1] = {kS * 2};
    const cuuint32_t box[2] = {64, 40};
    encode(enc, &p.tmY, scr->y, 2, dims, st, box);
  }
  {
    const cuuint64_t dims[3] = {1024, kD / 2, 4}, st[2] = {8192, 2048};
    const cuuint32_t box[3] = {16, 32, 4};
    encode(enc, &p.tmKV, scr->kvx, 3, dims, st, box, CU_TENSOR_MAP_SWIZZLE_32B);
  }
  fused_kernel<<<132, 512, SMEM_BYTES, cudaStreamPerThread>>>(p);
}
```

```cpp
#include <cuda_runtime.h>
#include <cuda.h>
#include <cuda_bf16.h>
#include <stdint.h>

template <int N> struct WG;
template <> struct WG<16> {
  static __device__ __forceinline__ void rs(float* d, const uint32_t* a, uint64_t db) {
    asm volatile("{\n.reg .pred p;\nsetp.ne.b32 p, 1, 0;\nwgmma.mma_async.sync.aligned.m64n16k16.f32.bf16.bf16 {"
      "%0, %1, %2, %3, %4, %5, %6, %7"
      "}, {%8, %9, %10, %11}, %12, p, 1, 1, 0;\n}\n"
      :
      "+f"(d[0]), "+f"(d[1]), "+f"(d[2]), "+f"(d[3]), "+f"(d[4]), "+f"(d[5]), "+f"(d[6]), "+f"(d[7])
      : "r"(a[0]), "r"(a[1]), "r"(a[2]), "r"(a[3]), "l"(db));
  }
};
template <> struct WG<32> {
  static __device__ __forceinline__ void rs(float* d, const uint32_t* a, uint64_t db) {
    asm volatile("{\n.reg .pred p;\nsetp.ne.b32 p, 1, 0;\nwgmma.mma_async.sync.aligned.m64n32k16.f32.bf16.bf16 {"
      "%0, %1, %2, %3, %4, %5, %6, %7, %8, %9, %10, %11, %12, %13, %14, %15"
      "}, {%16, %17, %18, %19}, %20, p, 1, 1, 0;\n}\n"
      :
      "+f"(d[0]), "+f"(d[1]), "+f"(d[2]), "+f"(d[3]), "+f"(d[4]), "+f"(d[5]), "+f"(d[6]), "+f"(d[7]),
      "+f"(d[8]), "+f"(d[9]), "+f"(d[10]), "+f"(d[11]), "+f"(d[12]), "+f"(d[13]), "+f"(d[14]), "+f"(d[15])
      : "r"(a[0]), "r"(a[1]), "r"(a[2]), "r"(a[3]), "l"(db));
  }
};
template <> struct WG<48> {
  static __device__ __forceinline__ void rs(float* d, const uint32_t* a, uint64_t db) {
    asm volatile("{\n.reg .pred p;\nsetp.ne.b32 p, 1, 0;\nwgmma.mma_async.sync.aligned.m64n48k16.f32.bf16.bf16 {"
      "%0, %1, %2, %3, %4, %5, %6, %7, %8, %9, %10, %11, %12, %13, %14, %15, "
      "%16, %17, %18, %19, %20, %21, %22, %23"
      "}, {%24, %25, %26, %27}, %28, p, 1, 1, 0;\n}\n"
      :
      "+f"(d[0]), "+f"(d[1]), "+f"(d[2]), "+f"(d[3]), "+f"(d[4]), "+f"(d[5]), "+f"(d[6]), "+f"(d[7]),
      "+f"(d[8]), "+f"(d[9]), "+f"(d[10]), "+f"(d[11]), "+f"(d[12]), "+f"(d[13]), "+f"(d[14]), "+f"(d[15]),
      "+f"(d[16]), "+f"(d[17]), "+f"(d[18]), "+f"(d[19]), "+f"(d[20]), "+f"(d[21]), "+f"(d[22]), "+f"(d[23])
      : "r"(a[0]), "r"(a[1]), "r"(a[2]), "r"(a[3]), "l"(db));
  }
};
template <> struct WG<64> {
  static __device__ __forceinline__ void rs(float* d, const uint32_t* a, uint64_t db) {
    asm volatile("{\n.reg .pred p;\nsetp.ne.b32 p, 1, 0;\nwgmma.mma_async.sync.aligned.m64n64k16.f32.bf16.bf16 {"
      "%0, %1, %2, %3, %4, %5, %6, %7, %8, %9, %10, %11, %12, %13, %14, %15, "
      "%16, %17, %18, %19, %20, %21, %22, %23, %24, %25, %26, %27, %28, %29, %30, %31"
      "}, {%32, %33, %34, %35}, %36, p, 1, 1, 0;\n}\n"
      :
      "+f"(d[0]), "+f"(d[1]), "+f"(d[2]), "+f"(d[3]), "+f"(d[4]), "+f"(d[5]), "+f"(d[6]), "+f"(d[7]),
      "+f"(d[8]), "+f"(d[9]), "+f"(d[10]), "+f"(d[11]), "+f"(d[12]), "+f"(d[13]), "+f"(d[14]), "+f"(d[15]),
      "+f"(d[16]), "+f"(d[17]), "+f"(d[18]), "+f"(d[19]), "+f"(d[20]), "+f"(d[21]), "+f"(d[22]), "+f"(d[23]),
      "+f"(d[24]), "+f"(d[25]), "+f"(d[26]), "+f"(d[27]), "+f"(d[28]), "+f"(d[29]), "+f"(d[30]), "+f"(d[31])
      : "r"(a[0]), "r"(a[1]), "r"(a[2]), "r"(a[3]), "l"(db));
  }
};
template <> struct WG<80> {
  static __device__ __forceinline__ void rs(float* d, const uint32_t* a, uint64_t db) {
    asm volatile("{\n.reg .pred p;\nsetp.ne.b32 p, 1, 0;\nwgmma.mma_async.sync.aligned.m64n80k16.f32.bf16.bf16 {"
      "%0, %1, %2, %3, %4, %5, %6, %7, %8, %9, %10, %11, %12, %13, %14, %15, "
      "%16, %17, %18, %19, %20, %21, %22, %23, %24, %25, %26, %27, %28, %29, %30, %31, "
      "%32, %33, %34, %35, %36, %37, %38, %39"
      "}, {%40, %41, %42, %43}, %44, p, 1, 1, 0;\n}\n"
      :
      "+f"(d[0]), "+f"(d[1]), "+f"(d[2]), "+f"(d[3]), "+f"(d[4]), "+f"(d[5]), "+f"(d[6]), "+f"(d[7]),
      "+f"(d[8]), "+f"(d[9]), "+f"(d[10]), "+f"(d[11]), "+f"(d[12]), "+f"(d[13]), "+f"(d[14]), "+f"(d[15]),
      "+f"(d[16]), "+f"(d[17]), "+f"(d[18]), "+f"(d[19]), "+f"(d[20]), "+f"(d[21]), "+f"(d[22]), "+f"(d[23]),
      "+f"(d[24]), "+f"(d[25]), "+f"(d[26]), "+f"(d[27]), "+f"(d[28]), "+f"(d[29]), "+f"(d[30]), "+f"(d[31]),
      "+f"(d[32]), "+f"(d[33]), "+f"(d[34]), "+f"(d[35]), "+f"(d[36]), "+f"(d[37]), "+f"(d[38]), "+f"(d[39])
      : "r"(a[0]), "r"(a[1]), "r"(a[2]), "r"(a[3]), "l"(db));
  }
};
template <> struct WG<96> {
  static __device__ __forceinline__ void rs(float* d, const uint32_t* a, uint64_t db) {
    asm volatile("{\n.reg .pred p;\nsetp.ne.b32 p, 1, 0;\nwgmma.mma_async.sync.aligned.m64n96k16.f32.bf16.bf16 {"
      "%0, %1, %2, %3, %4, %5, %6, %7, %8, %9, %10, %11, %12, %13, %14, %15, "
      "%16, %17, %18, %19, %20, %21, %22, %23, %24, %25, %26, %27, %28, %29, %30, %31, "
      "%32, %33, %34, %35, %36, %37, %38, %39, %40, %41, %42, %43, %44, %45, %46, %47"
      "}, {%48, %49, %50, %51}, %52, p, 1, 1, 0;\n}\n"
      :
      "+f"(d[0]), "+f"(d[1]), "+f"(d[2]), "+f"(d[3]), "+f"(d[4]), "+f"(d[5]), "+f"(d[6]), "+f"(d[7]),
      "+f"(d[8]), "+f"(d[9]), "+f"(d[10]), "+f"(d[11]), "+f"(d[12]), "+f"(d[13]), "+f"(d[14]), "+f"(d[15]),
      "+f"(d[16]), "+f"(d[17]), "+f"(d[18]), "+f"(d[19]), "+f"(d[20]), "+f"(d[21]), "+f"(d[22]), "+f"(d[23]),
      "+f"(d[24]), "+f"(d[25]), "+f"(d[26]), "+f"(d[27]), "+f"(d[28]), "+f"(d[29]), "+f"(d[30]), "+f"(d[31]),
      "+f"(d[32]), "+f"(d[33]), "+f"(d[34]), "+f"(d[35]), "+f"(d[36]), "+f"(d[37]), "+f"(d[38]), "+f"(d[39]),
      "+f"(d[40]), "+f"(d[41]), "+f"(d[42]), "+f"(d[43]), "+f"(d[44]), "+f"(d[45]), "+f"(d[46]), "+f"(d[47])
      : "r"(a[0]), "r"(a[1]), "r"(a[2]), "r"(a[3]), "l"(db));
  }
};
template <> struct WG<112> {
  static __device__ __forceinline__ void rs(float* d, const uint32_t* a, uint64_t db) {
    asm volatile("{\n.reg .pred p;\nsetp.ne.b32 p, 1, 0;\nwgmma.mma_async.sync.aligned.m64n112k16.f32.bf16.bf16 {"
      "%0, %1, %2, %3, %4, %5, %6, %7, %8, %9, %10, %11, %12, %13, %14, %15, "
      "%16, %17, %18, %19, %20, %21, %22, %23, %24, %25, %26, %27, %28, %29, %30, %31, "
      "%32, %33, %34, %35, %36, %37, %38, %39, %40, %41, %42, %43, %44, %45, %46, %47, "
      "%48, %49, %50, %51, %52, %53, %54, %55"
      "}, {%56, %57, %58, %59}, %60, p, 1, 1, 0;\n}\n"
      :
      "+f"(d[0]), "+f"(d[1]), "+f"(d[2]), "+f"(d[3]), "+f"(d[4]), "+f"(d[5]), "+f"(d[6]), "+f"(d[7]),
      "+f"(d[8]), "+f"(d[9]), "+f"(d[10]), "+f"(d[11]), "+f"(d[12]), "+f"(d[13]), "+f"(d[14]), "+f"(d[15]),
      "+f"(d[16]), "+f"(d[17]), "+f"(d[18]), "+f"(d[19]), "+f"(d[20]), "+f"(d[21]), "+f"(d[22]), "+f"(d[23]),
      "+f"(d[24]), "+f"(d[25]), "+f"(d[26]), "+f"(d[27]), "+f"(d[28]), "+f"(d[29]), "+f"(d[30]), "+f"(d[31]),
      "+f"(d[32]), "+f"(d[33]), "+f"(d[34]), "+f"(d[35]), "+f"(d[36]), "+f"(d[37]), "+f"(d[38]), "+f"(d[39]),
      "+f"(d[40]), "+f"(d[41]), "+f"(d[42]), "+f"(d[43]), "+f"(d[44]), "+f"(d[45]), "+f"(d[46]), "+f"(d[47]),
      "+f"(d[48]), "+f"(d[49]), "+f"(d[50]), "+f"(d[51]), "+f"(d[52]), "+f"(d[53]), "+f"(d[54]), "+f"(d[55])
      : "r"(a[0]), "r"(a[1]), "r"(a[2]), "r"(a[3]), "l"(db));
  }
};
template <> struct WG<128> {
  static __device__ __forceinline__ void rs(float* d, const uint32_t* a, uint64_t db) {
    asm volatile("{\n.reg .pred p;\nsetp.ne.b32 p, 1, 0;\nwgmma.mma_async.sync.aligned.m64n128k16.f32.bf16.bf16 {"
      "%0, %1, %2, %3, %4, %5, %6, %7, %8, %9, %10, %11, %12, %13, %14, %15, "
      "%16, %17, %18, %19, %20, %21, %22, %23, %24, %25, %26, %27, %28, %29, %30, %31, "
      "%32, %33, %34, %35, %36, %37, %38, %39, %40, %41, %42, %43, %44, %45, %46, %47, "
      "%48, %49, %50, %51, %52, %53, %54, %55, %56, %57, %58, %59, %60, %61, %62, %63"
      "}, {%64, %65, %66, %67}, %68, p, 1, 1, 0;\n}\n"
      :
      "+f"(d[0]), "+f"(d[1]), "+f"(d[2]), "+f"(d[3]), "+f"(d[4]), "+f"(d[5]), "+f"(d[6]), "+f"(d[7]),
      "+f"(d[8]), "+f"(d[9]), "+f"(d[10]), "+f"(d[11]), "+f"(d[12]), "+f"(d[13]), "+f"(d[14]), "+f"(d[15]),
      "+f"(d[16]), "+f"(d[17]), "+f"(d[18]), "+f"(d[19]), "+f"(d[20]), "+f"(d[21]), "+f"(d[22]), "+f"(d[23]),
      "+f"(d[24]), "+f"(d[25]), "+f"(d[26]), "+f"(d[27]), "+f"(d[28]), "+f"(d[29]), "+f"(d[30]), "+f"(d[31]),
      "+f"(d[32]), "+f"(d[33]), "+f"(d[34]), "+f"(d[35]), "+f"(d[36]), "+f"(d[37]), "+f"(d[38]), "+f"(d[39]),
      "+f"(d[40]), "+f"(d[41]), "+f"(d[42]), "+f"(d[43]), "+f"(d[44]), "+f"(d[45]), "+f"(d[46]), "+f"(d[47]),
      "+f"(d[48]), "+f"(d[49]), "+f"(d[50]), "+f"(d[51]), "+f"(d[52]), "+f"(d[53]), "+f"(d[54]), "+f"(d[55]),
      "+f"(d[56]), "+f"(d[57]), "+f"(d[58]), "+f"(d[59]), "+f"(d[60]), "+f"(d[61]), "+f"(d[62]), "+f"(d[63])
      : "r"(a[0]), "r"(a[1]), "r"(a[2]), "r"(a[3]), "l"(db));
  }
};
template <int N> struct KB;
template <> struct KB<80> {
  template <int W, int RC, int RA, int BSTEP> static __device__ __forceinline__ void run(float* d, uint64_t da, uint64_t db, uint32_t rel, uint32_t rela, uint32_t doR, uint32_t fa, uint32_t pa, uint32_t fb, uint32_t pb, uint32_t acc) {
    if constexpr (W == 0 && RC == 1 && RA == 0) asm volatile(
    "{\n.reg .pred p, q, r, t;\n.reg .b64 a, b;\n.reg .u32 n;\nsetp.ne.b32 t, 1, 0;\nsetp.ne.b32 r, %49, 0;\n"
    "wgmma.mma_async.sync.aligned.m64n80k16.f32.bf16.bf16 {"
      "%0, %1, %2, %3, %4, %5, %6, %7, %8, %9, %10, %11, %12, %13, %14, %15, "
      "%16, %17, %18, %19, %20, %21, %22, %23, %24, %25, %26, %27, %28, %29, %30, %31, "
      "%32, %33, %34, %35, %36, %37, %38, %39"
      "}, %40, %41, r, 1, 1, 0, 1;\n"
    "add.u64 a, %40, 2;\nadd.u64 b, %41, %48;\n"
    "wgmma.mma_async.sync.aligned.m64n80k16.f32.bf16.bf16 {"
      "%0, %1, %2, %3, %4, %5, %6, %7, %8, %9, %10, %11, %12, %13, %14, %15, "
      "%16, %17, %18, %19, %20, %21, %22, %23, %24, %25, %26, %27, %28, %29, %30, %31, "
      "%32, %33, %34, %35, %36, %37, %38, %39"
      "}, a, b, t, 1, 1, 0, 1;\n"
    "wgmma.commit_group.sync.aligned;\nwgmma.wait_group.sync.aligned 1;\n"
    "add.u64 a, %40, 4;\nadd.u64 b, %41, 2*%48;\n"
    "wgmma.mma_async.sync.aligned.m64n80k16.f32.bf16.bf16 {"
      "%0, %1, %2, %3, %4, %5, %6, %7, %8, %9, %10, %11, %12, %13, %14, %15, "
      "%16, %17, %18, %19, %20, %21, %22, %23, %24, %25, %26, %27, %28, %29, %30, %31, "
      "%32, %33, %34, %35, %36, %37, %38, %39"
      "}, a, b, t, 1, 1, 0, 1;\n"
    "setp.ne.u32 q, %43, 0;\n@q mbarrier.arrive.shared::cta.b64 _, [%42];\n"
    "add.u64 a, %40, 6;\nadd.u64 b, %41, 3*%48;\n"
    "wgmma.mma_async.sync.aligned.m64n80k16.f32.bf16.bf16 {"
      "%0, %1, %2, %3, %4, %5, %6, %7, %8, %9, %10, %11, %12, %13, %14, %15, "
      "%16, %17, %18, %19, %20, %21, %22, %23, %24, %25, %26, %27, %28, %29, %30, %31, "
      "%32, %33, %34, %35, %36, %37, %38, %39"
      "}, a, b, t, 1, 1, 0, 1;\n"
    "wgmma.commit_group.sync.aligned;\n"
    "}\n"
      :
      "+f"(d[0]), "+f"(d[1]), "+f"(d[2]), "+f"(d[3]), "+f"(d[4]), "+f"(d[5]), "+f"(d[6]), "+f"(d[7]),
      "+f"(d[8]), "+f"(d[9]), "+f"(d[10]), "+f"(d[11]), "+f"(d[12]), "+f"(d[13]), "+f"(d[14]), "+f"(d[15]),
      "+f"(d[16]), "+f"(d[17]), "+f"(d[18]), "+f"(d[19]), "+f"(d[20]), "+f"(d[21]), "+f"(d[22]), "+f"(d[23]),
      "+f"(d[24]), "+f"(d[25]), "+f"(d[26]), "+f"(d[27]), "+f"(d[28]), "+f"(d[29]), "+f"(d[30]), "+f"(d[31]),
      "+f"(d[32]), "+f"(d[33]), "+f"(d[34]), "+f"(d[35]), "+f"(d[36]), "+f"(d[37]), "+f"(d[38]), "+f"(d[39])
      : "l"(da), "l"(db), "r"(rel), "r"(doR), "r"(fa), "r"(pa), "r"(fb), "r"(pb), "n"(BSTEP), "r"(acc), "r"(rela) : "memory");
    else if constexpr (W == 0 && RC == 1 && RA == 1) asm volatile(
    "{\n.reg .pred p, q, r, t;\n.reg .b64 a, b;\n.reg .u32 n;\nsetp.ne.b32 t, 1, 0;\nsetp.ne.b32 r, %49, 0;\n"
    "wgmma.mma_async.sync.aligned.m64n80k16.f32.bf16.bf16 {"
      "%0, %1, %2, %3, %4, %5, %6, %7, %8, %9, %10, %11, %12, %13, %14, %15, "
      "%16, %17, %18, %19, %20, %21, %22, %23, %24, %25, %26, %27, %28, %29, %30, %31, "
      "%32, %33, %34, %35, %36, %37, %38, %39"
      "}, %40, %41, r, 1, 1, 0, 1;\n"
    "add.u64 a, %40, 2;\nadd.u64 b, %41, %48;\n"
    "wgmma.mma_async.sync.aligned.m64n80k16.f32.bf16.bf16 {"
      "%0, %1, %2, %3, %4, %5, %6, %7, %8, %9, %10, %11, %12, %13, %14, %15, "
      "%16, %17, %18, %19, %20, %21, %22, %23, %24, %25, %26, %27, %28, %29, %30, %31, "
      "%32, %33, %34, %35, %36, %37, %38, %39"
      "}, a, b, t, 1, 1, 0, 1;\n"
    "wgmma.commit_group.sync.aligned;\nwgmma.wait_group.sync.aligned 1;\n"
    "add.u64 a, %40, 4;\nadd.u64 b, %41, 2*%48;\n"
    "wgmma.mma_async.sync.aligned.m64n80k16.f32.bf16.bf16 {"
      "%0, %1, %2, %3, %4, %5, %6, %7, %8, %9, %10, %11, %12, %13, %14, %15, "
      "%16, %17, %18, %19, %20, %21, %22, %23, %24, %25, %26, %27, %28, %29, %30, %31, "
      "%32, %33, %34, %35, %36, %37, %38, %39"
      "}, a, b, t, 1, 1, 0, 1;\n"
    "setp.ne.u32 q, %43, 0;\n@q mbarrier.arrive.shared::cta.b64 _, [%42];\n@q mbarrier.arrive.shared::cta.b64 _, [%50];\n"
    "add.u64 a, %40, 6;\nadd.u64 b, %41, 3*%48;\n"
    "wgmma.mma_async.sync.aligned.m64n80k16.f32.bf16.bf16 {"
      "%0, %1, %2, %3, %4, %5, %6, %7, %8, %9, %10, %11, %12, %13, %14, %15, "
      "%16, %17, %18, %19, %20, %21, %22, %23, %24, %25, %26, %27, %28, %29, %30, %31, "
      "%32, %33, %34, %35, %36, %37, %38, %39"
      "}, a, b, t, 1, 1, 0, 1;\n"
    "wgmma.commit_group.sync.aligned;\n"
    "}\n"
      :
      "+f"(d[0]), "+f"(d[1]), "+f"(d[2]), "+f"(d[3]), "+f"(d[4]), "+f"(d[5]), "+f"(d[6]), "+f"(d[7]),
      "+f"(d[8]), "+f"(d[9]), "+f"(d[10]), "+f"(d[11]), "+f"(d[12]), "+f"(d[13]), "+f"(d[14]), "+f"(d[15]),
      "+f"(d[16]), "+f"(d[17]), "+f"(d[18]), "+f"(d[19]), "+f"(d[20]), "+f"(d[21]), "+f"(d[22]), "+f"(d[23]),
      "+f"(d[24]), "+f"(d[25]), "+f"(d[26]), "+f"(d[27]), "+f"(d[28]), "+f"(d[29]), "+f"(d[30]), "+f"(d[31]),
      "+f"(d[32]), "+f"(d[33]), "+f"(d[34]), "+f"(d[35]), "+f"(d[36]), "+f"(d[37]), "+f"(d[38]), "+f"(d[39])
      : "l"(da), "l"(db), "r"(rel), "r"(doR), "r"(fa), "r"(pa), "r"(fb), "r"(pb), "n"(BSTEP), "r"(acc), "r"(rela) : "memory");
    else if constexpr (W == 1 && RC == 1 && RA == 0) asm volatile(
    "{\n.reg .pred p, q, r, t;\n.reg .b64 a, b;\n.reg .u32 n;\nsetp.ne.b32 t, 1, 0;\nsetp.ne.b32 r, %49, 0;\n"
    "wgmma.mma_async.sync.aligned.m64n80k16.f32.bf16.bf16 {"
      "%0, %1, %2, %3, %4, %5, %6, %7, %8, %9, %10, %11, %12, %13, %14, %15, "
      "%16, %17, %18, %19, %20, %21, %22, %23, %24, %25, %26, %27, %28, %29, %30, %31, "
      "%32, %33, %34, %35, %36, %37, %38, %39"
      "}, %40, %41, r, 1, 1, 0, 1;\n"
    "add.u64 a, %40, 2;\nadd.u64 b, %41, %48;\n"
    "wgmma.mma_async.sync.aligned.m64n80k16.f32.bf16.bf16 {"
      "%0, %1, %2, %3, %4, %5, %6, %7, %8, %9, %10, %11, %12, %13, %14, %15, "
      "%16, %17, %18, %19, %20, %21, %22, %23, %24, %25, %26, %27, %28, %29, %30, %31, "
      "%32, %33, %34, %35, %36, %37, %38, %39"
      "}, a, b, t, 1, 1, 0, 1;\n"
    "wgmma.commit_group.sync.aligned;\nwgmma.wait_group.sync.aligned 1;\n"
    "add.u64 a, %40, 4;\nadd.u64 b, %41, 2*%48;\n"
    "wgmma.mma_async.sync.aligned.m64n80k16.f32.bf16.bf16 {"
      "%0, %1, %2, %3, %4, %5, %6, %7, %8, %9, %10, %11, %12, %13, %14, %15, "
      "%16, %17, %18, %19, %20, %21, %22, %23, %24, %25, %26, %27, %28, %29, %30, %31, "
      "%32, %33, %34, %35, %36, %37, %38, %39"
      "}, a, b, t, 1, 1, 0, 1;\n"
    "setp.ne.u32 q, %43, 0;\n@q mbarrier.arrive.shared::cta.b64 _, [%42];\n"
    "mbarrier.test_wait.parity.shared::cta.b64 p, [%46], %47;\n"
    "add.u64 a, %40, 6;\nadd.u64 b, %41, 3*%48;\n"
    "wgmma.mma_async.sync.aligned.m64n80k16.f32.bf16.bf16 {"
      "%0, %1, %2, %3, %4, %5, %6, %7, %8, %9, %10, %11, %12, %13, %14, %15, "
      "%16, %17, %18, %19, %20, %21, %22, %23, %24, %25, %26, %27, %28, %29, %30, %31, "
      "%32, %33, %34, %35, %36, %37, %38, %39"
      "}, a, b, t, 1, 1, 0, 1;\n"
    "wgmma.commit_group.sync.aligned;\n"
    "@p bra.uni DN;\nmov.u32 n, 0;\nWT: mbarrier.try_wait.parity.shared::cta.b64 p, [%46], %47;\n@p bra.uni DN;\nadd.u32 n, n, 1;\nsetp.lt.u32 p, n, 0x100000;\n@p bra.uni WT;\nDN:\n"
    "}\n"
      :
      "+f"(d[0]), "+f"(d[1]), "+f"(d[2]), "+f"(d[3]), "+f"(d[4]), "+f"(d[5]), "+f"(d[6]), "+f"(d[7]),
      "+f"(d[8]), "+f"(d[9]), "+f"(d[10]), "+f"(d[11]), "+f"(d[12]), "+f"(d[13]), "+f"(d[14]), "+f"(d[15]),
      "+f"(d[16]), "+f"(d[17]), "+f"(d[18]), "+f"(d[19]), "+f"(d[20]), "+f"(d[21]), "+f"(d[22]), "+f"(d[23]),
      "+f"(d[24]), "+f"(d[25]), "+f"(d[26]), "+f"(d[27]), "+f"(d[28]), "+f"(d[29]), "+f"(d[30]), "+f"(d[31]),
      "+f"(d[32]), "+f"(d[33]), "+f"(d[34]), "+f"(d[35]), "+f"(d[36]), "+f"(d[37]), "+f"(d[38]), "+f"(d[39])
      : "l"(da), "l"(db), "r"(rel), "r"(doR), "r"(fa), "r"(pa), "r"(fb), "r"(pb), "n"(BSTEP), "r"(acc), "r"(rela) : "memory");
    else if constexpr (W == 2 && RC == 1 && RA == 0) asm volatile(
    "{\n.reg .pred p, q, r, t;\n.reg .b64 a, b;\n.reg .u32 n;\nsetp.ne.b32 t, 1, 0;\nsetp.ne.b32 r, %49, 0;\n"
    "wgmma.mma_async.sync.aligned.m64n80k16.f32.bf16.bf16 {"
      "%0, %1, %2, %3, %4, %5, %6, %7, %8, %9, %10, %11, %12, %13, %14, %15, "
      "%16, %17, %18, %19, %20, %21, %22, %23, %24, %25, %26, %27, %28, %29, %30, %31, "
      "%32, %33, %34, %35, %36, %37, %38, %39"
      "}, %40, %41, r, 1, 1, 0, 1;\n"
    "add.u64 a, %40, 2;\nadd.u64 b, %41, %48;\n"
    "wgmma.mma_async.sync.aligned.m64n80k16.f32.bf16.bf16 {"
      "%0, %1, %2, %3, %4, %5, %6, %7, %8, %9, %10, %11, %12, %13, %14, %15, "
      "%16, %17, %18, %19, %20, %21, %22, %23, %24, %25, %26, %27, %28, %29, %30, %31, "
      "%32, %33, %34, %35, %36, %37, %38, %39"
      "}, a, b, t, 1, 1, 0, 1;\n"
    "wgmma.commit_group.sync.aligned;\nwgmma.wait_group.sync.aligned 1;\n"
    "add.u64 a, %40, 4;\nadd.u64 b, %41, 2*%48;\n"
    "wgmma.mma_async.sync.aligned.m64n80k16.f32.bf16.bf16 {"
      "%0, %1, %2, %3, %4, %5, %6, %7, %8, %9, %10, %11, %12, %13, %14, %15, "
      "%16, %17, %18, %19, %20, %21, %22, %23, %24, %25, %26, %27, %28, %29, %30, %31, "
      "%32, %33, %34, %35, %36, %37, %38, %39"
      "}, a, b, t, 1, 1, 0, 1;\n"
    "setp.ne.u32 q, %43, 0;\n@q mbarrier.arrive.shared::cta.b64 _, [%42];\n"
    "mbarrier.test_wait.parity.shared::cta.b64 p, [%46], %47;\n"
    "mbarrier.test_wait.parity.shared::cta.b64 r, [%44], %45;\nand.pred p, p, r;\n"
    "add.u64 a, %40, 6;\nadd.u64 b, %41, 3*%48;\n"
    "wgmma.mma_async.sync.aligned.m64n80k16.f32.bf16.bf16 {"
      "%0, %1, %2, %3, %4, %5, %6, %7, %8, %9, %10, %11, %12, %13, %14, %15, "
      "%16, %17, %18, %19, %20, %21, %22, %23, %24, %25, %26, %27, %28, %29, %30, %31, "
      "%32, %33, %34, %35, %36, %37, %38, %39"
      "}, a, b, t, 1, 1, 0, 1;\n"
    "wgmma.commit_group.sync.aligned;\n"
    "@p bra.uni DN;\nmov.u32 n, 0;\nWT: mbarrier.try_wait.parity.shared::cta.b64 p, [%46], %47;\nmbarrier.try_wait.parity.shared::cta.b64 r, [%44], %45;\nand.pred p, p, r;\n@p bra.uni DN;\nadd.u32 n, n, 1;\nsetp.lt.u32 p, n, 0x100000;\n@p bra.uni WT;\nDN:\n"
    "}\n"
      :
      "+f"(d[0]), "+f"(d[1]), "+f"(d[2]), "+f"(d[3]), "+f"(d[4]), "+f"(d[5]), "+f"(d[6]), "+f"(d[7]),
      "+f"(d[8]), "+f"(d[9]), "+f"(d[10]), "+f"(d[11]), "+f"(d[12]), "+f"(d[13]), "+f"(d[14]), "+f"(d[15]),
      "+f"(d[16]), "+f"(d[17]), "+f"(d[18]), "+f"(d[19]), "+f"(d[20]), "+f"(d[21]), "+f"(d[22]), "+f"(d[23]),
      "+f"(d[24]), "+f"(d[25]), "+f"(d[26]), "+f"(d[27]), "+f"(d[28]), "+f"(d[29]), "+f"(d[30]), "+f"(d[31]),
      "+f"(d[32]), "+f"(d[33]), "+f"(d[34]), "+f"(d[35]), "+f"(d[36]), "+f"(d[37]), "+f"(d[38]), "+f"(d[39])
      : "l"(da), "l"(db), "r"(rel), "r"(doR), "r"(fa), "r"(pa), "r"(fb), "r"(pb), "n"(BSTEP), "r"(acc), "r"(rela) : "memory");
    else if constexpr (W == 2 && RC == 1 && RA == 1) asm volatile(
    "{\n.reg .pred p, q, r, t;\n.reg .b64 a, b;\n.reg .u32 n;\nsetp.ne.b32 t, 1, 0;\nsetp.ne.b32 r, %49, 0;\n"
    "wgmma.mma_async.sync.aligned.m64n80k16.f32.bf16.bf16 {"
      "%0, %1, %2, %3, %4, %5, %6, %7, %8, %9, %10, %11, %12, %13, %14, %15, "
      "%16, %17, %18, %19, %20, %21, %22, %23, %24, %25, %26, %27, %28, %29, %30, %31, "
      "%32, %33, %34, %35, %36, %37, %38, %39"
      "}, %40, %41, r, 1, 1, 0, 1;\n"
    "add.u64 a, %40, 2;\nadd.u64 b, %41, %48;\n"
    "wgmma.mma_async.sync.aligned.m64n80k16.f32.bf16.bf16 {"
      "%0, %1, %2, %3, %4, %5, %6, %7, %8, %9, %10, %11, %12, %13, %14, %15, "
      "%16, %17, %18, %19, %20, %21, %22, %23, %24, %25, %26, %27, %28, %29, %30, %31, "
      "%32, %33, %34, %35, %36, %37, %38, %39"
      "}, a, b, t, 1, 1, 0, 1;\n"
    "wgmma.commit_group.sync.aligned;\nwgmma.wait_group.sync.aligned 1;\n"
    "add.u64 a, %40, 4;\nadd.u64 b, %41, 2*%48;\n"
    "wgmma.mma_async.sync.aligned.m64n80k16.f32.bf16.bf16 {"
      "%0, %1, %2, %3, %4, %5, %6, %7, %8, %9, %10, %11, %12, %13, %14, %15, "
      "%16, %17, %18, %19, %20, %21, %22, %23, %24, %25, %26, %27, %28, %29, %30, %31, "
      "%32, %33, %34, %35, %36, %37, %38, %39"
      "}, a, b, t, 1, 1, 0, 1;\n"
    "setp.ne.u32 q, %43, 0;\n@q mbarrier.arrive.shared::cta.b64 _, [%42];\n@q mbarrier.arrive.shared::cta.b64 _, [%50];\n"
    "mbarrier.test_wait.parity.shared::cta.b64 p, [%46], %47;\n"
    "mbarrier.test_wait.parity.shared::cta.b64 r, [%44], %45;\nand.pred p, p, r;\n"
    "add.u64 a, %40, 6;\nadd.u64 b, %41, 3*%48;\n"
    "wgmma.mma_async.sync.aligned.m64n80k16.f32.bf16.bf16 {"
      "%0, %1, %2, %3, %4, %5, %6, %7, %8, %9, %10, %11, %12, %13, %14, %15, "
      "%16, %17, %18, %19, %20, %21, %22, %23, %24, %25, %26, %27, %28, %29, %30, %31, "
      "%32, %33, %34, %35, %36, %37, %38, %39"
      "}, a, b, t, 1, 1, 0, 1;\n"
    "wgmma.commit_group.sync.aligned;\n"
    "@p bra.uni DN;\nmov.u32 n, 0;\nWT: mbarrier.try_wait.parity.shared::cta.b64 p, [%46], %47;\nmbarrier.try_wait.parity.shared::cta.b64 r, [%44], %45;\nand.pred p, p, r;\n@p bra.uni DN;\nadd.u32 n, n, 1;\nsetp.lt.u32 p, n, 0x100000;\n@p bra.uni WT;\nDN:\n"
    "}\n"
      :
      "+f"(d[0]), "+f"(d[1]), "+f"(d[2]), "+f"(d[3]), "+f"(d[4]), "+f"(d[5]), "+f"(d[6]), "+f"(d[7]),
      "+f"(d[8]), "+f"(d[9]), "+f"(d[10]), "+f"(d[11]), "+f"(d[12]), "+f"(d[13]), "+f"(d[14]), "+f"(d[15]),
      "+f"(d[16]), "+f"(d[17]), "+f"(d[18]), "+f"(d[19]), "+f"(d[20]), "+f"(d[21]), "+f"(d[22]), "+f"(d[23]),
      "+f"(d[24]), "+f"(d[25]), "+f"(d[26]), "+f"(d[27]), "+f"(d[28]), "+f"(d[29]), "+f"(d[30]), "+f"(d[31]),
      "+f"(d[32]), "+f"(d[33]), "+f"(d[34]), "+f"(d[35]), "+f"(d[36]), "+f"(d[37]), "+f"(d[38]), "+f"(d[39])
      : "l"(da), "l"(db), "r"(rel), "r"(doR), "r"(fa), "r"(pa), "r"(fb), "r"(pb), "n"(BSTEP), "r"(acc), "r"(rela) : "memory");
    else static_assert(W < 0, "variant not generated");
  }
};
template <> struct KB<160> {
  template <int W, int RC, int RA, int BSTEP> static __device__ __forceinline__ void run(float* d, uint64_t da, uint64_t db, uint32_t rel, uint32_t rela, uint32_t doR, uint32_t fa, uint32_t pa, uint32_t fb, uint32_t pb, uint32_t acc) {
    if constexpr (W == 0 && RC == 2 && RA == 0) asm volatile(
    "{\n.reg .pred p, q, r, t;\n.reg .b64 a, b;\n.reg .u32 n;\nsetp.ne.b32 t, 1, 0;\nsetp.ne.b32 r, %89, 0;\n"
    "wgmma.mma_async.sync.aligned.m64n160k16.f32.bf16.bf16 {"
      "%0, %1, %2, %3, %4, %5, %6, %7, %8, %9, %10, %11, %12, %13, %14, %15, "
      "%16, %17, %18, %19, %20, %21, %22, %23, %24, %25, %26, %27, %28, %29, %30, %31, "
      "%32, %33, %34, %35, %36, %37, %38, %39, %40, %41, %42, %43, %44, %45, %46, %47, "
      "%48, %49, %50, %51, %52, %53, %54, %55, %56, %57, %58, %59, %60, %61, %62, %63, "
      "%64, %65, %66, %67, %68, %69, %70, %71, %72, %73, %74, %75, %76, %77, %78, %79"
      "}, %80, %81, r, 1, 1, 0, 1;\n"
    "add.u64 a, %80, 2;\nadd.u64 b, %81, %88;\n"
    "wgmma.mma_async.sync.aligned.m64n160k16.f32.bf16.bf16 {"
      "%0, %1, %2, %3, %4, %5, %6, %7, %8, %9, %10, %11, %12, %13, %14, %15, "
      "%16, %17, %18, %19, %20, %21, %22, %23, %24, %25, %26, %27, %28, %29, %30, %31, "
      "%32, %33, %34, %35, %36, %37, %38, %39, %40, %41, %42, %43, %44, %45, %46, %47, "
      "%48, %49, %50, %51, %52, %53, %54, %55, %56, %57, %58, %59, %60, %61, %62, %63, "
      "%64, %65, %66, %67, %68, %69, %70, %71, %72, %73, %74, %75, %76, %77, %78, %79"
      "}, a, b, t, 1, 1, 0, 1;\n"
    "wgmma.commit_group.sync.aligned;\nwgmma.wait_group.sync.aligned 1;\n"
    "add.u64 a, %80, 4;\nadd.u64 b, %81, 2*%88;\n"
    "wgmma.mma_async.sync.aligned.m64n160k16.f32.bf16.bf16 {"
      "%0, %1, %2, %3, %4, %5, %6, %7, %8, %9, %10, %11, %12, %13, %14, %15, "
      "%16, %17, %18, %19, %20, %21, %22, %23, %24, %25, %26, %27, %28, %29, %30, %31, "
      "%32, %33, %34, %35, %36, %37, %38, %39, %40, %41, %42, %43, %44, %45, %46, %47, "
      "%48, %49, %50, %51, %52, %53, %54, %55, %56, %57, %58, %59, %60, %61, %62, %63, "
      "%64, %65, %66, %67, %68, %69, %70, %71, %72, %73, %74, %75, %76, %77, %78, %79"
      "}, a, b, t, 1, 1, 0, 1;\n"
    "setp.ne.u32 q, %83, 0;\n@q mbarrier.arrive.shared::cta.b64 _, [%82];\n@q mbarrier.arrive.shared::cta.b64 _, [%82];\n"
    "add.u64 a, %80, 6;\nadd.u64 b, %81, 3*%88;\n"
    "wgmma.mma_async.sync.aligned.m64n160k16.f32.bf16.bf16 {"
      "%0, %1, %2, %3, %4, %5, %6, %7, %8, %9, %10, %11, %12, %13, %14, %15, "
      "%16, %17, %18, %19, %20, %21, %22, %23, %24, %25, %26, %27, %28, %29, %30, %31, "
      "%32, %33, %34, %35, %36, %37, %38, %39, %40, %41, %42, %43, %44, %45, %46, %47, "
      "%48, %49, %50, %51, %52, %53, %54, %55, %56, %57, %58, %59, %60, %61, %62, %63, "
      "%64, %65, %66, %67, %68, %69, %70, %71, %72, %73, %74, %75, %76, %77, %78, %79"
      "}, a, b, t, 1, 1, 0, 1;\n"
    "wgmma.commit_group.sync.aligned;\n"
    "}\n"
      :
      "+f"(d[0]), "+f"(d[1]), "+f"(d[2]), "+f"(d[3]), "+f"(d[4]), "+f"(d[5]), "+f"(d[6]), "+f"(d[7]),
      "+f"(d[8]), "+f"(d[9]), "+f"(d[10]), "+f"(d[11]), "+f"(d[12]), "+f"(d[13]), "+f"(d[14]), "+f"(d[15]),
      "+f"(d[16]), "+f"(d[17]), "+f"(d[18]), "+f"(d[19]), "+f"(d[20]), "+f"(d[21]), "+f"(d[22]), "+f"(d[23]),
      "+f"(d[24]), "+f"(d[25]), "+f"(d[26]), "+f"(d[27]), "+f"(d[28]), "+f"(d[29]), "+f"(d[30]), "+f"(d[31]),
      "+f"(d[32]), "+f"(d[33]), "+f"(d[34]), "+f"(d[35]), "+f"(d[36]), "+f"(d[37]), "+f"(d[38]), "+f"(d[39]),
      "+f"(d[40]), "+f"(d[41]), "+f"(d[42]), "+f"(d[43]), "+f"(d[44]), "+f"(d[45]), "+f"(d[46]), "+f"(d[47]),
      "+f"(d[48]), "+f"(d[49]), "+f"(d[50]), "+f"(d[51]), "+f"(d[52]), "+f"(d[53]), "+f"(d[54]), "+f"(d[55]),
      "+f"(d[56]), "+f"(d[57]), "+f"(d[58]), "+f"(d[59]), "+f"(d[60]), "+f"(d[61]), "+f"(d[62]), "+f"(d[63]),
      "+f"(d[64]), "+f"(d[65]), "+f"(d[66]), "+f"(d[67]), "+f"(d[68]), "+f"(d[69]), "+f"(d[70]), "+f"(d[71]),
      "+f"(d[72]), "+f"(d[73]), "+f"(d[74]), "+f"(d[75]), "+f"(d[76]), "+f"(d[77]), "+f"(d[78]), "+f"(d[79])
      : "l"(da), "l"(db), "r"(rel), "r"(doR), "r"(fa), "r"(pa), "r"(fb), "r"(pb), "n"(BSTEP), "r"(acc), "r"(rela) : "memory");
    else if constexpr (W == 1 && RC == 2 && RA == 0) asm volatile(
    "{\n.reg .pred p, q, r, t;\n.reg .b64 a, b;\n.reg .u32 n;\nsetp.ne.b32 t, 1, 0;\nsetp.ne.b32 r, %89, 0;\n"
    "wgmma.mma_async.sync.aligned.m64n160k16.f32.bf16.bf16 {"
      "%0, %1, %2, %3, %4, %5, %6, %7, %8, %9, %10, %11, %12, %13, %14, %15, "
      "%16, %17, %18, %19, %20, %21, %22, %23, %24, %25, %26, %27, %28, %29, %30, %31, "
      "%32, %33, %34, %35, %36, %37, %38, %39, %40, %41, %42, %43, %44, %45, %46, %47, "
      "%48, %49, %50, %51, %52, %53, %54, %55, %56, %57, %58, %59, %60, %61, %62, %63, "
      "%64, %65, %66, %67, %68, %69, %70, %71, %72, %73, %74, %75, %76, %77, %78, %79"
      "}, %80, %81, r, 1, 1, 0, 1;\n"
    "add.u64 a, %80, 2;\nadd.u64 b, %81, %88;\n"
    "wgmma.mma_async.sync.aligned.m64n160k16.f32.bf16.bf16 {"
      "%0, %1, %2, %3, %4, %5, %6, %7, %8, %9, %10, %11, %12, %13, %14, %15, "
      "%16, %17, %18, %19, %20, %21, %22, %23, %24, %25, %26, %27, %28, %29, %30, %31, "
      "%32, %33, %34, %35, %36, %37, %38, %39, %40, %41, %42, %43, %44, %45, %46, %47, "
      "%48, %49, %50, %51, %52, %53, %54, %55, %56, %57, %58, %59, %60, %61, %62, %63, "
      "%64, %65, %66, %67, %68, %69, %70, %71, %72, %73, %74, %75, %76, %77, %78, %79"
      "}, a, b, t, 1, 1, 0, 1;\n"
    "wgmma.commit_group.sync.aligned;\nwgmma.wait_group.sync.aligned 1;\n"
    "add.u64 a, %80, 4;\nadd.u64 b, %81, 2*%88;\n"
    "wgmma.mma_async.sync.aligned.m64n160k16.f32.bf16.bf16 {"
      "%0, %1, %2, %3, %4, %5, %6, %7, %8, %9, %10, %11, %12, %13, %14, %15, "
      "%16, %17, %18, %19, %20, %21, %22, %23, %24, %25, %26, %27, %28, %29, %30, %31, "
      "%32, %33, %34, %35, %36, %37, %38, %39, %40, %41, %42, %43, %44, %45, %46, %47, "
      "%48, %49, %50, %51, %52, %53, %54, %55, %56, %57, %58, %59, %60, %61, %62, %63, "
      "%64, %65, %66, %67, %68, %69, %70, %71, %72, %73, %74, %75, %76, %77, %78, %79"
      "}, a, b, t, 1, 1, 0, 1;\n"
    "setp.ne.u32 q, %83, 0;\n@q mbarrier.arrive.shared::cta.b64 _, [%82];\n@q mbarrier.arrive.shared::cta.b64 _, [%82];\n"
    "mbarrier.test_wait.parity.shared::cta.b64 p, [%86], %87;\n"
    "add.u64 a, %80, 6;\nadd.u64 b, %81, 3*%88;\n"
    "wgmma.mma_async.sync.aligned.m64n160k16.f32.bf16.bf16 {"
      "%0, %1, %2, %3, %4, %5, %6, %7, %8, %9, %10, %11, %12, %13, %14, %15, "
      "%16, %17, %18, %19, %20, %21, %22, %23, %24, %25, %26, %27, %28, %29, %30, %31, "
      "%32, %33, %34, %35, %36, %37, %38, %39, %40, %41, %42, %43, %44, %45, %46, %47, "
      "%48, %49, %50, %51, %52, %53, %54, %55, %56, %57, %58, %59, %60, %61, %62, %63, "
      "%64, %65, %66, %67, %68, %69, %70, %71, %72, %73, %74, %75, %76, %77, %78, %79"
      "}, a, b, t, 1, 1, 0, 1;\n"
    "wgmma.commit_group.sync.aligned;\n"
    "@p bra.uni DN;\nmov.u32 n, 0;\nWT: mbarrier.try_wait.parity.shared::cta.b64 p, [%86], %87;\n@p bra.uni DN;\nadd.u32 n, n, 1;\nsetp.lt.u32 p, n, 0x100000;\n@p bra.uni WT;\nDN:\n"
    "}\n"
      :
      "+f"(d[0]), "+f"(d[1]), "+f"(d[2]), "+f"(d[3]), "+f"(d[4]), "+f"(d[5]), "+f"(d[6]), "+f"(d[7]),
      "+f"(d[8]), "+f"(d[9]), "+f"(d[10]), "+f"(d[11]), "+f"(d[12]), "+f"(d[13]), "+f"(d[14]), "+f"(d[15]),
      "+f"(d[16]), "+f"(d[17]), "+f"(d[18]), "+f"(d[19]), "+f"(d[20]), "+f"(d[21]), "+f"(d[22]), "+f"(d[23]),
      "+f"(d[24]), "+f"(d[25]), "+f"(d[26]), "+f"(d[27]), "+f"(d[28]), "+f"(d[29]), "+f"(d[30]), "+f"(d[31]),
      "+f"(d[32]), "+f"(d[33]), "+f"(d[34]), "+f"(d[35]), "+f"(d[36]), "+f"(d[37]), "+f"(d[38]), "+f"(d[39]),
      "+f"(d[40]), "+f"(d[41]), "+f"(d[42]), "+f"(d[43]), "+f"(d[44]), "+f"(d[45]), "+f"(d[46]), "+f"(d[47]),
      "+f"(d[48]), "+f"(d[49]), "+f"(d[50]), "+f"(d[51]), "+f"(d[52]), "+f"(d[53]), "+f"(d[54]), "+f"(d[55]),
      "+f"(d[56]), "+f"(d[57]), "+f"(d[58]), "+f"(d[59]), "+f"(d[60]), "+f"(d[61]), "+f"(d[62]), "+f"(d[63]),
      "+f"(d[64]), "+f"(d[65]), "+f"(d[66]), "+f"(d[67]), "+f"(d[68]), "+f"(d[69]), "+f"(d[70]), "+f"(d[71]),
      "+f"(d[72]), "+f"(d[73]), "+f"(d[74]), "+f"(d[75]), "+f"(d[76]), "+f"(d[77]), "+f"(d[78]), "+f"(d[79])
      : "l"(da), "l"(db), "r"(rel), "r"(doR), "r"(fa), "r"(pa), "r"(fb), "r"(pb), "n"(BSTEP), "r"(acc), "r"(rela) : "memory");
    else static_assert(W < 0, "variant not generated");
  }
};
template <> struct KB<192> {
  template <int W, int RC, int RA, int BSTEP> static __device__ __forceinline__ void run(float* d, uint64_t da, uint64_t db, uint32_t rel, uint32_t rela, uint32_t doR, uint32_t fa, uint32_t pa, uint32_t fb, uint32_t pb, uint32_t acc) {
    if constexpr (W == 0 && RC == 2 && RA == 0) asm volatile(
    "{\n.reg .pred p, q, r, t;\n.reg .b64 a, b;\n.reg .u32 n;\nsetp.ne.b32 t, 1, 0;\nsetp.ne.b32 r, %105, 0;\n"
    "wgmma.mma_async.sync.aligned.m64n192k16.f32.bf16.bf16 {"
      "%0, %1, %2, %3, %4, %5, %6, %7, %8, %9, %10, %11, %12, %13, %14, %15, "
      "%16, %17, %18, %19, %20, %21, %22, %23, %24, %25, %26, %27, %28, %29, %30, %31, "
      "%32, %33, %34, %35, %36, %37, %38, %39, %40, %41, %42, %43, %44, %45, %46, %47, "
      "%48, %49, %50, %51, %52, %53, %54, %55, %56, %57, %58, %59, %60, %61, %62, %63, "
      "%64, %65, %66, %67, %68, %69, %70, %71, %72, %73, %74, %75, %76, %77, %78, %79, "
      "%80, %81, %82, %83, %84, %85, %86, %87, %88, %89, %90, %91, %92, %93, %94, %95"
      "}, %96, %97, r, 1, 1, 0, 1;\n"
    "add.u64 a, %96, 2;\nadd.u64 b, %97, %104;\n"
    "wgmma.mma_async.sync.aligned.m64n192k16.f32.bf16.bf16 {"
      "%0, %1, %2, %3, %4, %5, %6, %7, %8, %9, %10, %11, %12, %13, %14, %15, "
      "%16, %17, %18, %19, %20, %21, %22, %23, %24, %25, %26, %27, %28, %29, %30, %31, "
      "%32, %33, %34, %35, %36, %37, %38, %39, %40, %41, %42, %43, %44, %45, %46, %47, "
      "%48, %49, %50, %51, %52, %53, %54, %55, %56, %57, %58, %59, %60, %61, %62, %63, "
      "%64, %65, %66, %67, %68, %69, %70, %71, %72, %73, %74, %75, %76, %77, %78, %79, "
      "%80, %81, %82, %83, %84, %85, %86, %87, %88, %89, %90, %91, %92, %93, %94, %95"
      "}, a, b, t, 1, 1, 0, 1;\n"
    "wgmma.commit_group.sync.aligned;\nwgmma.wait_group.sync.aligned 1;\n"
    "add.u64 a, %96, 4;\nadd.u64 b, %97, 2*%104;\n"
    "wgmma.mma_async.sync.aligned.m64n192k16.f32.bf16.bf16 {"
      "%0, %1, %2, %3, %4, %5, %6, %7, %8, %9, %10, %11, %12, %13, %14, %15, "
      "%16, %17, %18, %19, %20, %21, %22, %23, %24, %25, %26, %27, %28, %29, %30, %31, "
      "%32, %33, %34, %35, %36, %37, %38, %39, %40, %41, %42, %43, %44, %45, %46, %47, "
      "%48, %49, %50, %51, %52, %53, %54, %55, %56, %57, %58, %59, %60, %61, %62, %63, "
      "%64, %65, %66, %67, %68, %69, %70, %71, %72, %73, %74, %75, %76, %77, %78, %79, "
      "%80, %81, %82, %83, %84, %85, %86, %87, %88, %89, %90, %91, %92, %93, %94, %95"
      "}, a, b, t, 1, 1, 0, 1;\n"
    "setp.ne.u32 q, %99, 0;\n@q mbarrier.arrive.shared::cta.b64 _, [%98];\n@q mbarrier.arrive.shared::cta.b64 _, [%98];\n"
    "add.u64 a, %96, 6;\nadd.u64 b, %97, 3*%104;\n"
    "wgmma.mma_async.sync.aligned.m64n192k16.f32.bf16.bf16 {"
      "%0, %1, %2, %3, %4, %5, %6, %7, %8, %9, %10, %11, %12, %13, %14, %15, "
      "%16, %17, %18, %19, %20, %21, %22, %23, %24, %25, %26, %27, %28, %29, %30, %31, "
      "%32, %33, %34, %35, %36, %37, %38, %39, %40, %41, %42, %43, %44, %45, %46, %47, "
      "%48, %49, %50, %51, %52, %53, %54, %55, %56, %57, %58, %59, %60, %61, %62, %63, "
      "%64, %65, %66, %67, %68, %69, %70, %71, %72, %73, %74, %75, %76, %77, %78, %79, "
      "%80, %81, %82, %83, %84, %85, %86, %87, %88, %89, %90, %91, %92, %93, %94, %95"
      "}, a, b, t, 1, 1, 0, 1;\n"
    "wgmma.commit_group.sync.aligned;\n"
    "}\n"
      :
      "+f"(d[0]), "+f"(d[1]), "+f"(d[2]), "+f"(d[3]), "+f"(d[4]), "+f"(d[5]), "+f"(d[6]), "+f"(d[7]),
      "+f"(d[8]), "+f"(d[9]), "+f"(d[10]), "+f"(d[11]), "+f"(d[12]), "+f"(d[13]), "+f"(d[14]), "+f"(d[15]),
      "+f"(d[16]), "+f"(d[17]), "+f"(d[18]), "+f"(d[19]), "+f"(d[20]), "+f"(d[21]), "+f"(d[22]), "+f"(d[23]),
      "+f"(d[24]), "+f"(d[25]), "+f"(d[26]), "+f"(d[27]), "+f"(d[28]), "+f"(d[29]), "+f"(d[30]), "+f"(d[31]),
      "+f"(d[32]), "+f"(d[33]), "+f"(d[34]), "+f"(d[35]), "+f"(d[36]), "+f"(d[37]), "+f"(d[38]), "+f"(d[39]),
      "+f"(d[40]), "+f"(d[41]), "+f"(d[42]), "+f"(d[43]), "+f"(d[44]), "+f"(d[45]), "+f"(d[46]), "+f"(d[47]),
      "+f"(d[48]), "+f"(d[49]), "+f"(d[50]), "+f"(d[51]), "+f"(d[52]), "+f"(d[53]), "+f"(d[54]), "+f"(d[55]),
      "+f"(d[56]), "+f"(d[57]), "+f"(d[58]), "+f"(d[59]), "+f"(d[60]), "+f"(d[61]), "+f"(d[62]), "+f"(d[63]),
      "+f"(d[64]), "+f"(d[65]), "+f"(d[66]), "+f"(d[67]), "+f"(d[68]), "+f"(d[69]), "+f"(d[70]), "+f"(d[71]),
      "+f"(d[72]), "+f"(d[73]), "+f"(d[74]), "+f"(d[75]), "+f"(d[76]), "+f"(d[77]), "+f"(d[78]), "+f"(d[79]),
      "+f"(d[80]), "+f"(d[81]), "+f"(d[82]), "+f"(d[83]), "+f"(d[84]), "+f"(d[85]), "+f"(d[86]), "+f"(d[87]),
      "+f"(d[88]), "+f"(d[89]), "+f"(d[90]), "+f"(d[91]), "+f"(d[92]), "+f"(d[93]), "+f"(d[94]), "+f"(d[95])
      : "l"(da), "l"(db), "r"(rel), "r"(doR), "r"(fa), "r"(pa), "r"(fb), "r"(pb), "n"(BSTEP), "r"(acc), "r"(rela) : "memory");
    else if constexpr (W == 0 && RC == 2 && RA == 2) asm volatile(
    "{\n.reg .pred p, q, r, t;\n.reg .b64 a, b;\n.reg .u32 n;\nsetp.ne.b32 t, 1, 0;\nsetp.ne.b32 r, %105, 0;\n"
    "wgmma.mma_async.sync.aligned.m64n192k16.f32.bf16.bf16 {"
      "%0, %1, %2, %3, %4, %5, %6, %7, %8, %9, %10, %11, %12, %13, %14, %15, "
      "%16, %17, %18, %19, %20, %21, %22, %23, %24, %25, %26, %27, %28, %29, %30, %31, "
      "%32, %33, %34, %35, %36, %37, %38, %39, %40, %41, %42, %43, %44, %45, %46, %47, "
      "%48, %49, %50, %51, %52, %53, %54, %55, %56, %57, %58, %59, %60, %61, %62, %63, "
      "%64, %65, %66, %67, %68, %69, %70, %71, %72, %73, %74, %75, %76, %77, %78, %79, "
      "%80, %81, %82, %83, %84, %85, %86, %87, %88, %89, %90, %91, %92, %93, %94, %95"
      "}, %96, %97, r, 1, 1, 0, 1;\n"
    "add.u64 a, %96, 2;\nadd.u64 b, %97, %104;\n"
    "wgmma.mma_async.sync.aligned.m64n192k16.f32.bf16.bf16 {"
      "%0, %1, %2, %3, %4, %5, %6, %7, %8, %9, %10, %11, %12, %13, %14, %15, "
      "%16, %17, %18, %19, %20, %21, %22, %23, %24, %25, %26, %27, %28, %29, %30, %31, "
      "%32, %33, %34, %35, %36, %37, %38, %39, %40, %41, %42, %43, %44, %45, %46, %47, "
      "%48, %49, %50, %51, %52, %53, %54, %55, %56, %57, %58, %59, %60, %61, %62, %63, "
      "%64, %65, %66, %67, %68, %69, %70, %71, %72, %73, %74, %75, %76, %77, %78, %79, "
      "%80, %81, %82, %83, %84, %85, %86, %87, %88, %89, %90, %91, %92, %93, %94, %95"
      "}, a, b, t, 1, 1, 0, 1;\n"
    "wgmma.commit_group.sync.aligned;\nwgmma.wait_group.sync.aligned 1;\n"
    "add.u64 a, %96, 4;\nadd.u64 b, %97, 2*%104;\n"
    "wgmma.mma_async.sync.aligned.m64n192k16.f32.bf16.bf16 {"
      "%0, %1, %2, %3, %4, %5, %6, %7, %8, %9, %10, %11, %12, %13, %14, %15, "
      "%16, %17, %18, %19, %20, %21, %22, %23, %24, %25, %26, %27, %28, %29, %30, %31, "
      "%32, %33, %34, %35, %36, %37, %38, %39, %40, %41, %42, %43, %44, %45, %46, %47, "
      "%48, %49, %50, %51, %52, %53, %54, %55, %56, %57, %58, %59, %60, %61, %62, %63, "
      "%64, %65, %66, %67, %68, %69, %70, %71, %72, %73, %74, %75, %76, %77, %78, %79, "
      "%80, %81, %82, %83, %84, %85, %86, %87, %88, %89, %90, %91, %92, %93, %94, %95"
      "}, a, b, t, 1, 1, 0, 1;\n"
    "setp.ne.u32 q, %99, 0;\n@q mbarrier.arrive.shared::cta.b64 _, [%98];\n@q mbarrier.arrive.shared::cta.b64 _, [%98];\n@q mbarrier.arrive.shared::cta.b64 _, [%106];\n@q mbarrier.arrive.shared::cta.b64 _, [%106];\n"
    "add.u64 a, %96, 6;\nadd.u64 b, %97, 3*%104;\n"
    "wgmma.mma_async.sync.aligned.m64n192k16.f32.bf16.bf16 {"
      "%0, %1, %2, %3, %4, %5, %6, %7, %8, %9, %10, %11, %12, %13, %14, %15, "
      "%16, %17, %18, %19, %20, %21, %22, %23, %24, %25, %26, %27, %28, %29, %30, %31, "
      "%32, %33, %34, %35, %36, %37, %38, %39, %40, %41, %42, %43, %44, %45, %46, %47, "
      "%48, %49, %50, %51, %52, %53, %54, %55, %56, %57, %58, %59, %60, %61, %62, %63, "
      "%64, %65, %66, %67, %68, %69, %70, %71, %72, %73, %74, %75, %76, %77, %78, %79, "
      "%80, %81, %82, %83, %84, %85, %86, %87, %88, %89, %90, %91, %92, %93, %94, %95"
      "}, a, b, t, 1, 1, 0, 1;\n"
    "wgmma.commit_group.sync.aligned;\n"
    "}\n"
      :
      "+f"(d[0]), "+f"(d[1]), "+f"(d[2]), "+f"(d[3]), "+f"(d[4]), "+f"(d[5]), "+f"(d[6]), "+f"(d[7]),
      "+f"(d[8]), "+f"(d[9]), "+f"(d[10]), "+f"(d[11]), "+f"(d[12]), "+f"(d[13]), "+f"(d[14]), "+f"(d[15]),
      "+f"(d[16]), "+f"(d[17]), "+f"(d[18]), "+f"(d[19]), "+f"(d[20]), "+f"(d[21]), "+f"(d[22]), "+f"(d[23]),
      "+f"(d[24]), "+f"(d[25]), "+f"(d[26]), "+f"(d[27]), "+f"(d[28]), "+f"(d[29]), "+f"(d[30]), "+f"(d[31]),
      "+f"(d[32]), "+f"(d[33]), "+f"(d[34]), "+f"(d[35]), "+f"(d[36]), "+f"(d[37]), "+f"(d[38]), "+f"(d[39]),
      "+f"(d[40]), "+f"(d[41]), "+f"(d[42]), "+f"(d[43]), "+f"(d[44]), "+f"(d[45]), "+f"(d[46]), "+f"(d[47]),
      "+f"(d[48]), "+f"(d[49]), "+f"(d[50]), "+f"(d[51]), "+f"(d[52]), "+f"(d[53]), "+f"(d[54]), "+f"(d[55]),
      "+f"(d[56]), "+f"(d[57]), "+f"(d[58]), "+f"(d[59]), "+f"(d[60]), "+f"(d[61]), "+f"(d[62]), "+f"(d[63]),
      "+f"(d[64]), "+f"(d[65]), "+f"(d[66]), "+f"(d[67]), "+f"(d[68]), "+f"(d[69]), "+f"(d[70]), "+f"(d[71]),
      "+f"(d[72]), "+f"(d[73]), "+f"(d[74]), "+f"(d[75]), "+f"(d[76]), "+f"(d[77]), "+f"(d[78]), "+f"(d[79]),
      "+f"(d[80]), "+f"(d[81]), "+f"(d[82]), "+f"(d[83]), "+f"(d[84]), "+f"(d[85]), "+f"(d[86]), "+f"(d[87]),
      "+f"(d[88]), "+f"(d[89]), "+f"(d[90]), "+f"(d[91]), "+f"(d[92]), "+f"(d[93]), "+f"(d[94]), "+f"(d[95])
      : "l"(da), "l"(db), "r"(rel), "r"(doR), "r"(fa), "r"(pa), "r"(fb), "r"(pb), "n"(BSTEP), "r"(acc), "r"(rela) : "memory");
    else if constexpr (W == 1 && RC == 2 && RA == 2) asm volatile(
    "{\n.reg .pred p, q, r, t;\n.reg .b64 a, b;\n.reg .u32 n;\nsetp.ne.b32 t, 1, 0;\nsetp.ne.b32 r, %105, 0;\n"
    "wgmma.mma_async.sync.aligned.m64n192k16.f32.bf16.bf16 {"
      "%0, %1, %2, %3, %4, %5, %6, %7, %8, %9, %10, %11, %12, %13, %14, %15, "
      "%16, %17, %18, %19, %20, %21, %22, %23, %24, %25, %26, %27, %28, %29, %30, %31, "
      "%32, %33, %34, %35, %36, %37, %38, %39, %40, %41, %42, %43, %44, %45, %46, %47, "
      "%48, %49, %50, %51, %52, %53, %54, %55, %56, %57, %58, %59, %60, %61, %62, %63, "
      "%64, %65, %66, %67, %68, %69, %70, %71, %72, %73, %74, %75, %76, %77, %78, %79, "
      "%80, %81, %82, %83, %84, %85, %86, %87, %88, %89, %90, %91, %92, %93, %94, %95"
      "}, %96, %97, r, 1, 1, 0, 1;\n"
    "add.u64 a, %96, 2;\nadd.u64 b, %97, %104;\n"
    "wgmma.mma_async.sync.aligned.m64n192k16.f32.bf16.bf16 {"
      "%0, %1, %2, %3, %4, %5, %6, %7, %8, %9, %10, %11, %12, %13, %14, %15, "
      "%16, %17, %18, %19, %20, %21, %22, %23, %24, %25, %26, %27, %28, %29, %30, %31, "
      "%32, %33, %34, %35, %36, %37, %38, %39, %40, %41, %42, %43, %44, %45, %46, %47, "
      "%48, %49, %50, %51, %52, %53, %54, %55, %56, %57, %58, %59, %60, %61, %62, %63, "
      "%64, %65, %66, %67, %68, %69, %70, %71, %72, %73, %74, %75, %76, %77, %78, %79, "
      "%80, %81, %82, %83, %84, %85, %86, %87, %88, %89, %90, %91, %92, %93, %94, %95"
      "}, a, b, t, 1, 1, 0, 1;\n"
    "wgmma.commit_group.sync.aligned;\nwgmma.wait_group.sync.aligned 1;\n"
    "add.u64 a, %96, 4;\nadd.u64 b, %97, 2*%104;\n"
    "wgmma.mma_async.sync.aligned.m64n192k16.f32.bf16.bf16 {"
      "%0, %1, %2, %3, %4, %5, %6, %7, %8, %9, %10, %11, %12, %13, %14, %15, "
      "%16, %17, %18, %19, %20, %21, %22, %23, %24, %25, %26, %27, %28, %29, %30, %31, "
      "%32, %33, %34, %35, %36, %37, %38, %39, %40, %41, %42, %43, %44, %45, %46, %47, "
      "%48, %49, %50, %51, %52, %53, %54, %55, %56, %57, %58, %59, %60, %61, %62, %63, "
      "%64, %65, %66, %67, %68, %69, %70, %71, %72, %73, %74, %75, %76, %77, %78, %79, "
      "%80, %81, %82, %83, %84, %85, %86, %87, %88, %89, %90, %91, %92, %93, %94, %95"
      "}, a, b, t, 1, 1, 0, 1;\n"
    "setp.ne.u32 q, %99, 0;\n@q mbarrier.arrive.shared::cta.b64 _, [%98];\n@q mbarrier.arrive.shared::cta.b64 _, [%98];\n@q mbarrier.arrive.shared::cta.b64 _, [%106];\n@q mbarrier.arrive.shared::cta.b64 _, [%106];\n"
    "mbarrier.test_wait.parity.shared::cta.b64 p, [%102], %103;\n"
    "add.u64 a, %96, 6;\nadd.u64 b, %97, 3*%104;\n"
    "wgmma.mma_async.sync.aligned.m64n192k16.f32.bf16.bf16 {"
      "%0, %1, %2, %3, %4, %5, %6, %7, %8, %9, %10, %11, %12, %13, %14, %15, "
      "%16, %17, %18, %19, %20, %21, %22, %23, %24, %25, %26, %27, %28, %29, %30, %31, "
      "%32, %33, %34, %35, %36, %37, %38, %39, %40, %41, %42, %43, %44, %45, %46, %47, "
      "%48, %49, %50, %51, %52, %53, %54, %55, %56, %57, %58, %59, %60, %61, %62, %63, "
      "%64, %65, %66, %67, %68, %69, %70, %71, %72, %73, %74, %75, %76, %77, %78, %79, "
      "%80, %81, %82, %83, %84, %85, %86, %87, %88, %89, %90, %91, %92, %93, %94, %95"
      "}, a, b, t, 1, 1, 0, 1;\n"
    "wgmma.commit_group.sync.aligned;\n"
    "@p bra.uni DN;\nmov.u32 n, 0;\nWT: mbarrier.try_wait.parity.shared::cta.b64 p, [%102], %103;\n@p bra.uni DN;\nadd.u32 n, n, 1;\nsetp.lt.u32 p, n, 0x100000;\n@p bra.uni WT;\nDN:\n"
    "}\n"
      :
      "+f"(d[0]), "+f"(d[1]), "+f"(d[2]), "+f"(d[3]), "+f"(d[4]), "+f"(d[5]), "+f"(d[6]), "+f"(d[7]),
      "+f"(d[8]), "+f"(d[9]), "+f"(d[10]), "+f"(d[11]), "+f"(d[12]), "+f"(d[13]), "+f"(d[14]), "+f"(d[15]),
      "+f"(d[16]), "+f"(d[17]), "+f"(d[18]), "+f"(d[19]), "+f"(d[20]), "+f"(d[21]), "+f"(d[22]), "+f"(d[23]),
      "+f"(d[24]), "+f"(d[25]), "+f"(d[26]), "+f"(d[27]), "+f"(d[28]), "+f"(d[29]), "+f"(d[30]), "+f"(d[31]),
      "+f"(d[32]), "+f"(d[33]), "+f"(d[34]), "+f"(d[35]), "+f"(d[36]), "+f"(d[37]), "+f"(d[38]), "+f"(d[39]),
      "+f"(d[40]), "+f"(d[41]), "+f"(d[42]), "+f"(d[43]), "+f"(d[44]), "+f"(d[45]), "+f"(d[46]), "+f"(d[47]),
      "+f"(d[48]), "+f"(d[49]), "+f"(d[50]), "+f"(d[51]), "+f"(d[52]), "+f"(d[53]), "+f"(d[54]), "+f"(d[55]),
      "+f"(d[56]), "+f"(d[57]), "+f"(d[58]), "+f"(d[59]), "+f"(d[60]), "+f"(d[61]), "+f"(d[62]), "+f"(d[63]),
      "+f"(d[64]), "+f"(d[65]), "+f"(d[66]), "+f"(d[67]), "+f"(d[68]), "+f"(d[69]), "+f"(d[70]), "+f"(d[71]),
      "+f"(d[72]), "+f"(d[73]), "+f"(d[74]), "+f"(d[75]), "+f"(d[76]), "+f"(d[77]), "+f"(d[78]), "+f"(d[79]),
      "+f"(d[80]), "+f"(d[81]), "+f"(d[82]), "+f"(d[83]), "+f"(d[84]), "+f"(d[85]), "+f"(d[86]), "+f"(d[87]),
      "+f"(d[88]), "+f"(d[89]), "+f"(d[90]), "+f"(d[91]), "+f"(d[92]), "+f"(d[93]), "+f"(d[94]), "+f"(d[95])
      : "l"(da), "l"(db), "r"(rel), "r"(doR), "r"(fa), "r"(pa), "r"(fb), "r"(pb), "n"(BSTEP), "r"(acc), "r"(rela) : "memory");
    else if constexpr (W == 2 && RC == 2 && RA == 0) asm volatile(
    "{\n.reg .pred p, q, r, t;\n.reg .b64 a, b;\n.reg .u32 n;\nsetp.ne.b32 t, 1, 0;\nsetp.ne.b32 r, %105, 0;\n"
    "wgmma.mma_async.sync.aligned.m64n192k16.f32.bf16.bf16 {"
      "%0, %1, %2, %3, %4, %5, %6, %7, %8, %9, %10, %11, %12, %13, %14, %15, "
      "%16, %17, %18, %19, %20, %21, %22, %23, %24, %25, %26, %27, %28, %29, %30, %31, "
      "%32, %33, %34, %35, %36, %37, %38, %39, %40, %41, %42, %43, %44, %45, %46, %47, "
      "%48, %49, %50, %51, %52, %53, %54, %55, %56, %57, %58, %59, %60, %61, %62, %63, "
      "%64, %65, %66, %67, %68, %69, %70, %71, %72, %73, %74, %75, %76, %77, %78, %79, "
      "%80, %81, %82, %83, %84, %85, %86, %87, %88, %89, %90, %91, %92, %93, %94, %95"
      "}, %96, %97, r, 1, 1, 0, 1;\n"
    "add.u64 a, %96, 2;\nadd.u64 b, %97, %104;\n"
    "wgmma.mma_async.sync.aligned.m64n192k16.f32.bf16.bf16 {"
      "%0, %1, %2, %3, %4, %5, %6, %7, %8, %9, %10, %11, %12, %13, %14, %15, "
      "%16, %17, %18, %19, %20, %21, %22, %23, %24, %25, %26, %27, %28, %29, %30, %31, "
      "%32, %33, %34, %35, %36, %37, %38, %39, %40, %41, %42, %43, %44, %45, %46, %47, "
      "%48, %49, %50, %51, %52, %53, %54, %55, %56, %57, %58, %59, %60, %61, %62, %63, "
      "%64, %65, %66, %67, %68, %69, %70, %71, %72, %73, %74, %75, %76, %77, %78, %79, "
      "%80, %81, %82, %83, %84, %85, %86, %87, %88, %89, %90, %91, %92, %93, %94, %95"
      "}, a, b, t, 1, 1, 0, 1;\n"
    "wgmma.commit_group.sync.aligned;\nwgmma.wait_group.sync.aligned 1;\n"
    "add.u64 a, %96, 4;\nadd.u64 b, %97, 2*%104;\n"
    "wgmma.mma_async.sync.aligned.m64n192k16.f32.bf16.bf16 {"
      "%0, %1, %2, %3, %4, %5, %6, %7, %8, %9, %10, %11, %12, %13, %14, %15, "
      "%16, %17, %18, %19, %20, %21, %22, %23, %24, %25, %26, %27, %28, %29, %30, %31, "
      "%32, %33, %34, %35, %36, %37, %38, %39, %40, %41, %42, %43, %44, %45, %46, %47, "
      "%48, %49, %50, %51, %52, %53, %54, %55, %56, %57, %58, %59, %60, %61, %62, %63, "
      "%64, %65, %66, %67, %68, %69, %70, %71, %72, %73, %74, %75, %76, %77, %78, %79, "
      "%80, %81, %82, %83, %84, %85, %86, %87, %88, %89, %90, %91, %92, %93, %94, %95"
      "}, a, b, t, 1, 1, 0, 1;\n"
    "setp.ne.u32 q, %99, 0;\n@q mbarrier.arrive.shared::cta.b64 _, [%98];\n@q mbarrier.arrive.shared::cta.b64 _, [%98];\n"
    "mbarrier.test_wait.parity.shared::cta.b64 p, [%102], %103;\n"
    "mbarrier.test_wait.parity.shared::cta.b64 r, [%100], %101;\nand.pred p, p, r;\n"
    "add.u64 a, %96, 6;\nadd.u64 b, %97, 3*%104;\n"
    "wgmma.mma_async.sync.aligned.m64n192k16.f32.bf16.bf16 {"
      "%0, %1, %2, %3, %4, %5, %6, %7, %8, %9, %10, %11, %12, %13, %14, %15, "
      "%16, %17, %18, %19, %20, %21, %22, %23, %24, %25, %26, %27, %28, %29, %30, %31, "
      "%32, %33, %34, %35, %36, %37, %38, %39, %40, %41, %42, %43, %44, %45, %46, %47, "
      "%48, %49, %50, %51, %52, %53, %54, %55, %56, %57, %58, %59, %60, %61, %62, %63, "
      "%64, %65, %66, %67, %68, %69, %70, %71, %72, %73, %74, %75, %76, %77, %78, %79, "
      "%80, %81, %82, %83, %84, %85, %86, %87, %88, %89, %90, %91, %92, %93, %94, %95"
      "}, a, b, t, 1, 1, 0, 1;\n"
    "wgmma.commit_group.sync.aligned;\n"
    "@p bra.uni DN;\nmov.u32 n, 0;\nWT: mbarrier.try_wait.parity.shared::cta.b64 p, [%102], %103;\nmbarrier.try_wait.parity.shared::cta.b64 r, [%100], %101;\nand.pred p, p, r;\n@p bra.uni DN;\nadd.u32 n, n, 1;\nsetp.lt.u32 p, n, 0x100000;\n@p bra.uni WT;\nDN:\n"
    "}\n"
      :
      "+f"(d[0]), "+f"(d[1]), "+f"(d[2]), "+f"(d[3]), "+f"(d[4]), "+f"(d[5]), "+f"(d[6]), "+f"(d[7]),
      "+f"(d[8]), "+f"(d[9]), "+f"(d[10]), "+f"(d[11]), "+f"(d[12]), "+f"(d[13]), "+f"(d[14]), "+f"(d[15]),
      "+f"(d[16]), "+f"(d[17]), "+f"(d[18]), "+f"(d[19]), "+f"(d[20]), "+f"(d[21]), "+f"(d[22]), "+f"(d[23]),
      "+f"(d[24]), "+f"(d[25]), "+f"(d[26]), "+f"(d[27]), "+f"(d[28]), "+f"(d[29]), "+f"(d[30]), "+f"(d[31]),
      "+f"(d[32]), "+f"(d[33]), "+f"(d[34]), "+f"(d[35]), "+f"(d[36]), "+f"(d[37]), "+f"(d[38]), "+f"(d[39]),
      "+f"(d[40]), "+f"(d[41]), "+f"(d[42]), "+f"(d[43]), "+f"(d[44]), "+f"(d[45]), "+f"(d[46]), "+f"(d[47]),
      "+f"(d[48]), "+f"(d[49]), "+f"(d[50]), "+f"(d[51]), "+f"(d[52]), "+f"(d[53]), "+f"(d[54]), "+f"(d[55]),
      "+f"(d[56]), "+f"(d[57]), "+f"(d[58]), "+f"(d[59]), "+f"(d[60]), "+f"(d[61]), "+f"(d[62]), "+f"(d[63]),
      "+f"(d[64]), "+f"(d[65]), "+f"(d[66]), "+f"(d[67]), "+f"(d[68]), "+f"(d[69]), "+f"(d[70]), "+f"(d[71]),
      "+f"(d[72]), "+f"(d[73]), "+f"(d[74]), "+f"(d[75]), "+f"(d[76]), "+f"(d[77]), "+f"(d[78]), "+f"(d[79]),
      "+f"(d[80]), "+f"(d[81]), "+f"(d[82]), "+f"(d[83]), "+f"(d[84]), "+f"(d[85]), "+f"(d[86]), "+f"(d[87]),
      "+f"(d[88]), "+f"(d[89]), "+f"(d[90]), "+f"(d[91]), "+f"(d[92]), "+f"(d[93]), "+f"(d[94]), "+f"(d[95])
      : "l"(da), "l"(db), "r"(rel), "r"(doR), "r"(fa), "r"(pa), "r"(fb), "r"(pb), "n"(BSTEP), "r"(acc), "r"(rela) : "memory");
    else if constexpr (W == 2 && RC == 2 && RA == 2) asm volatile(
    "{\n.reg .pred p, q, r, t;\n.reg .b64 a, b;\n.reg .u32 n;\nsetp.ne.b32 t, 1, 0;\nsetp.ne.b32 r, %105, 0;\n"
    "wgmma.mma_async.sync.aligned.m64n192k16.f32.bf16.bf16 {"
      "%0, %1, %2, %3, %4, %5, %6, %7, %8, %9, %10, %11, %12, %13, %14, %15, "
      "%16, %17, %18, %19, %20, %21, %22, %23, %24, %25, %26, %27, %28, %29, %30, %31, "
      "%32, %33, %34, %35, %36, %37, %38, %39, %40, %41, %42, %43, %44, %45, %46, %47, "
      "%48, %49, %50, %51, %52, %53, %54, %55, %56, %57, %58, %59, %60, %61, %62, %63, "
      "%64, %65, %66, %67, %68, %69, %70, %71, %72, %73, %74, %75, %76, %77, %78, %79, "
      "%80, %81, %82, %83, %84, %85, %86, %87, %88, %89, %90, %91, %92, %93, %94, %95"
      "}, %96, %97, r, 1, 1, 0, 1;\n"
    "add.u64 a, %96, 2;\nadd.u64 b, %97, %104;\n"
    "wgmma.mma_async.sync.aligned.m64n192k16.f32.bf16.bf16 {"
      "%0, %1, %2, %3, %4, %5, %6, %7, %8, %9, %10, %11, %12, %13, %14, %15, "
      "%16, %17, %18, %19, %20, %21, %22, %23, %24, %25, %26, %27, %28, %29, %30, %31, "
      "%32, %33, %34, %35, %36, %37, %38, %39, %40, %41, %42, %43, %44, %45, %46, %47, "
      "%48, %49, %50, %51, %52, %53, %54, %55, %56, %57, %58, %59, %60, %61, %62, %63, "
      "%64, %65, %66, %67, %68, %69, %70, %71, %72, %73, %74, %75, %76, %77, %78, %79, "
      "%80, %81, %82, %83, %84, %85, %86, %87, %88, %89, %90, %91, %92, %93, %94, %95"
      "}, a, b, t, 1, 1, 0, 1;\n"
    "wgmma.commit_group.sync.aligned;\nwgmma.wait_group.sync.aligned 1;\n"
    "add.u64 a, %96, 4;\nadd.u64 b, %97, 2*%104;\n"
    "wgmma.mma_async.sync.aligned.m64n192k16.f32.bf16.bf16 {"
      "%0, %1, %2, %3, %4, %5, %6, %7, %8, %9, %10, %11, %12, %13, %14, %15, "
      "%16, %17, %18, %19, %20, %21, %22, %23, %24, %25, %26, %27, %28, %29, %30, %31, "
      "%32, %33, %34, %35, %36, %37, %38, %39, %40, %41, %42, %43, %44, %45, %46, %47, "
      "%48, %49, %50, %51, %52, %53, %54, %55, %56, %57, %58, %59, %60, %61, %62, %63, "
      "%64, %65, %66, %67, %68, %69, %70, %71, %72, %73, %74, %75, %76, %77, %78, %79, "
      "%80, %81, %82, %83, %84, %85, %86, %87, %88, %89, %90, %91, %92, %93, %94, %95"
      "}, a, b, t, 1, 1, 0, 1;\n"
    "setp.ne.u32 q, %99, 0;\n@q mbarrier.arrive.shared::cta.b64 _, [%98];\n@q mbarrier.arrive.shared::cta.b64 _, [%98];\n@q mbarrier.arrive.shared::cta.b64 _, [%106];\n@q mbarrier.arrive.shared::cta.b64 _, [%106];\n"
    "mbarrier.test_wait.parity.shared::cta.b64 p, [%102], %103;\n"
    "mbarrier.test_wait.parity.shared::cta.b64 r, [%100], %101;\nand.pred p, p, r;\n"
    "add.u64 a, %96, 6;\nadd.u64 b, %97, 3*%104;\n"
    "wgmma.mma_async.sync.aligned.m64n192k16.f32.bf16.bf16 {"
      "%0, %1, %2, %3, %4, %5, %6, %7, %8, %9, %10, %11, %12, %13, %14, %15, "
      "%16, %17, %18, %19, %20, %21, %22, %23, %24, %25, %26, %27, %28, %29, %30, %31, "
      "%32, %33, %34, %35, %36, %37, %38, %39, %40, %41, %42, %43, %44, %45, %46, %47, "
      "%48, %49, %50, %51, %52, %53, %54, %55, %56, %57, %58, %59, %60, %61, %62, %63, "
      "%64, %65, %66, %67, %68, %69, %70, %71, %72, %73, %74, %75, %76, %77, %78, %79, "
      "%80, %81, %82, %83, %84, %85, %86, %87, %88, %89, %90, %91, %92, %93, %94, %95"
      "}, a, b, t, 1, 1, 0, 1;\n"
    "wgmma.commit_group.sync.aligned;\n"
    "@p bra.uni DN;\nmov.u32 n, 0;\nWT: mbarrier.try_wait.parity.shared::cta.b64 p, [%102], %103;\nmbarrier.try_wait.parity.shared::cta.b64 r, [%100], %101;\nand.pred p, p, r;\n@p bra.uni DN;\nadd.u32 n, n, 1;\nsetp.lt.u32 p, n, 0x100000;\n@p bra.uni WT;\nDN:\n"
    "}\n"
      :
      "+f"(d[0]), "+f"(d[1]), "+f"(d[2]), "+f"(d[3]), "+f"(d[4]), "+f"(d[5]), "+f"(d[6]), "+f"(d[7]),
      "+f"(d[8]), "+f"(d[9]), "+f"(d[10]), "+f"(d[11]), "+f"(d[12]), "+f"(d[13]), "+f"(d[14]), "+f"(d[15]),
      "+f"(d[16]), "+f"(d[17]), "+f"(d[18]), "+f"(d[19]), "+f"(d[20]), "+f"(d[21]), "+f"(d[22]), "+f"(d[23]),
      "+f"(d[24]), "+f"(d[25]), "+f"(d[26]), "+f"(d[27]), "+f"(d[28]), "+f"(d[29]), "+f"(d[30]), "+f"(d[31]),
      "+f"(d[32]), "+f"(d[33]), "+f"(d[34]), "+f"(d[35]), "+f"(d[36]), "+f"(d[37]), "+f"(d[38]), "+f"(d[39]),
      "+f"(d[40]), "+f"(d[41]), "+f"(d[42]), "+f"(d[43]), "+f"(d[44]), "+f"(d[45]), "+f"(d[46]), "+f"(d[47]),
      "+f"(d[48]), "+f"(d[49]), "+f"(d[50]), "+f"(d[51]), "+f"(d[52]), "+f"(d[53]), "+f"(d[54]), "+f"(d[55]),
      "+f"(d[56]), "+f"(d[57]), "+f"(d[58]), "+f"(d[59]), "+f"(d[60]), "+f"(d[61]), "+f"(d[62]), "+f"(d[63]),
      "+f"(d[64]), "+f"(d[65]), "+f"(d[66]), "+f"(d[67]), "+f"(d[68]), "+f"(d[69]), "+f"(d[70]), "+f"(d[71]),
      "+f"(d[72]), "+f"(d[73]), "+f"(d[74]), "+f"(d[75]), "+f"(d[76]), "+f"(d[77]), "+f"(d[78]), "+f"(d[79]),
      "+f"(d[80]), "+f"(d[81]), "+f"(d[82]), "+f"(d[83]), "+f"(d[84]), "+f"(d[85]), "+f"(d[86]), "+f"(d[87]),
      "+f"(d[88]), "+f"(d[89]), "+f"(d[90]), "+f"(d[91]), "+f"(d[92]), "+f"(d[93]), "+f"(d[94]), "+f"(d[95])
      : "l"(da), "l"(db), "r"(rel), "r"(doR), "r"(fa), "r"(pa), "r"(fb), "r"(pb), "n"(BSTEP), "r"(acc), "r"(rela) : "memory");
    else static_assert(W < 0, "variant not generated");
  }
};

#define NPRE 2
#define KV_T0 4000
#define KV2T 2000
#define XSD 400
#define CSD 600
#define ZW 300
#define TP_T 5000
#define PF2_D 200
#define PF_D 600
#define LKI 14
#define LEAD 4
#define PA 1
#define XE 1
#define TAE 0
#define HD 300
#define YD 600
#define HP0 3500
#define HPD 450
#define NSLEEP 100
#define MAP 4
#define EARLY 0

namespace {

constexpr int kS = 2048, kD = 640, kF = 1536;
constexpr int A_SLOT = 8192, B_SLOT = 24576, W_SLOT = 20480;
constexpr int OFF_A = 0;
constexpr int OFF_B = OFF_A + 10 * A_SLOT;
constexpr int XB_PL = 2112;
constexpr int CV_KE = 4224, CV_KO = CV_KE + 4160;
constexpr int CV_SZ = CV_KO + 4160;
constexpr int OFF_CV = OFF_B + 5 * B_SLOT;
constexpr int OFF_CS = OFF_CV + 2 * CV_SZ;
constexpr int OFF_XS = OFF_CS + 1536;
constexpr int OFF_BAR = OFF_XS + 512;
constexpr int SMEM_BYTES = OFF_BAR + 512;
static_assert(SMEM_BYTES <= 232448, "smem");
constexpr int OFF_RT = OFF_CS + 768;
constexpr int BAR_AF = OFF_BAR, BAR_BF = OFF_BAR + 8 * 10, BAR_WF = OFF_BAR + 8 * 15, BAR_ST = OFF_BAR + 8 * 21, BAR_XF = OFF_BAR + 8 * 23;
constexpr int BAR_ZP = OFF_BAR + 8 * 25, BAR_DUMMY = OFF_BAR + 8 * 27, BAR_PART = OFF_BAR + 8 * 28, BAR_WO = OFF_BAR + 8 * 29;
constexpr int BAR_YT = OFF_BAR + 8 * 30, BAR_KV2 = OFF_BAR + 8 * 31, BAR_XS = OFF_BAR + 8 * 32, BAR_HOLD = OFF_BAR + 8 * 33, BAR_ZG = OFF_BAR + 8 * 34;
constexpr int OFF_TAG = OFF_BAR + 8 * 35;
constexpr int BAR_HV = OFF_BAR + 8 * 36;
constexpr int BAR_HR = BAR_HV + 64, BAR_B2 = OFF_BAR + 8 * 26;
constexpr int BAR_XL = OFF_CS - 16;
constexpr int BAR_AE = OFF_BAR + 8 * 45, BAR_BE = OFF_BAR + 8 * 53, BAR_WE = OFF_BAR + 8 * 58;
constexpr int NB_WG = 1, NB_G1 = 3, NB_WO = 4, NB_CD = 5, NB_Z = 6, NB_C = 7, NB_KU = 8, NB_SV = 9, NB_PC = 11, NB_KF = 12, NB_G1D = 13, NB_KU2 = 14, NB_KL = 15;

#define NB_SV2(h) ((h) ? NB_KU2 : NB_KU)

constexpr int CNT_KV = 0, CNT_WO = 4, CNT_Z = 8;
struct Scratch {
  uint8_t kvx[kD * 4096];
  uint8_t z2[4 * 32 * 24576];
  uint8_t h[32 * 12 * 8192];
  uint8_t wo[4 * 12 * 20480];
  uint8_t y[kD * 4096];
  uint4 zstat[32 * 128];
  uint2 xstat[kS];
  uint32_t colsum[kF];
  uint32_t cnt[32];
  uint32_t hflag[32 * 32];
  uint32_t epoch[136];

};
__device__ __align__(1024) Scratch g_scr;
#define TSP
#define TSA
#define TR(i)
#define STAMP(i)
#define STAMPE(i)
#define STAMP2(i)
#define STAMPW(i)

struct Params {
  Scratch* scr;
  int by_smid;
  const __nv_bfloat16 *x, *k, *v, *shift, *ssmk, *ssmD, *wsp, *bsp, *wout;
  __nv_bfloat16* out;
  CUtensorMap tmX, tmW, tmWsp, tmY, tmKV;
  uint16_t job[132];
};

__device__ __forceinline__ uint64_t mkdesc(uint32_t addr, uint32_t lbo, uint32_t sbo, uint32_t swz) {
  return (uint64_t)((addr & 0x3FFFF) >> 4) | ((uint64_t)(lbo >> 4) << 16) | ((uint64_t)(sbo >> 4) << 32) | ((uint64_t)swz << 62);
}
#define WG_FENCE() asm volatile("wgmma.fence.sync.aligned;" ::: "memory")
#define WG_COMMIT() asm volatile("wgmma.commit_group.sync.aligned;" ::: "memory")
#define WG_WAIT(n) asm volatile("wgmma.wait_group.sync.aligned %0;" ::"n"(n) : "memory")
template <int N> __device__ __forceinline__ void acc_fence(float* d) {
#pragma unroll
  for (int i = 0; i < N; i++) asm volatile("" : "+f"(d[i])::"memory");
}
__device__ __forceinline__ void mbar_init(uint32_t bar, int cnt) { asm volatile("mbarrier.init.shared::cta.b64 [%0], %1;" ::"r"(bar), "r"(cnt) : "memory"); }
__device__ __forceinline__ void mbar_expect(uint32_t bar, uint32_t bytes) { asm volatile("mbarrier.arrive.expect_tx.shared::cta.b64 _, [%0], %1;" ::"r"(bar), "r"(bytes) : "memory"); }
__device__ __forceinline__ void mbar_arrive(uint32_t bar) { asm volatile("mbarrier.arrive.shared::cta.b64 _, [%0];" ::"r"(bar) : "memory"); }
__device__ __forceinline__ void mbar_arrive_if(uint32_t bar, bool c) {
  asm volatile("{\n.reg .pred p;\nsetp.ne.u32 p, %1, 0;\n@p mbarrier.arrive.shared::cta.b64 _, [%0];\n}\n" ::"r"(bar), "r"((uint32_t)c) : "memory");
}
__device__ __forceinline__ bool mbar_try(uint32_t bar, uint32_t parity) {
  uint32_t ok;
  asm volatile("{\n.reg .pred p;\nmbarrier.try_wait.parity.shared::cta.b64 p, [%1], %2;\nselp.u32 %0, 1, 0, p;\n}\n" : "=r"(ok) : "r"(bar), "r"(parity) : "memory");
  return ok;
}
__device__ __forceinline__ void die() { asm volatile("st.volatile.global.u32 [%0], %1;" ::"l"(0ull), "r"(0) : "memory"); }
template <bool G = false> __device__ __forceinline__ void spin_guard(uint32_t& n, uint32_t = 0) { if (G && ++n == (1u << 20)) die(); }
template <bool G = false> __device__ __forceinline__ void mbar_wait(uint32_t bar, uint32_t parity) {
  uint32_t t0 = 0;
#pragma unroll 1
  while (!mbar_try(bar, parity)) spin_guard<G>(t0, bar);
}
__device__ __forceinline__ void mbar_wait2(uint32_t b0, uint32_t p0, uint32_t b1, uint32_t p1) { mbar_wait(b0, p0); mbar_wait(b1, p1); }
__device__ __forceinline__ int tid_now() { int v; asm volatile("mov.u32 %0, %%tid.x;" : "=r"(v)); return v & 127; }
__device__ __forceinline__ bool elect_one() {
  uint32_t p;
  asm volatile("{\n.reg .pred P;\nelect.sync _|P, 0xffffffff;\nselp.u32 %0, 1, 0, P;\n}\n" : "=r"(p));
  return p;
}
__device__ __forceinline__ void bar_sync(int id, int n) { asm volatile("bar.sync %0, %1;" ::"r"(id), "r"(n) : "memory"); }
__device__ __forceinline__ void bar_arrive(int id, int n) { asm volatile("bar.arrive %0, %1;" ::"r"(id), "r"(n) : "memory"); }
__device__ __forceinline__ void fence_async_smem() { asm volatile("fence.proxy.async.shared::cta;" ::: "memory"); }
__device__ __forceinline__ void bulk_g2s(uint32_t dst, const void* src, uint32_t bytes, uint32_t bar) {
  asm volatile("cp.async.bulk.shared::cluster.global.mbarrier::complete_tx::bytes [%0], [%1], %2, [%3];" ::"r"(dst), "l"(src), "r"(bytes), "r"(bar) : "memory");
}
__device__ __forceinline__ void bulk_s2g(void* dst, uint32_t src, uint32_t bytes) {
  asm volatile("cp.async.bulk.global.shared::cta.bulk_group [%0], [%1], %2;" ::"l"(dst), "r"(src), "r"(bytes) : "memory");
}
__device__ __forceinline__ void tma2d(uint32_t dst, const CUtensorMap* m, int c0, int c1, uint32_t bar) {
  asm volatile("cp.async.bulk.tensor.2d.shared::cluster.global.mbarrier::complete_tx::bytes [%0], [%1, {%3, %4}], [%2];" ::"r"(dst), "l"(m), "r"(bar), "r"(c0), "r"(c1) : "memory");
}
__device__ __forceinline__ void tma3d(uint32_t dst, const CUtensorMap* m, int c0, int c1, int c2, uint32_t bar) {
  asm volatile("cp.async.bulk.tensor.3d.shared::cluster.global.mbarrier::complete_tx::bytes [%0], [%1, {%3, %4, %5}], [%2];" ::"r"(dst), "l"(m), "r"(bar), "r"(c0), "r"(c1), "r"(c2) : "memory");
}
__device__ __forceinline__ uint4 ld_ll4(const void* p) {
  uint64_t a, b;
  asm volatile("ld.relaxed.gpu.global.v2.u64 {%0,%1}, [%2];" : "=l"(a), "=l"(b) : "l"(p) : "memory");
  return make_uint4((uint32_t)a, (uint32_t)(a >> 32), (uint32_t)b, (uint32_t)(b >> 32));
}
__device__ __forceinline__ void st_ll4(void* p, uint32_t a, uint32_t b, uint32_t c, uint32_t d) {
  asm volatile("st.relaxed.gpu.global.v2.u64 [%0], {%1,%2};" ::"l"(p), "l"(a | ((uint64_t)b << 32)), "l"(c | ((uint64_t)d << 32)) : "memory");
}
__device__ __forceinline__ void st_ll2(void* p, uint32_t a, uint32_t b) { asm volatile("st.relaxed.gpu.global.u64 [%0], %1;" ::"l"(p), "l"(a | ((uint64_t)b << 32)) : "memory"); }
__device__ __forceinline__ void wgmma_colsum(float* d, uint64_t da, uint64_t db) {
  asm volatile("{\n.reg .pred p;\nsetp.ne.b32 p, 1, 0;\nwgmma.mma_async.sync.aligned.m64n8k16.f32.bf16.bf16 {%0, %1, %2, %3}, %4, %5, p, 1, 1, 1, 0;\n}\n"
               : "+f"(d[0]), "+f"(d[1]), "+f"(d[2]), "+f"(d[3]) : "l"(da), "l"(db));
}
__device__ __forceinline__ void prefetch_l2(const void* p) { asm volatile("prefetch.global.L2 [%0];" ::"l"(p)); }
template <bool SLEEP = true> __device__ __forceinline__ void pace(uint32_t& t, uint32_t dt) {
  t += dt;
  while ((int32_t)((uint32_t)clock() - t) < 0) { if (SLEEP) __nanosleep(NSLEEP); }
}
__device__ __forceinline__ void red_release(uint32_t* p) { asm volatile("red.release.gpu.global.add.u32 [%0], 1;" ::"l"(p) : "memory"); }
__device__ __forceinline__ uint4 ldg4(const void* p) { uint4 v; asm volatile("ld.global.v4.u32 {%0,%1,%2,%3}, [%4];" : "=r"(v.x), "=r"(v.y), "=r"(v.z), "=r"(v.w) : "l"(p) : "memory"); return v; }
__device__ __forceinline__ uint32_t ldg1(const void* p) { uint32_t v; asm volatile("ld.global.u32 %0, [%1];" : "=r"(v) : "l"(p) : "memory"); return v; }
__device__ __forceinline__ void stg4_if(void* p, uint32_t a, uint32_t b, uint32_t c, uint32_t d, bool on) {
  asm volatile("{\n.reg .pred p;\nsetp.ne.u32 p, %5, 0;\n@p st.global.v4.u32 [%0], {%1,%2,%3,%4};\n}\n" ::"l"(p), "r"(a), "r"(b), "r"(c), "r"(d), "r"((uint32_t)on) : "memory");
}
template <int OFF> __device__ __forceinline__ uint32_t lds32(uint32_t a) { uint32_t v; asm volatile("ld.shared.u32 %0, [%1+%2];" : "=r"(v) : "r"(a), "n"(OFF)); return v; }
__device__ __forceinline__ uint4 lds128(uint32_t a) { uint4 v; asm volatile("ld.shared.v4.u32 {%0,%1,%2,%3}, [%4];" : "=r"(v.x), "=r"(v.y), "=r"(v.z), "=r"(v.w) : "r"(a) : "memory"); return v; }
__device__ __forceinline__ float2 lds64f(uint32_t a) { float2 v; asm volatile("ld.shared.v2.f32 {%0,%1}, [%2];" : "=f"(v.x), "=f"(v.y) : "r"(a) : "memory"); return v; }
__device__ __forceinline__ void sts64f(uint32_t a, float x, float y) { asm volatile("st.shared.v2.f32 [%0], {%1,%2};" ::"r"(a), "f"(x), "f"(y) : "memory"); }
__device__ __forceinline__ void sts32(uint32_t a, uint32_t x) { asm volatile("st.shared.u32 [%0], %1;" ::"r"(a), "r"(x) : "memory"); }
__device__ __forceinline__ void sts128(uint32_t a, uint32_t x, uint32_t y, uint32_t z, uint32_t w) { asm volatile("st.shared.v4.u32 [%0], {%1,%2,%3,%4};" ::"r"(a), "r"(x), "r"(y), "r"(z), "r"(w) : "memory"); }
__device__ __forceinline__ void stsm4(uint32_t a, uint32_t r0, uint32_t r1, uint32_t r2, uint32_t r3) {
  asm volatile("stmatrix.sync.aligned.m8n8.x4.shared.b16 [%0], {%1,%2,%3,%4};" ::"r"(a), "r"(r0), "r"(r1), "r"(r2), "r"(r3) : "memory");
}
__device__ __forceinline__ void stsm4t(uint32_t a, uint32_t r0, uint32_t r1, uint32_t r2, uint32_t r3) {
  asm volatile("stmatrix.sync.aligned.m8n8.x4.trans.shared.b16 [%0], {%1,%2,%3,%4};" ::"r"(a), "r"(r0), "r"(r1), "r"(r2), "r"(r3) : "memory");
}
__device__ __forceinline__ void ldsm4t(uint32_t* r, uint32_t a) {
  asm volatile("ldmatrix.sync.aligned.m8n8.x4.trans.shared.b16 {%0,%1,%2,%3}, [%4];" : "=r"(r[0]), "=r"(r[1]), "=r"(r[2]), "=r"(r[3]) : "r"(a) : "memory");
}
__device__ __forceinline__ uint32_t pack2(float lo, float hi) { uint32_t r; asm("cvt.rn.bf16x2.f32 %0, %1, %2;" : "=r"(r) : "f"(hi), "f"(lo)); return r; }
__device__ __forceinline__ float bf_lo(uint32_t u) { return __uint_as_float(u << 16); }
__device__ __forceinline__ float bf_hi(uint32_t u) { return __uint_as_float(u & 0xffff0000u); }
__device__ __forceinline__ uint32_t hmul2(uint32_t a, uint32_t b) { uint32_t r; asm("mul.rn.bf16x2 %0, %1, %2;" : "=r"(r) : "r"(a), "r"(b)); return r; }
__device__ __forceinline__ uint32_t hfma2(uint32_t a, uint32_t b, uint32_t c) { uint32_t r; asm("fma.rn.bf16x2 %0, %1, %2, %3;" : "=r"(r) : "r"(a), "r"(b), "r"(c)); return r; }
__device__ __forceinline__ uint32_t prmt(uint32_t a, uint32_t b, uint32_t s) { return __byte_perm(a, b, s); }

__device__ __forceinline__ uint32_t ld_relaxed(const uint32_t* p) { uint32_t v; asm volatile("ld.relaxed.gpu.global.u32 %0, [%1];" : "=r"(v) : "l"(p) : "memory"); return v; }
__device__ __forceinline__ void acquire_fence() { asm volatile("fence.acquire.gpu;\nfence.proxy.async.global;" ::: "memory"); }
__device__ __forceinline__ uint32_t load_epoch(const Params& p, int idx, int lane) { return ld_relaxed(&p.scr->epoch[idx + (((lane * lane) & 3) == 2 ? 1 : 0)]); }
template <bool G, class L, class C>
__device__ __forceinline__ auto poll(L load, C ok) {
  uint32_t t0 = 0;
  auto a = load();
#pragma unroll 1
  while (!__all_sync(0xffffffff, ok(a))) { spin_guard<G>(t0); a = load(); }
  return a;
}
__device__ __forceinline__ void poll_flags4(const uint32_t* flags, uint32_t tag, int lane) {
  poll<false>([&]() { return ld_relaxed(flags + (lane & 3) * 8); }, [&](uint32_t v) { return v == tag; });
  acquire_fence();
}
__device__ __forceinline__ void st_relaxed(uint32_t* p, uint32_t v) { asm volatile("st.relaxed.gpu.global.u32 [%0], %1;" ::"l"(p), "r"(v) : "memory"); }
__device__ __forceinline__ uint32_t tag8(uint32_t tag) { return (tag & 127) | 128; }
__device__ __forceinline__ uint32_t tagged(float v, uint32_t t8) { return (__float_as_uint(v) & ~255u) | t8; }
__device__ __forceinline__ void reset_sector(uint32_t* f) { st_ll4(f, 0, 0, 0, 0); st_ll4(f + 4, 0, 0, 0, 0); }
template <bool G = false> __device__ __forceinline__ void poll_counter(const uint32_t* cnt, uint32_t target) {
  poll<G>([&]() { return ld_relaxed(cnt); }, [&](uint32_t v) { return v == target; });
  acquire_fence();
}

__device__ __forceinline__ uint32_t hadd2(uint32_t a, uint32_t b) { uint32_t r; asm("add.rn.bf16x2 %0, %1, %2;" : "=r"(r) : "r"(a), "r"(b)); return r; }
__device__ __forceinline__ uint32_t htanh2(uint32_t a) { uint32_t r; asm("tanh.approx.bf16x2 %0, %1;" : "=r"(r) : "r"(a)); return r; }
__device__ __forceinline__ void red_relaxed(uint32_t* p) { asm volatile("red.relaxed.gpu.global.add.u32 [%0], 1;" ::"l"(p) : "memory"); }
__device__ __forceinline__ void bulk_commit_wait() { asm volatile("cp.async.bulk.commit_group;\ncp.async.bulk.wait_group 0;" ::: "memory"); }

__device__ __forceinline__ int g3_block(int cb, int it) { return it < 3 ? cb * 3 + it : (it - 3 < cb * 3 ? it - 3 : it); }

#define GSTAMP(m, i)
struct NoHook { __device__ __forceinline__ void operator()(int = 0) const {} };
template <int N, int MODE, class F = NoHook, class F0 = NoHook>
__device__ __forceinline__ void gemm_seg(float* d, uint32_t sb, uint64_t db0, int i0, int i1, int s, uint32_t pb, uint32_t doR, uint32_t acc TSP, F hook = F(), F0 pre = F0()) {
  constexpr bool G3 = MODE == 2 || MODE == 4;
  constexpr int RA = (MODE == 1 || MODE == 3) ? 2 : (PA && MODE == 2);
  constexpr int W = MODE <= 2 ? 2 : 1, RC = (MODE == 2 || (PA && MODE == 4)) ? 1 : 2, NS = G3 ? 6 : 5, BSTEP = G3 ? 320 : 128;
  const uint64_t da0 = mkdesc(sb + OFF_A, 16, 1024, 1);
  auto sa = [](int i) { return MODE == 1 ? (i + 3) & 7 : (G3 && i >= 9 ? i - 9 : i); };
  auto fa = [&](int i) { return sb + (MODE == 2 ? (i < 3 ? BAR_HR : BAR_HV + 8 * (i - 3)) : BAR_AF + 8 * sa(i)); };
  auto pa = [](int i) { return MODE == 1 ? ((i >> 3) & 1) ^ 1 : MODE == 2 && i >= 9; };
  auto fb = [&](int s_) { return sb + (G3 ? BAR_WF : BAR_BF) + 8 * s_; };
  auto db = [&](int s_) { return db0 + (G3 ? (s_ >= 3 ? s_ - 3 : s_ + 3) * (W_SLOT >> 4) : s_ * (B_SLOT >> 4)); };
  const uint32_t dummy = sb + BAR_DUMMY;
  auto ea = [&](int i) { return MODE == 2 ? (i == 2 ? sb + BAR_B2 : dummy) : (MODE == 3 && i >= 8 ? dummy : sb + BAR_AE + 8 * sa(i)); };
  uint32_t rel = dummy, rela = dummy;
  acc_fence<N / 2>(d);
  pre();
  if (W == 2) mbar_wait(fa(i0), pa(i0));
  mbar_wait(fb(s), pb);
  WG_FENCE();
#pragma unroll 1
  for (int i = i0; i < i1 - 1; i++) {
    GSTAMP(MODE, i);
    const int n = s + 1 == NS ? 0 : s + 1;
    if (n == 0) pb ^= 1;
    KB<N>::template run<W, RC, RA, BSTEP>(d, da0 + sa(i) * (A_SLOT >> 4), db(s), rel, rela, doR, fa(i + 1), pa(i + 1), fb(n), pb, acc);
    rel = G3 ? (i < 6 ? sb + BAR_WE + 8 * s : dummy) : sb + BAR_BE + 8 * s;
    rela = ea(i);
    s = n;
    acc = 1;
  }
  hook();
  GSTAMP(MODE, i1 - 1);
  KB<N>::template run<0, RC, RA, BSTEP>(d, da0 + sa(i1 - 1) * (A_SLOT >> 4), db(s), rel, rela, doR, 0, 0, 0, 0, 1);
  WG_WAIT(0);
  GSTAMP(MODE, i1);
  acc_fence<N / 2>(d);
  if (MODE != 2 && !(PA && MODE == 4)) {
    rel = sb + (G3 ? BAR_WE : BAR_BE) + 8 * s;
    mbar_arrive_if(rel, doR);
    mbar_arrive_if(rel, doR);
    if (RA) { mbar_arrive_if(ea(i1 - 1), doR); mbar_arrive_if(ea(i1 - 1), doR); }
  }
}

__device__ __forceinline__ uint32_t val_off(int lane) { return lane * 32 + ((lane >> 2) & 1) * 16 + (lane >> 3) * 4; }
template <int NK, int PAD = 0, class F>
__device__ __forceinline__ void validate(uint32_t a, uint32_t par, uint32_t rt, F reload) {
  uint32_t t0 = 0;
#pragma unroll 1
  while (true) {
    uint32_t v[NK], any = 0;
#pragma unroll
    for (int i = 0; i < NK; i++) asm volatile("ld.shared.u32 %0, [%1];" : "=r"(v[i]) : "r"(a + i * 1024 + (i >> 1) * PAD) : "memory");
#pragma unroll
    for (int i = 0; i < NK; i++) any |= v[i] ^ par;
    if (!__any_sync(0xffffffff, any & 1)) break;
    spin_guard(t0);
    fence_async_smem();
    __syncwarp();
    if (elect_one()) { mbar_init(rt, 1); fence_async_smem(); mbar_expect(rt, NK * 1024); reload(); }
    __syncwarp();
    mbar_wait(rt, 0);
    __syncwarp();
    if (elect_one()) asm volatile("mbarrier.inval.shared::cta.b64 [%0];" ::"r"(rt) : "memory");
  }
}
__device__ __forceinline__ uint32_t part_addr(uint32_t sb, int j, int t) { const int q = j * 128 + t; return sb + OFF_B + 5 * W_SLOT + (q / 80) * 2560 + (q % 80) * 16; }
__device__ __forceinline__ uint32_t swz_base(uint32_t img, int w, int lane) { return img + (w * 16 + (lane & 15)) * 128 + (((lane >> 4) ^ lane) & 7) * 16; }

template <bool STATS>
__device__ __forceinline__ void gelu_tile(const float* d, uint32_t* z, float* st, uint32_t cs0, float2 s0, float2 s1, uint32_t done) {
  const float kA = 0.7978845608028654f, kB = 0.7978845608028654f * 0.044715f;
  const float ra = s0.y, rb = s1.y;
  const float a1 = kA * ra, a3 = kB * ra * ra * ra, b1 = kA * rb, b3 = kB * rb * rb * rb;
  const uint32_t c1[2] = {pack2(a1, a1), pack2(b1, b1)}, c3[2] = {pack2(a3, a3), pack2(b3, b3)};
  const float m[2] = {-s0.x, -s1.x};
  uint32_t S[2][2], Q[2][2];
#pragma unroll
  for (int j = 0; j < 24; j++) {
    if (!STATS && j && j % 6 == 0) mbar_wait(done, 0);
    const float2 cs = lds64f(cs0 + j * 32);
#pragma unroll
    for (int r = 0; r < 2; r++) {
      const uint32_t v = pack2(fmaf(m[r], cs.x, d[4 * j + 2 * r]), fmaf(m[r], cs.y, d[4 * j + 2 * r + 1]));
      uint32_t y = hfma2(v, htanh2(hmul2(v, hfma2(hmul2(v, v), c3[r], c1[r]))), v);
      asm volatile("" : "+r"(y));
      z[2 * j + r] = y;
      if (STATS) {
        S[r][j & 1] = j < 2 ? y : hadd2(S[r][j & 1], y);
        Q[r][j & 1] = j < 2 ? hmul2(y, y) : hfma2(y, y, Q[r][j & 1]);
      }
    }
  }
  if (STATS) {
#pragma unroll
    for (int r = 0; r < 2; r++) {
      st[2 * r] = (bf_lo(S[r][0]) + bf_hi(S[r][0])) + (bf_lo(S[r][1]) + bf_hi(S[r][1]));
      st[2 * r + 1] = (bf_lo(Q[r][0]) + bf_hi(Q[r][0])) + (bf_lo(Q[r][1]) + bf_hi(Q[r][1]));
    }
  }
}

__device__ __forceinline__ float2 quad_sum(const float* st, int t) {
  const bool o = t & 1;
  float s = (o ? st[2] : st[0]) + __shfl_xor_sync(0xffffffff, o ? st[0] : st[2], 1);
  float q = (o ? st[3] : st[1]) + __shfl_xor_sync(0xffffffff, o ? st[1] : st[3], 1);
  s += __shfl_xor_sync(0xffffffff, s, 2);
  q += __shfl_xor_sync(0xffffffff, q, 2);
  return make_float2(s, q);
}
template <int Q> __device__ __forceinline__ void conv_load(uint32_t* a, uint32_t ab) {
  a[0] = lds32<512 * Q>(ab);       a[1] = lds32<512 * Q + 256>(ab);  a[2] = lds32<512 * Q + 16>(ab);   a[3] = lds32<512 * Q + 272>(ab);
  a[4] = lds32<512 * Q + 32>(ab);  a[5] = lds32<512 * Q + 288>(ab);  a[6] = lds32<512 * Q + 48>(ab);   a[7] = lds32<512 * Q + 304>(ab);
  a[8] = lds32<512 * Q + 64>(ab);  a[9] = lds32<512 * Q + 320>(ab);  a[10] = lds32<512 * Q + 80>(ab);  a[11] = lds32<512 * Q + 336>(ab);
  a[12] = lds32<512 * Q + 96>(ab); a[13] = lds32<512 * Q + 352>(ab); a[14] = lds32<512 * Q + 112>(ab); a[15] = lds32<512 * Q + 368>(ab);
}
template <int Q, int L> __device__ __forceinline__ void conv_step(float* d, uint32_t (*a)[16], uint32_t ab, uint64_t db) {
  WG_FENCE();
#pragma unroll
  for (int s = 0; s < 4; s++) WG<128 - 16 * Q>::rs(d, a[Q] + 4 * s, db + s + 16 * Q);
  WG_COMMIT();
  WG_WAIT(1);
  if (L >= 0) conv_load<(L >= 0 ? L : 0)>(a[L >= 0 ? L : 0], ab);
  if (Q == 0) WG_WAIT(0);
}

__device__ __forceinline__ void final_load_x(uint32_t (*xw)[10], const __nv_bfloat16* x0, int t) {
#pragma unroll
  for (int r = 0; r < 2; r++) {
    const __nv_bfloat16* q = x0 + r * 8 * kD;
    const uint4 u = ldg4(q + t * 8), v = ldg4(q + 32 + t * 8);
    asm volatile("ld.global.v2.u32 {%0,%1}, [%2];" : "=r"(xw[r][8]), "=r"(xw[r][9]) : "l"(q + 64 + t * 4) : "memory");
    xw[r][0] = u.x; xw[r][1] = u.y; xw[r][2] = u.z; xw[r][3] = u.w;
    xw[r][4] = v.x; xw[r][5] = v.y; xw[r][6] = v.z; xw[r][7] = v.w;
  }
}
template <class F>
__device__ __forceinline__ void final_out(const float* d, const uint32_t (*xw)[10], const uint32_t* rn, const float* c, uint32_t yt, __nv_bfloat16* o0, int w, int lane, F wait_y) {
  const int r8 = lane & 7, mi = lane >> 3, t = lane & 3;
  const uint32_t ya = yt + ((mi >> 1) * 8 + r8) * 128 + (((2 * w + (mi & 1)) ^ r8) << 4);
#pragma unroll
  for (int q = 0; q < 3; q++) {
    const int n = q < 2 ? 8 : 4;
    uint32_t gt[8], y[8];
#pragma unroll
    for (int e = 0; e < n; e++) {
      const int i = q * 8 + e;
      const uint32_t h = pack2(d[2 * i] * c[i & 1], d[2 * i + 1] * c[i & 1]);
      gt[e] = hmul2(hfma2(h, htanh2(h), h), hfma2(xw[i & 1][i >> 1], rn[i & 1], rn[2 + (i & 1)]));
      if (q == 0) asm volatile("" : "+r"(gt[e]));
    }
    if (q == 0) wait_y();
    ldsm4t(y, ya + q * 4096);
    if (q < 2) ldsm4t(y + 4, ya + q * 4096 + 2048);
#pragma unroll
    for (int e = 0; e < n; e++) y[e] = hfma2(gt[e], y[e], xw[e & 1][q * 4 + (e >> 1)]);
#pragma unroll
    for (int r = 0; r < 2; r++) {
      __nv_bfloat16* o = o0 + r * 8 * kD;
      if (q < 2) stg4_if(o + q * 32 + t * 8, y[r], y[2 + r], y[4 + r], y[6 + r], true);
      else asm volatile("st.global.v2.u32 [%0], {%1,%2};" ::"l"(o + 64 + t * 4), "r"(y[r]), "r"(y[2 + r]) : "memory");
    }
  }
}

struct Taps { uint4 r0, r1; uint32_t n0, n1, dd; };
__device__ __forceinline__ void load_taps(Taps& k, const Params& p, int ch, int tid) {
  const uint4* kp = (const uint4*)(p.ssmk + (size_t)ch * kS);
  k.r0 = ldg4(kp + tid); k.r1 = ldg4(kp + 128 + tid);
  k.n0 = ldg1(kp + tid + 1); k.n1 = tid < 127 ? ldg1(kp + 129 + tid) : 0u;
  k.dd = __bfloat16_as_ushort(p.ssmD[ch]);
}
__device__ __forceinline__ void convx_copy(const Params& p, uint32_t cv, uint32_t bar, int ch) {
  bulk_g2s(cv, p.scr->kvx + (size_t)ch * 4096, 2048, bar);
  bulk_g2s(cv + XB_PL, p.scr->kvx + (size_t)ch * 4096 + 2048, 2048, bar);
}
__device__ __forceinline__ void convx_issue(const Params& p, uint32_t sb, int h, int ch) {
  if (elect_one()) { mbar_expect(sb + BAR_XL + 8 * h, 4096); convx_copy(p, sb + OFF_CV + (1 - h) * CV_SZ, sb + BAR_XL + 8 * h, ch); }
}
__device__ __forceinline__ void convx_finish(const Params& p, uint32_t sb, int h, int ch, int i, uint32_t par, int lane) {
  const uint32_t cv = sb + OFF_CV + (1 - h) * CV_SZ, rt = sb + BAR_XL - 16 + 8 * h;
  mbar_wait(sb + BAR_XL + 8 * h, i & 1);
  validate<4, XB_PL - 2048>(cv + lane * 32, par, rt, [&]() { convx_copy(p, cv, rt, ch); });
  if (elect_one()) mbar_arrive(sb + BAR_XF + 8 * h);
}
__device__ __forceinline__ void zero_pads(uint32_t cv, int lane) {
  if (lane < 8) sts128(cv + (lane >> 2) * XB_PL + 2048 + (lane & 3) * 16, 0, 0, 0, 0);
  else if (lane < 12) sts128(cv + ((lane & 2) ? CV_KO : CV_KE) + (lane & 1) * 16, 0, 0, 0, 0);
  fence_async_smem();
  __syncwarp();
}
__device__ __forceinline__ int y_row(int c) {
  const int cc = c % 80;
  return c - cc + (cc & 1) + (cc < 64 ? (cc & 32) + ((cc >> 1) & 3) * 8 + ((cc >> 3) & 3) * 2 : 64 + ((cc >> 1) & 1) * 8 + ((cc >> 2) & 3) * 2);
}
struct KvRegs { uint32_t k[11], v[8]; uint4 sh; };
__device__ __forceinline__ void kv_load(KvRegs& q, const __nv_bfloat16* kp, const __nv_bfloat16* vp, const __nv_bfloat16* sp, bool halo) {
#pragma unroll
  for (int i = 0; i < 11; i++) q.k[i] = (i >= 3 || halo) ? ldg1(kp + i * kD) : 0u;
#pragma unroll
  for (int i = 0; i < 8; i++) q.v[i] = ldg1(vp + i * kD);
  q.sh = ldg4(sp);
}
__device__ __forceinline__ void kv_calc(const KvRegs& q, uint32_t* o) {
  const uint32_t w0 = prmt(q.sh.x, q.sh.z, 0x5410), w1 = prmt(q.sh.x, q.sh.z, 0x7632), w2 = prmt(q.sh.y, q.sh.w, 0x5410), w3 = prmt(q.sh.y, q.sh.w, 0x7632);
  uint32_t r[8];
#pragma unroll
  for (int i = 0; i < 8; i++) r[i] = hmul2(hfma2(q.k[i + 3], w0, hfma2(q.k[i + 2], w1, hfma2(q.k[i + 1], w2, hmul2(q.k[i], w3)))), q.v[i]);
#pragma unroll
  for (int i = 0; i < 4; i++) { o[i] = prmt(r[7 - 2 * i], r[6 - 2 * i], 0x5410); o[4 + i] = prmt(r[7 - 2 * i], r[6 - 2 * i], 0x7632); }
}
__device__ __forceinline__ void kv_put(const uint32_t* o, uint32_t oa, uint32_t tm, uint32_t tb) {
  sts128(oa, (o[0] & tm) | tb, o[1], o[2], o[3]);
  sts128(oa + 2048, (o[4] & tm) | tb, o[5], o[6], o[7]);
}

__device__ __forceinline__ void kv_store(const Params& p, uint32_t src, int tb, int unit) {
  asm volatile("cp.async.bulk.tensor.3d.global.shared::cta.bulk_group [%0, {%2, %3, %4}], [%1];" ::"l"(&p.tmKV), "r"(src), "r"((63 - tb) * 16), "r"(unit * 32), "r"(0) : "memory");
}
__device__ __forceinline__ uint32_t kv_stage_addr(int w, int lane) { return ((3 - w) & 1) * 1024 + lane * 32 + ((((3 - w) >> 1) ^ (lane >> 2)) & 1) * 16; }

template <class F>
__device__ __forceinline__ void conv_service(const Params& p, uint32_t sb, int h, int ch, uint32_t par, int lane, F mid) {
#pragma unroll 1
  for (int i = 0; i < 2 + h; i++, ch += 128) {
    bar_sync(NB_SV + h, 160);
    if (i < h) convx_issue(p, sb, h, ch + 128);
    uint8_t* dst = p.scr->y + (size_t)y_row(ch) * 4096;
    bar_sync(NB_SV2(h), 160);
    if (elect_one()) {
      bulk_s2g(dst, sb + OFF_A + 9 * A_SLOT + h * 4096, 4096);
      bulk_commit_wait();
    }
    __syncwarp();
    if (i > h) break;
    if (i == h) { mid(); mbar_wait(sb + BAR_KV2, 0); convx_issue(p, sb, h, ch + 128); }
    convx_finish(p, sb, h, ch + 128, i + 1, par, lane);
  }
}
__device__ __forceinline__ void conv_worker(const Params& p, Taps& k, uint32_t sb, int h, int ch0, int w, int lane, int tid, int rb, int cb TSP) {
  const uint32_t cv = sb + OFF_CV + (1 - h) * CV_SZ, yb0 = sb + OFF_A + 9 * A_SLOT + h * 4096, xbar = sb + BAR_XF + 8 * h;
  const int n = 2 + h, nbar = NB_WG + h;
  const int g = lane >> 2, t = lane & 3, w0 = w & 1, w1 = w >> 1;
  const uint32_t ab = cv + ((g & 1) ? CV_KE : CV_KO) + 32 + 2 * (64 * w0 + 8 * w1 + ((g - 15) & ~1) + 2 * t);
  const uint32_t scA = cv + (w1 ? CV_KO : CV_KE) + 32, scB = scA + 2048;
  const int dl = (t >> 1) ^ 1, col = lane & 7, mi = lane >> 3;
  if (h == 0) mbar_wait(xbar, 0);
  TR(26);
#pragma unroll 1
  for (int i = 0; i < n; i++) {
    if (tid == 0) {
      k.r0.x = (k.r0.x & 0xffff0000u) | (pack2(bf_lo(k.r0.x) + bf_lo(k.dd), 0.f) & 0xffffu);
      sts32(cv + CV_KO + 28, k.r0.x << 16);
    }
    sts128(cv + CV_KE + 32 + tid * 16, k.r0.x, k.r0.y, k.r0.z, k.r0.w);
    sts128(cv + CV_KO + 32 + tid * 16, prmt(k.r0.x, k.r0.y, 0x5432), prmt(k.r0.y, k.r0.z, 0x5432), prmt(k.r0.z, k.r0.w, 0x5432), prmt(k.r0.w, k.n0, 0x5432));
    sts128(cv + CV_KE + 2080 + tid * 16, k.r1.x, k.r1.y, k.r1.z, k.r1.w);
    sts128(cv + CV_KO + 2080 + tid * 16, prmt(k.r1.x, k.r1.y, 0x5432), prmt(k.r1.y, k.r1.z, 0x5432), prmt(k.r1.z, k.r1.w, 0x5432), prmt(k.r1.w, k.n1, 0x5432));
    TR(30 + i * 10);
    if (i + 1 < n) load_taps(k, p, ch0 + (i + 1) * 128, tid);
    bar_sync(nbar, 128);
    TR(31 + i * 10);
    const uint64_t db = mkdesc(cv + (i & 0x1000), XB_PL, 128, 0);
    float d[64];
    uint32_t a[8][16];
    conv_load<7>(a[7], ab);
    conv_load<6>(a[6], ab);
    conv_load<5>(a[5], ab);
    conv_load<4>(a[4], ab);
#pragma unroll
    for (int j = 0; j < 64; j++) d[j] = 0.f;
    if (i == 0) STAMPW(h ? 43 : 8);
    TR(32 + i * 10);
    mbar_wait2(xbar, i & 1, sb + (i + 1 < n ? BAR_ZG : (h ? BAR_HOLD : BAR_HR)), 0);
    if (i == 0) STAMPW(h ? 51 : 7);
    TR(33 + i * 10);
    conv_step<7, -1>(d, a, ab, db); conv_step<6, -1>(d, a, ab, db); conv_step<5, -1>(d, a, ab, db); conv_step<4, 3>(d, a, ab, db);
    conv_step<3, 2>(d, a, ab, db); conv_step<2, 1>(d, a, ab, db); conv_step<1, 0>(d, a, ab, db); conv_step<0, -1>(d, a, ab, db);
    acc_fence<64>(d);
    TR(34 + i * 10);
    bar_arrive(NB_SV + h, 160);
    if (i == 0) mbar_wait(sb + BAR_YT, 0);
    const uint32_t par = lds32<0>(sb + OFF_TAG);
    TR(35 + i * 10);
    float E[16][2];
#pragma unroll
    for (int j = 0; j < 15; j++) { E[j][0] = d[4 * j] + d[4 * j + 6]; E[j][1] = d[4 * j + 1] + d[4 * j + 7]; }
    E[15][0] = d[60]; E[15][1] = d[61];
    if (w0 == 0) {
#pragma unroll
      for (int j = 8; j < 16; j++) sts64f(scA + (j - 8) * 256 + lane * 8, E[j][0], E[j][1]);
    } else {
      const uint32_t a = scB - dl * 256 + (lane ^ 2) * 8;
#pragma unroll
      for (int j = 1; j < 8; j++) sts64f(a + j * 256, E[j][0], E[j][1]);
      sts64f(scB + (dl ? 7 * 256 : 0) + (lane ^ 2) * 8, dl ? E[8][0] : E[0][0], dl ? E[8][1] : E[0][1]);
    }
    TR(36 + i * 10);
    bar_sync(nbar, 128);
    uint32_t pk[8];
    const bool tg = w1 == 0 && g == 0;
    const uint32_t tm = tg ? ~0x10001u : ~0u, tb = tg && (par & 1) ? 0x10001u : 0;
    if (w0 == 0) {
#pragma unroll
      for (int j = 0; j < 8; j++) { const float2 v = lds64f(scB + j * 256 + lane * 8); pk[j] = (pack2(E[j][0] + v.x, E[j][1] + v.y) & tm) | tb; }
      const uint32_t ya = yb0 + 32 * (127 - (8 * mi + col)) + 16 * w1;
      stsm4t(ya, pk[0], pk[1], pk[2], pk[3]);
      stsm4t(ya - 1024, pk[4], pk[5], pk[6], pk[7]);
    } else {
      const uint32_t a0 = scA - dl * 256 + (lane ^ 2) * 8;
#pragma unroll
      for (int j = 9; j < 16; j++) { const float2 v = lds64f(a0 + (j - 8) * 256); pk[j - 8] = (pack2(E[j][0] + v.x, E[j][1] + v.y) & tm) | tb; }
      const float2 v = lds64f(scA + (dl ? 7 * 256 : 0) + (lane ^ 2) * 8);
      pk[0] = (pack2((dl ? 0.f : E[8][0]) + v.x, (dl ? 0.f : E[8][1]) + v.y) & tm) | tb;
      const uint32_t yb = yb0 + 32 * (127 - (92 + 8 * mi + col)) + 16 * w1;
      const uint32_t ya = (mi == 0 && col < 4) ? yb0 + 32 * (3 - col) + 16 * w1 : yb + 1024;
      stsm4t(ya, pk[0], pk[1], pk[2], pk[3]);
      stsm4t(yb, pk[4], pk[5], pk[6], pk[7]);
    }
    TR(37 + i * 10);
    fence_async_smem();
    bar_arrive(NB_SV2(h), 160);
    if (i + 1 < n) bar_sync(nbar, 128);
    TR(38 + i * 10);
    STAMPW((h ? 40 : 5) + i);
    if (i == 0 && h == 0) {
      const int tn = tid_now();
      {
        const int ln = tn & 31, t0 = (rb * 2 + (cb & 1)) * 32 + w * 8, c0 = (cb >> 1) * 320 + 192 + ln * 2;
        KvRegs q0, q1;
        uint32_t o[8];
        kv_load(q0, p.k + (size_t)(t0 - 3) * kD + c0, p.v + (size_t)t0 * kD + c0, p.shift + c0 * 4, t0 > 0);
        kv_load(q1, p.k + (size_t)(t0 - 3) * kD + c0 + 64, p.v + (size_t)t0 * kD + c0 + 64, p.shift + c0 * 4 + 256, t0 > 0);
        const uint32_t oa = sb + OFF_A + 8 * A_SLOT + kv_stage_addr(w, ln), km = w >= 2 ? ~1u : ~0u, kb = w >= 2 ? lds32<0>(sb + OFF_TAG) & 1 : 0;
        kv_calc(q0, o);
        kv_put(o, oa, km, kb);
        kv_calc(q1, o);
        kv_put(o, oa + 4096, km, kb);
        fence_async_smem();
        bar_arrive(NB_KL, 160);
      }
      STAMPW(56);
      const int u = (tn >> 3) % 5, kg = rb * 3 + (tn < 120 ? (tn >> 3) / 5 : 0), c = u < 4 ? (u >> 1) * 10 + (u & 1) * 4 : 8, o2 = u < 4 ? 2 : 10;
      const uint4* wp = (const uint4*)(p.wout + (size_t)(kg * 8 + (tn & 7)) * kD + cb * 160) + c;
      const uint4 w0 = ldg4(wp), w1 = ldg4(wp + 1), w2 = ldg4(wp + o2), w3 = ldg4(wp + o2 + 1);
      uint8_t* dst = p.scr->wo + (size_t)cb * (12 * W_SLOT) + kg * 2560 + c * 128 + (tn & 7) * 16;
      const bool f = u < 4, on = tn < 120;
      stg4_if(dst, w0.x, f ? w1.x : w0.z, f ? w2.x : w1.x, f ? w3.x : w1.z, on);
      stg4_if(dst + 128, w0.y, f ? w1.y : w0.w, f ? w2.y : w1.y, f ? w3.y : w1.w, on);
      stg4_if(dst + o2 * 128, f ? w0.z : w2.x, f ? w1.z : w2.z, f ? w2.z : w3.x, w3.z, on);
      stg4_if(dst + o2 * 128 + 128, f ? w0.w : w2.y, f ? w1.w : w2.w, f ? w2.w : w3.y, w3.w, on);
      bar_arrive(NB_WO, 160);
    }
  }
}

struct U6 { uint64_t a, b, c; };
__device__ __forceinline__ uint64_t ld_ll2(const void* p) { uint64_t a; asm volatile("ld.relaxed.gpu.global.u64 %0, [%1];" : "=l"(a) : "l"(p) : "memory"); return a; }
__device__ __forceinline__ void gather_colsum(const Params& p, uint32_t sb, int part, int cb, uint32_t tag8, int lane) {
  const uint32_t* src = p.scr->colsum + (uint32_t)((part ? 0 : 768) + cb * 192 + lane * 2);
  const uint64_t t2 = tag8 * 0x100000001ull;
  const U6 v = poll<false>([&]() { return U6{ld_ll2(src), ld_ll2(src + 64), ld_ll2(src + 128)}; },
                                    [&](const U6& u) { return (((u.a ^ t2) | (u.b ^ t2) | (u.c ^ t2)) & 0xff000000ffull) == 0; });
  const uint32_t dst = sb + OFF_CS + (part ? 0 : 768) + lane * 8;
  asm volatile("st.shared.u64 [%0], %1;\nst.shared.u64 [%0+256], %2;\nst.shared.u64 [%0+512], %3;" ::"r"(dst), "l"(v.a), "l"(v.b), "l"(v.c) : "memory");
  __syncwarp();
  mbar_arrive_if(sb + BAR_ST + 8 * part, lane == 0);
}

__device__ __forceinline__ void helper_cta(const Params& p, uint32_t sb, int cb, int warp, int lane TSP) {
  constexpr int NS = 9, ONES = NS * B_SLOT, BF = ONES + 256, BE = BF + 8 * NS;
  if (warp < NS && elect_one()) {
    mbar_init(sb + BF + 8 * warp, 1); mbar_init(sb + BE + 8 * warp, 1);
    fence_async_smem();
    if (warp == 0) { mbar_expect(sb + BF, B_SLOT); tma3d(sb, &p.tmW, 0, 0, 12 + cb * 3, sb + BF); }
  }
  if (warp == 15) { sts32(sb + ONES + lane * 4, 0x3f803f80u); sts32(sb + ONES + 128 + lane * 4, 0x3f803f80u); fence_async_smem(); }
  __syncthreads();
  if (warp == 4) {
    int s = 1, ph = 1;
    uint32_t tp = clock() + HP0;
#pragma unroll 1
    for (int it = 1; it < 20; it++) {
      if (it >= 10) pace(tp, HPD);
      mbar_wait(sb + BE + 8 * s, ph);
      if (elect_one()) { mbar_expect(sb + BF + 8 * s, B_SLOT); tma3d(sb + s * B_SLOT, &p.tmW, 0, (it < 10 ? it : it - 10) * 64, (it < 10 ? 12 : 0) + cb * 3, sb + BF + 8 * s); }
      if (++s == NS) { s = 0; ph ^= 1; }
    }
  } else if (warp < 4) {
    const uint32_t tag = load_epoch(p, 128 + cb, lane) + 1;
    const uint64_t db = mkdesc(sb + ONES, 128, 128, 0);
    uint32_t* dst = p.scr->colsum + cb * 192 + warp * 16 + (lane >> 2);
    if ((lane & 3) == 0) {
#pragma unroll 1
      for (int j = 0; j < 12; j++) st_relaxed(dst + (j < 6 ? 768 : 0) + ((j % 6) >> 1) * 64 + (j & 1) * 8, 0);
    }
    int s = 0, ph = 0;
#pragma unroll 1
    for (int part = 0; part < 2; part++) {
      float d[12];
#pragma unroll
      for (int i = 0; i < 12; i++) d[i] = 0.f;
#pragma unroll 1
      for (int it = 0; it < 10; it++) {
        mbar_wait(sb + BF + 8 * s, ph);
        const uint64_t da = mkdesc(sb + s * B_SLOT, 8192, 1024, 1);
        WG_FENCE();
#pragma unroll
        for (int j = 0; j < 12; j++) wgmma_colsum(d + 4 * (j % 3), da + (j % 3) * 512 + (j / 3) * 128, db);
        WG_COMMIT();
        WG_WAIT(1);
        mbar_arrive_if(sb + BE + 8 * (s == 0 ? NS - 1 : s - 1), threadIdx.x == 0 && (it | part) != 0);
        if (++s == NS) { s = 0; ph ^= 1; }
      }
      WG_WAIT(0);
      acc_fence<12>(d);
      if ((lane & 3) == 0) {
#pragma unroll
        for (int j = 0; j < 6; j++) st_relaxed(dst + (part ? 0 : 768) + (j >> 1) * 64 + (j & 1) * 8, tagged(d[2 * j], tag8(tag)));
      }
      STAMPW(1 + part);
    }
    if (threadIdx.x == 0) *(volatile uint32_t*)&p.scr->epoch[128 + cb] = tag;
  }
}

__global__ void __launch_bounds__(512, 1) fused_kernel(const __grid_constant__ Params p) {
  extern __shared__ __align__(1024) uint8_t smem[];
  const int warp = __shfl_sync(0xffffffff, (int)(threadIdx.x >> 5), 0);
  const int lane = threadIdx.x & 31;
  const uint32_t sb = __shfl_sync(0xffffffff, (uint32_t)__cvta_generic_to_shared(smem), 0);
  const uint32_t tstart = clock();
  int b = blockIdx.x;
  if (p.by_smid) asm volatile("mov.u32 %0, %%smid;" : "=r"(b));
  b = __shfl_sync(0xffffffff, b, 0);
  const int job = p.job[b], lin = job & 255, cb = job >> 8 & 3, rb = job >> 10;
  if (elect_one()) {
    mbar_init(sb + OFF_BAR + 8 * warp, 1);
    if (lin < 128) {
      if (warp < NPRE) { fence_async_smem(); mbar_expect(sb + BAR_AF + 8 * warp, A_SLOT); tma2d(sb + OFF_A + warp * A_SLOT, &p.tmX, warp * 64, rb * 64, sb + BAR_AF + 8 * warp); }
      if (warp >= 10 && warp < 10 + NPRE) { fence_async_smem(); mbar_expect(sb + OFF_BAR + 8 * warp, B_SLOT); tma3d(sb + OFF_B + (warp - 10) * B_SLOT, &p.tmW, 0, (warp - 10) * 64, 12 + cb * 3, sb + OFF_BAR + 8 * warp); }
    }
    if (warp >= 2 && warp < 5) asm volatile("prefetch.tensormap [%0];" ::"l"(&p.tmX + warp) : "memory");
    mbar_init(sb + OFF_BAR + 128 + 8 * warp, 1);
    if (warp != 3) mbar_init(sb + OFF_BAR + 256 + 8 * warp, (0x2224444444441111ull >> (4 * warp)) & 15);
    mbar_init(sb + OFF_BAR + 384 + 8 * warp, 2);
    if (warp < 2) mbar_init(sb + BAR_XL + 8 * warp, 1);
    asm volatile("fence.mbarrier_init.release.cluster;" ::: "memory");
  }
  if (lin >= 128) { helper_cta(p, sb, cb, warp, lane TSA); return; }
  const int chb = (cb >> 1) * 320 + rb * 2 + (cb & 1);
  if (sb & 1023) die();
  __syncthreads();

  if (warp >= 12) {
    asm volatile("setmaxnreg.dec.sync.aligned.u32 32;");
    const uint8_t* z2s = p.scr->z2 + (size_t)cb * 32 * B_SLOT;
    const char* wq = (const char*)p.wsp + (rb * 64 + cb * 16 + (lane >> 1)) * (kS * 2) + (lane & 1) * 128;
    if (warp == 12) {
      int s = NPRE, ph = 1;
#pragma unroll 1
      for (int it = NPRE; it < 20; it++) {
        if (it >= 5) mbar_wait<true>(sb + BAR_BE + 8 * s, ph);
        if (it < 5 && elect_one()) { mbar_expect(sb + BAR_AF + 8 * it, A_SLOT); tma2d(sb + OFF_A + it * A_SLOT, &p.tmX, it * 64, rb * 64, sb + BAR_AF + 8 * it); }
        if (elect_one()) {
          mbar_expect(sb + BAR_BF + 8 * s, B_SLOT);
          tma3d(sb + OFF_B + s * B_SLOT, &p.tmW, 0, (it < 10 ? it : it - 10) * 64, (it < 10 ? 12 : 0) + cb * 3, sb + BAR_BF + 8 * s);
        }
        if (it == 4) {
#pragma unroll 1
          for (int i = 5; i < 10; i++)
            if (elect_one()) { mbar_expect(sb + BAR_AF + 8 * i, A_SLOT); tma2d(sb + OFF_A + i * A_SLOT, &p.tmX, i * 64, rb * 64, sb + BAR_AF + 8 * i); }
          bar_arrive(NB_KF, 160);
        }
        STAMP2(32 + it);
        if (++s == 5) { s = 0; ph ^= 1; }
      }
      const uint32_t ztarget = (load_epoch(p, lin, lane) + 1) * 128;
#pragma unroll 1
      for (int i = 0; i < LEAD; i++) {
        mbar_wait<true>(sb + BAR_AE + 8 * (3 + i), 0);
        if (elect_one()) { mbar_expect(sb + BAR_AF + 8 * (3 + i), A_SLOT); tma2d(sb + OFF_A + (3 + i) * A_SLOT, &p.tmWsp, i * 64, rb * 64, sb + BAR_AF + 8 * (3 + i)); }
      }
      mbar_wait<true>(sb + BAR_ZP, 0);
      poll_counter<true>(p.scr->cnt + CNT_Z, ztarget);
      STAMP(24);
#pragma unroll 1
      for (int it = 0; it < 32; it++) {
        mbar_wait<true>(sb + BAR_BE + 8 * s, ph);
        if (elect_one()) {
          mbar_expect(sb + BAR_BF + 8 * s, B_SLOT);
          bulk_g2s(sb + OFF_B + s * B_SLOT, z2s + it * B_SLOT, B_SLOT, sb + BAR_BF + 8 * s);
        }
        if (it == 0) STAMP(22);
        const int ia = it + LEAD - 1, sa = (ia + 3) & 7;
        if (it >= 1 && ia < 32) {
          mbar_wait<true>(sb + BAR_AE + 8 * sa, (ia >> 3) & 1);
          if (elect_one()) { mbar_expect(sb + BAR_AF + 8 * sa, A_SLOT); tma2d(sb + OFF_A + sa * A_SLOT, &p.tmWsp, ia * 64, rb * 64, sb + BAR_AF + 8 * sa); }
        }
        STAMP2(52 + it);
        if (++s == 5) { s = 0; ph ^= 1; }
      }
      mbar_wait<true>(sb + BAR_WO, 0);
      acquire_fence();
      s = 0;
#pragma unroll 1
      for (int it = 0; it < 12; it++) {
        if (it < 6) mbar_wait<true>(sb + BAR_BE + 8 * ((0x110443 >> (4 * it)) & 7), it < 3 ? 1 : 0);
        else mbar_wait<true>(sb + BAR_WE + 8 * s, 0);
        mbar_arrive_if(sb + BAR_HOLD, it == 0 && lane == 0);
        if (elect_one()) {
          mbar_expect(sb + BAR_WF + 8 * s, W_SLOT);
          bulk_g2s(sb + OFF_B + (s >= 3 ? s - 3 : s + 3) * W_SLOT, p.scr->wo + (size_t)(cb * 12 + g3_block(cb, it)) * W_SLOT, W_SLOT, sb + BAR_WF + 8 * s);
        }
        STAMP2(84 + it);
        if (++s == 6) s = 0;
      }
      mbar_wait<true>(sb + BAR_WE, 1);
    } else if (warp == 13) {
      const uint32_t tag = load_epoch(p, lin, lane) + 1;
      if (elect_one()) reset_sector(&p.scr->hflag[rb * 32 + cb * 8]);
      if (lane == 0) sts32(sb + OFF_TAG, tag8(tag));
      mbar_wait(sb + BAR_AF + 72, 0);
      { uint32_t tp = clock(); pace(tp, CSD); }
      gather_colsum(p, sb, 0, cb, tag8(tag), lane);
      STAMP(27);
      bar_sync(NB_Z, 160);
      if (elect_one()) {
        mbar_arrive(sb + BAR_ZG);
        bulk_s2g((void*)(z2s + rb * B_SLOT), sb + OFF_A, B_SLOT);
        bulk_commit_wait();
        mbar_arrive(sb + BAR_ZP);
        STAMPE(58);
        red_release(p.scr->cnt + CNT_Z);
      }
      __syncwarp();
      STAMP(28);
      {
        uint32_t tp = clock();
#pragma unroll 1
        for (int i = 1; i < 16; i++) {
          pace(tp, PF_D);
          prefetch_l2(wq + i * 256);
          if (i == LKI) bar_sync(NB_KL, 160);
          if ((i == LKI || i == LKI + 1) && elect_one()) {
            kv_store(p, sb + OFF_A + 8 * A_SLOT + (i - LKI) * 4096, rb * 2 + (cb & 1), (cb >> 1) * 5 + 3 + i - LKI);
            bulk_commit_wait();
            if (i > LKI) red_relaxed(p.scr->cnt + CNT_KV + 2 + (cb >> 1));
          }
          __syncwarp();
          if (i == LKI + 1) STAMP(59);
        }
      }
      if (!EARLY) poll_counter(p.scr->cnt + CNT_KV + 2 + (cb >> 1), tag * 64);
      if (elect_one()) mbar_arrive(sb + BAR_KV2);
      STAMP(34);
      const uint8_t* hs = p.scr->h + (size_t)rb * 12 * A_SLOT;
#pragma unroll 1
      for (int i = 0; i < 3; i++) {
        mbar_wait(sb + BAR_HR - 16 + 8 * i, 0);
        if (elect_one()) bulk_s2g((void*)(hs + (cb * 3 + i) * A_SLOT), sb + OFF_A + i * A_SLOT, A_SLOT);
      }
      if (elect_one()) {
        st_relaxed(&p.scr->hflag[rb * 32 + cb * 8], tag);
        bulk_commit_wait();
        mbar_arrive(sb + BAR_ZP);
      }
      __syncwarp();
      STAMP(20);
      if (!EARLY) poll_flags4(p.scr->hflag + rb * 32, tag, lane);
      { uint32_t tp = clock(); pace<false>(tp, HD); }
      STAMP(37);
#pragma unroll 1
      for (int it = 3; it < 12; it++) {
        const int s = it < 9 ? it : it - 9;
        if (it == 9) { if (PA) mbar_wait2(sb + BAR_PART, 0, sb + BAR_B2, 0); else bar_sync(NB_PC, 288); }
        if (elect_one()) { mbar_expect(sb + BAR_AF + 8 * s, A_SLOT); bulk_g2s(sb + OFF_A + s * A_SLOT, hs + g3_block(cb, it) * A_SLOT, A_SLOT, sb + BAR_AF + 8 * s); }
      }
      STAMP(21);
    } else if (warp == 14) {
      const uint32_t tag = load_epoch(p, lin, lane) + 1;
      const int tb = rb * 2 + (cb & 1), u0 = (cb >> 1) * 5;
      const uint32_t ks = sb + OFF_CV + CV_SZ, par = __shfl_sync(0xffffffff, tag, 0);
      {
        uint32_t tp = tstart;
        pace(tp, TP_T);
        const char* q = (const char*)p.ssmk + chb * 4096 + lane * 128;
        prefetch_l2(q); prefetch_l2(q + 64 * 4096);
      }
      mbar_wait2(sb + BAR_XS, 0, sb + BAR_ST, 0);
      bar_sync(NB_KU, 160);
      if (elect_one()) { kv_store(p, ks, tb, u0); kv_store(p, ks + 4096, tb, u0 + 1); bulk_commit_wait(); red_relaxed(p.scr->cnt + CNT_KV + (cb >> 1)); }
      __syncwarp();
      STAMP(35);
      bar_sync(NB_KU2, 160);
      if (elect_one()) { kv_store(p, ks + 8192, tb, u0 + 2); bulk_commit_wait(); }
      __syncwarp();
      zero_pads(ks, lane);
      bar_arrive(NB_G1D, 64);
      STAMP(30);
      {
        uint32_t tp = clock();
        const size_t o = (size_t)(tb * 32 + lane) * (kD * 2) + (u0 + 3) * 128;
        const char* r = (const char*)p.wout + (rb * 24 + min(lane, 23)) * (kD * 2) + cb * 320;
        const char* q = (const char*)p.ssmk + (chb + 128) * 4096 + lane * 128;
#pragma unroll 1
        for (int i = 0; i < 10; i++) {
          pace(tp, PF2_D);
          prefetch_l2(i < 3 ? q + i * 64 * 4096 : (i < 7 ? (const char*)((i & 1) ? p.k : p.v) + o + ((i - 3) >> 1) * 128 : r + (i - 7) * 128));
        }
      }
      conv_service(p, sb, 0, chb + 64, par, lane, NoHook());
      bar_sync(NB_CD, 64);
      STAMP(47);
      if (!EARLY) mbar_wait(sb + BAR_WE + 40, 0);
      { uint32_t tp = clock(); pace<false>(tp, YD); }
      if (elect_one()) {
        mbar_expect(sb + BAR_YT, 20480);
#pragma unroll 1
        for (int i = 0; i < 4; i++) tma2d(sb + OFF_CV + i * 5120, &p.tmY, rb * 64, cb * 160 + i * 40, sb + BAR_YT);
      }
      if (lane == 0) *(volatile uint32_t*)&p.scr->epoch[lin] = tag;
      STAMP(23);
    } else {
      const uint32_t tag = load_epoch(p, lin, lane) + 1;
      mbar_wait(sb + BAR_AF + 72, 0);
      { uint32_t tp = clock(); pace(tp, XSD); }
      {
        const uint32_t t8 = tag8(tag);
        const uint4 u = poll<false>([&]() { return ld_ll4(&p.scr->xstat[rb * 64 + lane * 2]); },
                                                [&](const uint4& v) { return (((v.x ^ t8) | (v.y ^ t8) | (v.z ^ t8) | (v.w ^ t8)) & 255u) == 0; });
        sts128(sb + OFF_XS + lane * 16, u.x, u.y, u.z, u.w);
      }
      __syncwarp();
      if (lane == 0) mbar_arrive(sb + BAR_XS);
      STAMP(25);
      const uint32_t par = __shfl_sync(0xffffffff, tag, 0);
      bar_sync(NB_G1D, 64);
      if (!EARLY) poll_counter(p.scr->cnt + CNT_KV + (cb >> 1), tag * 64);
      convx_issue(p, sb, 1, chb);
      convx_issue(p, sb, 0, chb + 64);
#pragma unroll 1
      for (int h = 1; h >= 0; h--) convx_finish(p, sb, h, chb + 64 - 64 * h, 0, par, lane);
      STAMP(48);
      gather_colsum(p, sb, 1, cb, tag8(tag), lane);
      STAMP(38);
      conv_service(p, sb, 1, chb, par, lane, [&]() {
        bar_sync(NB_WO, 160);
        if (elect_one()) red_release(p.scr->cnt + CNT_WO + cb);
        STAMP(49);
        poll_counter(p.scr->cnt + CNT_WO + cb, tag * 32);
        if (elect_one()) mbar_arrive(sb + BAR_WO);
        STAMP(46);
      });
      bar_arrive(NB_CD, 64);
    }
  } else if (warp >= 8) {
    const int w = warp & 3;
    {
      const int tid = tid_now();
      uint2* xs = &p.scr->xstat[rb * 64 + cb * 16 + (tid >> 3)];
      if ((tid & 7) == 0) st_ll2(xs, 0, 0);
      const uint32_t epoch = load_epoch(p, lin, lane);
      float sa[4] = {0.f, 0.f, 0.f, 0.f}, qa[4] = {0.f, 0.f, 0.f, 0.f};
#pragma unroll 1
      for (int i = 0; i < 10; i++) {
        mbar_wait(sb + BAR_AF + 8 * i, 0);
        const uint4 x4 = lds128(sb + OFF_A + i * A_SLOT + cb * 2048 + tid * 16);
        const uint32_t u[4] = {x4.x, x4.y, x4.z, x4.w};
#pragma unroll
        for (int e = 0; e < 4; e++) { const float a = bf_lo(u[e]), c = bf_hi(u[e]); sa[e] += a + c; qa[e] = fmaf(a, a, fmaf(c, c, qa[e])); }
      }
      float s = (sa[0] + sa[1]) + (sa[2] + sa[3]), q = (qa[0] + qa[1]) + (qa[2] + qa[3]);
#pragma unroll
      for (int o = 1; o <= 4; o <<= 1) { s += __shfl_xor_sync(0xffffffff, s, o); q += __shfl_xor_sync(0xffffffff, q, o); }
      const float m = s * (1.f / kD);
      const float r = rsqrtf(fmaxf(fmaf(-m, m, q * (1.f / kD)), 0.f) + 1e-5f);
      if ((tid & 7) == 0) st_ll2(xs, tagged(m, tag8(epoch + 1)), tagged(r, tag8(epoch + 1)));
      STAMPW(12); TR(70);
      fence_async_smem();
    }
    asm volatile("setmaxnreg.inc.sync.aligned.u32 160;");
    const unsigned short* bp = (const unsigned short*)p.bsp + rb * 64 + w * 16 + (lane >> 2);
    const uint32_t bias = bp[0] | ((uint32_t)bp[8] << 16);
    float d[96];
    uint32_t z[48];
    {
      const uint64_t db = mkdesc(sb + OFF_B, 8192, 1024, 1);
#pragma unroll
      for (int i = 0; i < 96; i++) d[i] = 0.f;
      bar_sync(NB_G1, 256);
      TR(71);
      gemm_seg<192, 3>(d, sb, db, 0, 10, 0, 0, tid_now() == 0, 0 TSA);
      mbar_arrive_if(sb + BAR_YT, tid_now() == 0);
      STAMPW(14); TR(74);
      mbar_wait2(sb + BAR_XS, 0, sb + BAR_ST + 8, 0);
      const uint32_t xa1 = sb + OFF_XS + (w * 16 + (lane >> 2)) * 8;
      gelu_tile<false>(d, z, nullptr, sb + OFF_CS + (lane & 3) * 8, lds64f(xa1), lds64f(xa1 + 64), sb + BAR_XS);
    }
#pragma unroll
    for (int j = 0; j < 96; j++) d[j] = (j & 2) ? bf_hi(bias) : bf_lo(bias);
    STAMPW(15); TR(76);
    gemm_seg<192, 1>(d, sb, mkdesc(sb + OFF_B, 8192, 1024, 1), 0, 32, 0, 0, tid_now() == 0, 1 TSA);
    STAMPW(16); TR(77);
    {
      const int l2 = tid_now() & 31;
      const uint32_t ha = swz_base(sb + OFF_A, w, l2);
      const bool tg = (l2 & 3) == (l2 >> 3);
      const uint32_t tm = tg ? ~1u : ~0u, tb = tg ? lds32<0>(sb + OFF_TAG) & 1 : 0;
#pragma unroll
      for (int j = 0; j < 24; j += 2) {
#pragma unroll
        for (int e = 0; e < 4; e++) z[2 * j + e] = hmul2(z[2 * j + e], pack2(d[4 * j + 2 * e], d[4 * j + 2 * e + 1]));
        stsm4((ha ^ ((j & 7) * 16)) + (j >> 3) * A_SLOT, (z[2 * j] & tm) | tb, (z[2 * j + 1] & tm) | tb, z[2 * j + 2], z[2 * j + 3]);
        if ((j & 7) == 6) {
          fence_async_smem();
          __syncwarp();
          mbar_arrive_if(sb + BAR_HR - 16 + (j >> 3) * 8, l2 == 0);
        }
      }
    }
    STAMPW(17); TR(78);
    const int t3 = tid_now();
    {
      mbar_wait(sb + BAR_HR, 0);
      gemm_seg<80, 4>(d, sb, mkdesc(sb + OFF_B, 2560, 128, 0), 0, 3, 0, 0, t3 == 0, 0 TSA);
      TR(79);
#pragma unroll
      for (int j = 0; j < 5; j++)
        sts128(part_addr(sb, j, t3), pack2(d[8 * j], d[8 * j + 1]), pack2(d[8 * j + 2], d[8 * j + 3]), pack2(d[8 * j + 4], d[8 * j + 5]), pack2(d[8 * j + 6], d[8 * j + 7]));
      bar_sync(NB_C, 128);
      mbar_arrive_if(sb + BAR_PART, t3 == 0);
      STAMPW(45); TR(80);
    }
    {
      const uint32_t par = __shfl_sync(0xffffffff, lds32<0>(sb + OFF_TAG), 0), a = sb + OFF_A + w * 2048 + val_off(t3 & 31);
      const uint8_t* hs = p.scr->h + (size_t)rb * 12 * A_SLOT + w * 2048;
      const uint32_t rt = sb + OFF_RT + 8 * w;
#pragma unroll 1
      for (int it = 3; it < 12; it++) {
        const int s = it < 9 ? it : it - 9;
        mbar_wait(sb + BAR_AF + 8 * s, 1);
        validate<2>(a + s * A_SLOT, par, rt, [&]() { bulk_g2s(sb + OFF_A + s * A_SLOT + w * 2048, hs + g3_block(cb, it) * A_SLOT, 2048, rt); });
        if (elect_one()) mbar_arrive(sb + BAR_HV + 8 * (it - 3));
        if (it == 3) STAMPW(26);
      }
      {
        const int l = t3 & 31;
        mbar_wait(sb + BAR_YT, 1);
        validate<5>(sb + OFF_CV + w * 5120 + (l >> 2) * 128 + ((2 * (l & 3)) ^ (l >> 2)) * 16, par, rt, [&]() { tma2d(sb + OFF_CV + w * 5120, &p.tmY, rb * 64, cb * 160 + w * 40, rt); });
        bar_sync(NB_C, 128);
        mbar_arrive_if(sb + BAR_PART, t3 == 0);
        STAMPW(57);
      }
    }
  } else {
    const int h = warp >> 2, w = warp & 3;
    Taps k;
    asm volatile("setmaxnreg.inc.sync.aligned.u32 160;");
    if (h == 0) {
      uint4* zs = &p.scr->zstat[rb * 128 + w * 8 + (lane >> 2)];
      if ((lane & 3) == 0) st_ll4(zs + cb * 32, 0, 0, 0, 0);
      float d[96];
      uint32_t z[48];
#pragma unroll
      for (int i = 0; i < 96; i++) d[i] = 0.f;
      gemm_seg<192, 0>(d, sb, mkdesc(sb + OFF_B, 8192, 1024, 1), 0, 10, 0, 0, tid_now() == 0, 0 TSA, [&]() { bar_arrive(NB_G1, 256); });
      STAMPW(1); TR(0);
      const int tid = tid_now(), lane = tid & 31, g = lane >> 2, t = lane & 3;
      if (TAE == 2) load_taps(k, p, chb + 64, tid);
      mbar_wait2(sb + BAR_XS, 0, sb + BAR_ST, 0);
      STAMPW(52); TR(1);
      const uint32_t xa1 = sb + OFF_XS + (w * 16 + g) * 8;
      const uint32_t tag = lds32<0>(sb + OFF_TAG);
      const float2 s0 = lds64f(xa1), s1 = lds64f(xa1 + 64);
      float st[4];
      gelu_tile<true>(d, z, st, sb + OFF_CS + 768 + t * 8, s0, s1, 0);
      TR(2);
      float2 sq = quad_sum(st, t);
      if (t < 2) st_ll2((uint2*)(zs + cb * 32) + t, tagged(sq.x, tag), __float_as_uint(sq.y));
      STAMPW(2); TR(3);
      { uint32_t tp = clock(); pace<false>(tp, ZW); }
      const uint4 u = poll<false>([&]() { return ld_ll4(zs + t * 32); }, [&](const uint4& v) { return (((v.x ^ tag) | (v.z ^ tag)) & 255u) == 0; });
      STAMPW(3); TR(10);
      st[0] = __uint_as_float(u.x); st[1] = __uint_as_float(u.y); st[2] = __uint_as_float(u.z); st[3] = __uint_as_float(u.w);
      sq = quad_sum(st, t);
      const float ca = 0.5f * ((t & 1) ? s1.y : s0.y), ma = sq.x * (1.f / 768.f);
      const float ra = ca * rsqrtf(fmaf(fmaxf(fmaf(-ma, ma, sq.y * (1.f / 768.f)), 0.f), ca * ca, 1e-5f));
      const uint32_t r2 = pack2(ra, ra);
      const float na = -ma * bf_lo(r2);
      const uint32_t n2 = pack2(na, na), r2o = __shfl_xor_sync(0xffffffff, r2, 1), n2o = __shfl_xor_sync(0xffffffff, n2, 1);
      const uint32_t fr[2] = {(t & 1) ? r2o : r2, (t & 1) ? r2 : r2o}, fn[2] = {(t & 1) ? n2o : n2, (t & 1) ? n2 : n2o};
      const uint32_t za = swz_base(sb + OFF_A, w, lane);
      TR(11);
      mbar_wait(sb + BAR_AE + 16, 0);
      TR(12);
#pragma unroll
      for (int j = 0; j < 24; j += 2)
        stsm4((za ^ ((j & 7) * 16)) + (j >> 3) * A_SLOT, hfma2(z[2 * j], fr[0], fn[0]), hfma2(z[2 * j + 1], fr[1], fn[1]), hfma2(z[2 * j + 2], fr[0], fn[0]), hfma2(z[2 * j + 3], fr[1], fn[1]));
      TR(14);
      fence_async_smem();
      bar_arrive(NB_Z, 160);
      STAMPW(4); TR(15);
      if (TAE == 0) load_taps(k, p, chb + 64, tid);
    } else {
      if (w == 0) zero_pads(sb + OFF_CV, lane);
      const uint32_t epoch = load_epoch(p, lin, lane);
      const int t0 = (rb * 2 + (cb & 1)) * 32 + w * 8, c0 = (cb >> 1) * 320 + lane * 2;
      const __nv_bfloat16* kp = p.k + (size_t)(t0 - 3) * kD + c0;
      const __nv_bfloat16* vp = p.v + (size_t)t0 * kD + c0;
      const __nv_bfloat16* sp = p.shift + c0 * 4;
      const uint32_t oa = sb + OFF_CV + CV_SZ + kv_stage_addr(w, lane);
      bar_sync(NB_KF, 160);
      uint32_t tp = tstart;
      pace(tp, KV_T0);
      KvRegs n0, n1;
      uint32_t o[8];
      kv_load(n0, kp, vp, sp, t0 > 0);
      kv_load(n1, kp + 64, vp + 64, sp + 256, t0 > 0);
      const uint32_t tm = w >= 2 ? ~1u : ~0u, tb = w >= 2 ? (epoch + 1) & 1 : 0;
      kv_calc(n0, o);
      kv_put(o, oa, tm, tb);
      kv_calc(n1, o);
      kv_put(o, oa + 4096, tm, tb);
      fence_async_smem();
      bar_arrive(NB_KU, 160);
      TR(0);
      pace(tp, KV2T);
      kv_load(n0, kp + 128, vp + 128, sp + 512, t0 > 0);
      load_taps(k, p, chb, tid_now());
      kv_calc(n0, o);
      kv_put(o, oa + 8192, tm, tb);
      fence_async_smem();
      bar_arrive(NB_KU2, 160);
      STAMPW(13); TR(1);
    }
    uint32_t xw[2][10];
    {
      const int tid = tid_now();
      if (XE) final_load_x(xw, p.x + (rb * 64 + w * 16 + ((tid & 31) >> 2)) * kD + cb * 160 + h * 80, tid & 3);
      conv_worker(p, k, sb, h, chb + 64 - 64 * h, w, tid & 31, tid, rb, cb TSA);
    }
    float d[40];
    const int t3 = tid_now();
    const uint32_t o0 = (rb * 64 + w * 16 + ((t3 & 31) >> 2)) * kD + cb * 160 + h * 80;
    float cf[2];
    uint32_t rn[4];
    const uint32_t xs_addr = sb + OFF_XS + (w * 16 + ((t3 & 31) >> 2)) * 8;
    TR(60);
    if (!PA || h == 0) {
      mbar_wait(sb + BAR_PART, 0);
      TR(61);
#pragma unroll
      for (int j = 0; j < 5; j++) {
        const uint4 v = lds128(PA ? part_addr(sb, j, t3) : sb + OFF_A + (h * 5 + j) * 2048 + t3 * 16);
        d[8 * j] = bf_lo(v.x); d[8 * j + 1] = bf_hi(v.x); d[8 * j + 2] = bf_lo(v.y); d[8 * j + 3] = bf_hi(v.y);
        d[8 * j + 4] = bf_lo(v.z); d[8 * j + 5] = bf_hi(v.z); d[8 * j + 6] = bf_lo(v.w); d[8 * j + 7] = bf_hi(v.w);
      }
      fence_async_smem();
      if (PA) { bar_sync(NB_WG, 128); mbar_arrive_if(sb + BAR_WE + 16, t3 == 0); }
      else bar_arrive(NB_PC, 288);
    } else {
#pragma unroll
      for (int j = 0; j < 40; j++) d[j] = 0.f;
    }
    TR(62);
    gemm_seg<80, 2>(d, sb, mkdesc(sb + OFF_B + h * 1280, 2560, 128, 0), PA && h ? 0 : 3, 12, PA && h ? 0 : 3, 0, t3 == 0, 1 TSA, NoHook(), [&]() {
      if (!XE) final_load_x(xw, p.x + o0, t3 & 3);
      const float2 s0 = lds64f(xs_addr), s1 = lds64f(xs_addr + 64);
      cf[0] = 0.25f * s0.y; cf[1] = 0.25f * s1.y;
      rn[0] = pack2(s0.y, s0.y); rn[1] = pack2(s1.y, s1.y);
      rn[2] = pack2(-s0.x * bf_lo(rn[0]), -s0.x * bf_lo(rn[0])); rn[3] = pack2(-s1.x * bf_lo(rn[1]), -s1.x * bf_lo(rn[1]));
    });
    STAMPW(h ? 18 : 10);
    TR(63);
    const int l3 = tid_now() & 31;
    final_out(d, xw, rn, cf, sb + OFF_CV + h * 10240, p.out + o0, w, l3, [&]() {
      STAMPW(h ? 44 : 9);
      TR(64);
      mbar_wait(sb + BAR_PART, 1);
      TR(65);
    });
    TR(66);
    mbar_arrive_if(sb + BAR_WE, t3 == 0);
  }
}

typedef CUresult (*EncodeFn)(CUtensorMap*, CUtensorMapDataType, cuuint32_t, void*, const cuuint64_t*, const cuuint64_t*, const cuuint32_t*,
                             const cuuint32_t*, CUtensorMapInterleave, CUtensorMapSwizzle, CUtensorMapL2promotion, CUtensorMapFloatOOBfill);

void encode(EncodeFn fn, CUtensorMap* m, const void* ptr, int rank, const cuuint64_t* dims, const cuuint64_t* strides, const cuuint32_t* box,
            CUtensorMapSwizzle swz = CU_TENSOR_MAP_SWIZZLE_128B) {
  const cuuint32_t es[3] = {1, 1, 1};
  fn(m, CU_TENSOR_MAP_DATA_TYPE_BFLOAT16, rank, const_cast<void*>(ptr), dims, strides, box, es, CU_TENSOR_MAP_INTERLEAVE_NONE,
     swz, CU_TENSOR_MAP_L2_PROMOTION_L2_128B, CU_TENSOR_MAP_FLOAT_OOB_FILL_NONE);
}

}

extern "C" void kernel_launch(void* const* d_in, const int* in_sizes, int n_in, void* d_out, int out_size) {
  (void)in_sizes; (void)n_in; (void)out_size;
  static EncodeFn enc = nullptr;
  static Scratch* scr = nullptr;
  static int sms = 0;
  if (!enc) {
    void* fn = nullptr;
    cudaDriverEntryPointQueryResult qr;
    cudaGetDriverEntryPoint("cuTensorMapEncodeTiled", &fn, cudaEnableDefault, &qr);
    enc = (EncodeFn)fn;
    cudaFuncSetAttribute(fused_kernel, cudaFuncAttributeMaxDynamicSharedMemorySize, SMEM_BYTES);
    cudaGetSymbolAddress((void**)&scr, g_scr);
    int dev = 0;
    cudaGetDevice(&dev);
    cudaDeviceGetAttribute(&sms, cudaDevAttrMultiProcessorCount, dev);
  }
  Params p;
  p.scr = scr;
  p.by_smid = sms == 132;
  for (int b = 0; b < 132; b++) {
    const int tp = b >> 1, t7 = (tp - 32) / 7;
    const int lin = tp < 32 ? ((tp & 7) ? (tp & 7) * 16 : 8) + (tp >> 3) * 2 + (b & 1)
                            : (tp < 60 ? (tp - 31 - t7 * 7) * 16 + 8 + t7 * 2 + (b & 1) : (tp < 62 ? 128 + (b & 3) : b - 124));
    const int cb = ((lin >> 4) & 1) * 2 + (lin & 1), rb = (lin >> 5) * 8 + ((lin >> 1) & 7);
    p.job[b] = lin < 128 ? lin | cb << 8 | rb << 10 : lin | (lin & 3) << 8;
  }
  p.x = (const __nv_bfloat16*)d_in[0];
  p.k = (const __nv_bfloat16*)d_in[1];
  p.v = (const __nv_bfloat16*)d_in[2];
  p.shift = (const __nv_bfloat16*)d_in[3];
  p.ssmk = (const __nv_bfloat16*)d_in[4];
  p.ssmD = (const __nv_bfloat16*)d_in[5];
  p.wsp = (const __nv_bfloat16*)d_in[8];
  p.bsp = (const __nv_bfloat16*)d_in[9];
  p.wout = (const __nv_bfloat16*)d_in[10];
  p.out = (__nv_bfloat16*)d_out;
  {
    const cuuint64_t dims[2] = {kD, kS}, st[1] = {kD * 2};
    const cuuint32_t box[2] = {64, 64};
    encode(enc, &p.tmX, d_in[0], 2, dims, st, box);
  }
  {
    const cuuint64_t dims[3] = {64, kD, kF / 64}, st[2] = {kF * 2, 128};
    const cuuint32_t box[3] = {64, 64, 3};
    encode(enc, &p.tmW, d_in[7], 3, dims, st, box);
  }
  {
    const cuuint64_t dims[2] = {kS, kS}, st[1] = {kS * 2};
    const cuuint32_t box[2] = {64, 64};
    encode(enc, &p.tmWsp, d_in[8], 2, dims, st, box);
  }
  {
    const cuuint64_t dims[2] = {kS, kD}, st[1] = {kS * 2};
    const cuuint32_t box[2] = {64, 40};
    encode(enc, &p.tmY, scr->y, 2, dims, st, box);
  }
  {
    const cuuint64_t dims[3] = {1024, kD / 2, 4}, st[2] = {8192, 2048};
    const cuuint32_t box[3] = {16, 32, 4};
    encode(enc, &p.tmKV, scr->kvx, 3, dims, st, box, CU_TENSOR_MAP_SWIZZLE_32B);
  }
  fused_kernel<<<132, 512, SMEM_BYTES, cudaStreamPerThread>>>(p);
}
```

```cpp
#include <cuda_runtime.h>
#include <cuda.h>
#include <cuda_bf16.h>
#include <stdint.h>

template <int N> struct WG;
template <> struct WG<16> {
  static __device__ __forceinline__ void rs(float* d, const uint32_t* a, uint64_t db) {
    asm volatile("{\n.reg .pred p;\nsetp.ne.b32 p, 1, 0;\nwgmma.mma_async.sync.aligned.m64n16k16.f32.bf16.bf16 {"
      "%0, %1, %2, %3, %4, %5, %6, %7"
      "}, {%8, %9, %10, %11}, %12, p, 1, 1, 0;\n}\n"
      :
      "+f"(d[0]), "+f"(d[1]), "+f"(d[2]), "+f"(d[3]), "+f"(d[4]), "+f"(d[5]), "+f"(d[6]), "+f"(d[7])
      : "r"(a[0]), "r"(a[1]), "r"(a[2]), "r"(a[3]), "l"(db));
  }
};
template <> struct WG<32> {
  static __device__ __forceinline__ void rs(float* d, const uint32_t* a, uint64_t db) {
    asm volatile("{\n.reg .pred p;\nsetp.ne.b32 p, 1, 0;\nwgmma.mma_async.sync.aligned.m64n32k16.f32.bf16.bf16 {"
      "%0, %1, %2, %3, %4, %5, %6, %7, %8, %9, %10, %11, %12, %13, %14, %15"
      "}, {%16, %17, %18, %19}, %20, p, 1, 1, 0;\n}\n"
      :
      "+f"(d[0]), "+f"(d[1]), "+f"(d[2]), "+f"(d[3]), "+f"(d[4]), "+f"(d[5]), "+f"(d[6]), "+f"(d[7]),
      "+f"(d[8]), "+f"(d[9]), "+f"(d[10]), "+f"(d[11]), "+f"(d[12]), "+f"(d[13]), "+f"(d[14]), "+f"(d[15])
      : "r"(a[0]), "r"(a[1]), "r"(a[2]), "r"(a[3]), "l"(db));
  }
};
template <> struct WG<48> {
  static __device__ __forceinline__ void rs(float* d, const uint32_t* a, uint64_t db) {
    asm volatile("{\n.reg .pred p;\nsetp.ne.b32 p, 1, 0;\nwgmma.mma_async.sync.aligned.m64n48k16.f32.bf16.bf16 {"
      "%0, %1, %2, %3, %4, %5, %6, %7, %8, %9, %10, %11, %12, %13, %14, %15, "
      "%16, %17, %18, %19, %20, %21, %22, %23"
      "}, {%24, %25, %26, %27}, %28, p, 1, 1, 0;\n}\n"
      :
      "+f"(d[0]), "+f"(d[1]), "+f"(d[2]), "+f"(d[3]), "+f"(d[4]), "+f"(d[5]), "+f"(d[6]), "+f"(d[7]),
      "+f"(d[8]), "+f"(d[9]), "+f"(d[10]), "+f"(d[11]), "+f"(d[12]), "+f"(d[13]), "+f"(d[14]), "+f"(d[15]),
      "+f"(d[16]), "+f"(d[17]), "+f"(d[18]), "+f"(d[19]), "+f"(d[20]), "+f"(d[21]), "+f"(d[22]), "+f"(d[23])
      : "r"(a[0]), "r"(a[1]), "r"(a[2]), "r"(a[3]), "l"(db));
  }
};
template <> struct WG<64> {
  static __device__ __forceinline__ void rs(float* d, const uint32_t* a, uint64_t db) {
    asm volatile("{\n.reg .pred p;\nsetp.ne.b32 p, 1, 0;\nwgmma.mma_async.sync.aligned.m64n64k16.f32.bf16.bf16 {"
      "%0, %1, %2, %3, %4, %5, %6, %7, %8, %9, %10, %11, %12, %13, %14, %15, "
      "%16, %17, %18, %19, %20, %21, %22, %23, %24, %25, %26, %27, %28, %29, %30, %31"
      "}, {%32, %33, %34, %35}, %36, p, 1, 1, 0;\n}\n"
      :
      "+f"(d[0]), "+f"(d[1]), "+f"(d[2]), "+f"(d[3]), "+f"(d[4]), "+f"(d[5]), "+f"(d[6]), "+f"(d[7]),
      "+f"(d[8]), "+f"(d[9]), "+f"(d[10]), "+f"(d[11]), "+f"(d[12]), "+f"(d[13]), "+f"(d[14]), "+f"(d[15]),
      "+f"(d[16]), "+f"(d[17]), "+f"(d[18]), "+f"(d[19]), "+f"(d[20]), "+f"(d[21]), "+f"(d[22]), "+f"(d[23]),
      "+f"(d[24]), "+f"(d[25]), "+f"(d[26]), "+f"(d[27]), "+f"(d[28]), "+f"(d[29]), "+f"(d[30]), "+f"(d[31])
      : "r"(a[0]), "r"(a[1]), "r"(a[2]), "r"(a[3]), "l"(db));
  }
};
template <> struct WG<80> {
  static __device__ __forceinline__ void rs(float* d, const uint32_t* a, uint64_t db) {
    asm volatile("{\n.reg .pred p;\nsetp.ne.b32 p, 1, 0;\nwgmma.mma_async.sync.aligned.m64n80k16.f32.bf16.bf16 {"
      "%0, %1, %2, %3, %4, %5, %6, %7, %8, %9, %10, %11, %12, %13, %14, %15, "
      "%16, %17, %18, %19, %20, %21, %22, %23, %24, %25, %26, %27, %28, %29, %30, %31, "
      "%32, %33, %34, %35, %36, %37, %38, %39"
      "}, {%40, %41, %42, %43}, %44, p, 1, 1, 0;\n}\n"
      :
      "+f"(d[0]), "+f"(d[1]), "+f"(d[2]), "+f"(d[3]), "+f"(d[4]), "+f"(d[5]), "+f"(d[6]), "+f"(d[7]),
      "+f"(d[8]), "+f"(d[9]), "+f"(d[10]), "+f"(d[11]), "+f"(d[12]), "+f"(d[13]), "+f"(d[14]), "+f"(d[15]),
      "+f"(d[16]), "+f"(d[17]), "+f"(d[18]), "+f"(d[19]), "+f"(d[20]), "+f"(d[21]), "+f"(d[22]), "+f"(d[23]),
      "+f"(d[24]), "+f"(d[25]), "+f"(d[26]), "+f"(d[27]), "+f"(d[28]), "+f"(d[29]), "+f"(d[30]), "+f"(d[31]),
      "+f"(d[32]), "+f"(d[33]), "+f"(d[34]), "+f"(d[35]), "+f"(d[36]), "+f"(d[37]), "+f"(d[38]), "+f"(d[39])
      : "r"(a[0]), "r"(a[1]), "r"(a[2]), "r"(a[3]), "l"(db));
  }
};
template <> struct WG<96> {
  static __device__ __forceinline__ void rs(float* d, const uint32_t* a, uint64_t db) {
    asm volatile("{\n.reg .pred p;\nsetp.ne.b32 p, 1, 0;\nwgmma.mma_async.sync.aligned.m64n96k16.f32.bf16.bf16 {"
      "%0, %1, %2, %3, %4, %5, %6, %7, %8, %9, %10, %11, %12, %13, %14, %15, "
      "%16, %17, %18, %19, %20, %21, %22, %23, %24, %25, %26, %27, %28, %29, %30, %31, "
      "%32, %33, %34, %35, %36, %37, %38, %39, %40, %41, %42, %43, %44, %45, %46, %47"
      "}, {%48, %49, %50, %51}, %52, p, 1, 1, 0;\n}\n"
      :
      "+f"(d[0]), "+f"(d[1]), "+f"(d[2]), "+f"(d[3]), "+f"(d[4]), "+f"(d[5]), "+f"(d[6]), "+f"(d[7]),
      "+f"(d[8]), "+f"(d[9]), "+f"(d[10]), "+f"(d[11]), "+f"(d[12]), "+f"(d[13]), "+f"(d[14]), "+f"(d[15]),
      "+f"(d[16]), "+f"(d[17]), "+f"(d[18]), "+f"(d[19]), "+f"(d[20]), "+f"(d[21]), "+f"(d[22]), "+f"(d[23]),
      "+f"(d[24]), "+f"(d[25]), "+f"(d[26]), "+f"(d[27]), "+f"(d[28]), "+f"(d[29]), "+f"(d[30]), "+f"(d[31]),
      "+f"(d[32]), "+f"(d[33]), "+f"(d[34]), "+f"(d[35]), "+f"(d[36]), "+f"(d[37]), "+f"(d[38]), "+f"(d[39]),
      "+f"(d[40]), "+f"(d[41]), "+f"(d[42]), "+f"(d[43]), "+f"(d[44]), "+f"(d[45]), "+f"(d[46]), "+f"(d[47])
      : "r"(a[0]), "r"(a[1]), "r"(a[2]), "r"(a[3]), "l"(db));
  }
};
template <> struct WG<112> {
  static __device__ __forceinline__ void rs(float* d, const uint32_t* a, uint64_t db) {
    asm volatile("{\n.reg .pred p;\nsetp.ne.b32 p, 1, 0;\nwgmma.mma_async.sync.aligned.m64n112k16.f32.bf16.bf16 {"
      "%0, %1, %2, %3, %4, %5, %6, %7, %8, %9, %10, %11, %12, %13, %14, %15, "
      "%16, %17, %18, %19, %20, %21, %22, %23, %24, %25, %26, %27, %28, %29, %30, %31, "
      "%32, %33, %34, %35, %36, %37, %38, %39, %40, %41, %42, %43, %44, %45, %46, %47, "
      "%48, %49, %50, %51, %52, %53, %54, %55"
      "}, {%56, %57, %58, %59}, %60, p, 1, 1, 0;\n}\n"
      :
      "+f"(d[0]), "+f"(d[1]), "+f"(d[2]), "+f"(d[3]), "+f"(d[4]), "+f"(d[5]), "+f"(d[6]), "+f"(d[7]),
      "+f"(d[8]), "+f"(d[9]), "+f"(d[10]), "+f"(d[11]), "+f"(d[12]), "+f"(d[13]), "+f"(d[14]), "+f"(d[15]),
      "+f"(d[16]), "+f"(d[17]), "+f"(d[18]), "+f"(d[19]), "+f"(d[20]), "+f"(d[21]), "+f"(d[22]), "+f"(d[23]),
      "+f"(d[24]), "+f"(d[25]), "+f"(d[26]), "+f"(d[27]), "+f"(d[28]), "+f"(d[29]), "+f"(d[30]), "+f"(d[31]),
      "+f"(d[32]), "+f"(d[33]), "+f"(d[34]), "+f"(d[35]), "+f"(d[36]), "+f"(d[37]), "+f"(d[38]), "+f"(d[39]),
      "+f"(d[40]), "+f"(d[41]), "+f"(d[42]), "+f"(d[43]), "+f"(d[44]), "+f"(d[45]), "+f"(d[46]), "+f"(d[47]),
      "+f"(d[48]), "+f"(d[49]), "+f"(d[50]), "+f"(d[51]), "+f"(d[52]), "+f"(d[53]), "+f"(d[54]), "+f"(d[55])
      : "r"(a[0]), "r"(a[1]), "r"(a[2]), "r"(a[3]), "l"(db));
  }
};
template <> struct WG<128> {
  static __device__ __forceinline__ void rs(float* d, const uint32_t* a, uint64_t db) {
    asm volatile("{\n.reg .pred p;\nsetp.ne.b32 p, 1, 0;\nwgmma.mma_async.sync.aligned.m64n128k16.f32.bf16.bf16 {"
      "%0, %1, %2, %3, %4, %5, %6, %7, %8, %9, %10, %11, %12, %13, %14, %15, "
      "%16, %17, %18, %19, %20, %21, %22, %23, %24, %25, %26, %27, %28, %29, %30, %31, "
      "%32, %33, %34, %35, %36, %37, %38, %39, %40, %41, %42, %43, %44, %45, %46, %47, "
      "%48, %49, %50, %51, %52, %53, %54, %55, %56, %57, %58, %59, %60, %61, %62, %63"
      "}, {%64, %65, %66, %67}, %68, p, 1, 1, 0;\n}\n"
      :
      "+f"(d[0]), "+f"(d[1]), "+f"(d[2]), "+f"(d[3]), "+f"(d[4]), "+f"(d[5]), "+f"(d[6]), "+f"(d[7]),
      "+f"(d[8]), "+f"(d[9]), "+f"(d[10]), "+f"(d[11]), "+f"(d[12]), "+f"(d[13]), "+f"(d[14]), "+f"(d[15]),
      "+f"(d[16]), "+f"(d[17]), "+f"(d[18]), "+f"(d[19]), "+f"(d[20]), "+f"(d[21]), "+f"(d[22]), "+f"(d[23]),
      "+f"(d[24]), "+f"(d[25]), "+f"(d[26]), "+f"(d[27]), "+f"(d[28]), "+f"(d[29]), "+f"(d[30]), "+f"(d[31]),
      "+f"(d[32]), "+f"(d[33]), "+f"(d[34]), "+f"(d[35]), "+f"(d[36]), "+f"(d[37]), "+f"(d[38]), "+f"(d[39]),
      "+f"(d[40]), "+f"(d[41]), "+f"(d[42]), "+f"(d[43]), "+f"(d[44]), "+f"(d[45]), "+f"(d[46]), "+f"(d[47]),
      "+f"(d[48]), "+f"(d[49]), "+f"(d[50]), "+f"(d[51]), "+f"(d[52]), "+f"(d[53]), "+f"(d[54]), "+f"(d[55]),
      "+f"(d[56]), "+f"(d[57]), "+f"(d[58]), "+f"(d[59]), "+f"(d[60]), "+f"(d[61]), "+f"(d[62]), "+f"(d[63])
      : "r"(a[0]), "r"(a[1]), "r"(a[2]), "r"(a[3]), "l"(db));
  }
};
template <int N> struct KB;
template <> struct KB<80> {
  template <int W, int RC, int RA, int BSTEP> static __device__ __forceinline__ void run(float* d, uint64_t da, uint64_t db, uint32_t rel, uint32_t rela, uint32_t doR, uint32_t fa, uint32_t pa, uint32_t fb, uint32_t pb, uint32_t acc) {
    if constexpr (W == 0 && RC == 0 && RA == 0) asm volatile(
    "{\n.reg .pred p, q, r, t;\n.reg .b64 a, b;\n.reg .u32 n;\nsetp.ne.b32 t, 1, 0;\nsetp.ne.b32 r, %49, 0;\n"
    "wgmma.mma_async.sync.aligned.m64n80k16.f32.bf16.bf16 {"
      "%0, %1, %2, %3, %4, %5, %6, %7, %8, %9, %10, %11, %12, %13, %14, %15, "
      "%16, %17, %18, %19, %20, %21, %22, %23, %24, %25, %26, %27, %28, %29, %30, %31, "
      "%32, %33, %34, %35, %36, %37, %38, %39"
      "}, %40, %41, r, 1, 1, 0, 1;\n"
    "add.u64 a, %40, 2;\nadd.u64 b, %41, %48;\n"
    "wgmma.mma_async.sync.aligned.m64n80k16.f32.bf16.bf16 {"
      "%0, %1, %2, %3, %4, %5, %6, %7, %8, %9, %10, %11, %12, %13, %14, %15, "
      "%16, %17, %18, %19, %20, %21, %22, %23, %24, %25, %26, %27, %28, %29, %30, %31, "
      "%32, %33, %34, %35, %36, %37, %38, %39"
      "}, a, b, t, 1, 1, 0, 1;\n"
    "wgmma.commit_group.sync.aligned;\nwgmma.wait_group.sync.aligned 1;\n"
    "add.u64 a, %40, 4;\nadd.u64 b, %41, 2*%48;\n"
    "wgmma.mma_async.sync.aligned.m64n80k16.f32.bf16.bf16 {"
      "%0, %1, %2, %3, %4, %5, %6, %7, %8, %9, %10, %11, %12, %13, %14, %15, "
      "%16, %17, %18, %19, %20, %21, %22, %23, %24, %25, %26, %27, %28, %29, %30, %31, "
      "%32, %33, %34, %35, %36, %37, %38, %39"
      "}, a, b, t, 1, 1, 0, 1;\n"
    "add.u64 a, %40, 6;\nadd.u64 b, %41, 3*%48;\n"
    "wgmma.mma_async.sync.aligned.m64n80k16.f32.bf16.bf16 {"
      "%0, %1, %2, %3, %4, %5, %6, %7, %8, %9, %10, %11, %12, %13, %14, %15, "
      "%16, %17, %18, %19, %20, %21, %22, %23, %24, %25, %26, %27, %28, %29, %30, %31, "
      "%32, %33, %34, %35, %36, %37, %38, %39"
      "}, a, b, t, 1, 1, 0, 1;\n"
    "wgmma.commit_group.sync.aligned;\n"
    "}\n"
      :
      "+f"(d[0]), "+f"(d[1]), "+f"(d[2]), "+f"(d[3]), "+f"(d[4]), "+f"(d[5]), "+f"(d[6]), "+f"(d[7]),
      "+f"(d[8]), "+f"(d[9]), "+f"(d[10]), "+f"(d[11]), "+f"(d[12]), "+f"(d[13]), "+f"(d[14]), "+f"(d[15]),
      "+f"(d[16]), "+f"(d[17]), "+f"(d[18]), "+f"(d[19]), "+f"(d[20]), "+f"(d[21]), "+f"(d[22]), "+f"(d[23]),
      "+f"(d[24]), "+f"(d[25]), "+f"(d[26]), "+f"(d[27]), "+f"(d[28]), "+f"(d[29]), "+f"(d[30]), "+f"(d[31]),
      "+f"(d[32]), "+f"(d[33]), "+f"(d[34]), "+f"(d[35]), "+f"(d[36]), "+f"(d[37]), "+f"(d[38]), "+f"(d[39])
      : "l"(da), "l"(db), "r"(rel), "r"(doR), "r"(fa), "r"(pa), "r"(fb), "r"(pb), "n"(BSTEP), "r"(acc), "r"(rela) : "memory");
    else if constexpr (W == 0 && RC == 1 && RA == 0) asm volatile(
    "{\n.reg .pred p, q, r, t;\n.reg .b64 a, b;\n.reg .u32 n;\nsetp.ne.b32 t, 1, 0;\nsetp.ne.b32 r, %49, 0;\n"
    "wgmma.mma_async.sync.aligned.m64n80k16.f32.bf16.bf16 {"
      "%0, %1, %2, %3, %4, %5, %6, %7, %8, %9, %10, %11, %12, %13, %14, %15, "
      "%16, %17, %18, %19, %20, %21, %22, %23, %24, %25, %26, %27, %28, %29, %30, %31, "
      "%32, %33, %34, %35, %36, %37, %38, %39"
      "}, %40, %41, r, 1, 1, 0, 1;\n"
    "add.u64 a, %40, 2;\nadd.u64 b, %41, %48;\n"
    "wgmma.mma_async.sync.aligned.m64n80k16.f32.bf16.bf16 {"
      "%0, %1, %2, %3, %4, %5, %6, %7, %8, %9, %10, %11, %12, %13, %14, %15, "
      "%16, %17, %18, %19, %20, %21, %22, %23, %24, %25, %26, %27, %28, %29, %30, %31, "
      "%32, %33, %34, %35, %36, %37, %38, %39"
      "}, a, b, t, 1, 1, 0, 1;\n"
    "wgmma.commit_group.sync.aligned;\nwgmma.wait_group.sync.aligned 1;\n"
    "add.u64 a, %40, 4;\nadd.u64 b, %41, 2*%48;\n"
    "wgmma.mma_async.sync.aligned.m64n80k16.f32.bf16.bf16 {"
      "%0, %1, %2, %3, %4, %5, %6, %7, %8, %9, %10, %11, %12, %13, %14, %15, "
      "%16, %17, %18, %19, %20, %21, %22, %23, %24, %25, %26, %27, %28, %29, %30, %31, "
      "%32, %33, %34, %35, %36, %37, %38, %39"
      "}, a, b, t, 1, 1, 0, 1;\n"
    "setp.ne.u32 q, %43, 0;\n@q mbarrier.arrive.shared::cta.b64 _, [%42];\n"
    "add.u64 a, %40, 6;\nadd.u64 b, %41, 3*%48;\n"
    "wgmma.mma_async.sync.aligned.m64n80k16.f32.bf16.bf16 {"
      "%0, %1, %2, %3, %4, %5, %6, %7, %8, %9, %10, %11, %12, %13, %14, %15, "
      "%16, %17, %18, %19, %20, %21, %22, %23, %24, %25, %26, %27, %28, %29, %30, %31, "
      "%32, %33, %34, %35, %36, %37, %38, %39"
      "}, a, b, t, 1, 1, 0, 1;\n"
    "wgmma.commit_group.sync.aligned;\n"
    "}\n"
      :
      "+f"(d[0]), "+f"(d[1]), "+f"(d[2]), "+f"(d[3]), "+f"(d[4]), "+f"(d[5]), "+f"(d[6]), "+f"(d[7]),
      "+f"(d[8]), "+f"(d[9]), "+f"(d[10]), "+f"(d[11]), "+f"(d[12]), "+f"(d[13]), "+f"(d[14]), "+f"(d[15]),
      "+f"(d[16]), "+f"(d[17]), "+f"(d[18]), "+f"(d[19]), "+f"(d[20]), "+f"(d[21]), "+f"(d[22]), "+f"(d[23]),
      "+f"(d[24]), "+f"(d[25]), "+f"(d[26]), "+f"(d[27]), "+f"(d[28]), "+f"(d[29]), "+f"(d[30]), "+f"(d[31]),
      "+f"(d[32]), "+f"(d[33]), "+f"(d[34]), "+f"(d[35]), "+f"(d[36]), "+f"(d[37]), "+f"(d[38]), "+f"(d[39])
      : "l"(da), "l"(db), "r"(rel), "r"(doR), "r"(fa), "r"(pa), "r"(fb), "r"(pb), "n"(BSTEP), "r"(acc), "r"(rela) : "memory");
    else if constexpr (W == 1 && RC == 0 && RA == 0) asm volatile(
    "{\n.reg .pred p, q, r, t;\n.reg .b64 a, b;\n.reg .u32 n;\nsetp.ne.b32 t, 1, 0;\nsetp.ne.b32 r, %49, 0;\n"
    "wgmma.mma_async.sync.aligned.m64n80k16.f32.bf16.bf16 {"
      "%0, %1, %2, %3, %4, %5, %6, %7, %8, %9, %10, %11, %12, %13, %14, %15, "
      "%16, %17, %18, %19, %20, %21, %22, %23, %24, %25, %26, %27, %28, %29, %30, %31, "
      "%32, %33, %34, %35, %36, %37, %38, %39"
      "}, %40, %41, r, 1, 1, 0, 1;\n"
    "add.u64 a, %40, 2;\nadd.u64 b, %41, %48;\n"
    "wgmma.mma_async.sync.aligned.m64n80k16.f32.bf16.bf16 {"
      "%0, %1, %2, %3, %4, %5, %6, %7, %8, %9, %10, %11, %12, %13, %14, %15, "
      "%16, %17, %18, %19, %20, %21, %22, %23, %24, %25, %26, %27, %28, %29, %30, %31, "
      "%32, %33, %34, %35, %36, %37, %38, %39"
      "}, a, b, t, 1, 1, 0, 1;\n"
    "wgmma.commit_group.sync.aligned;\nwgmma.wait_group.sync.aligned 1;\n"
    "add.u64 a, %40, 4;\nadd.u64 b, %41, 2*%48;\n"
    "wgmma.mma_async.sync.aligned.m64n80k16.f32.bf16.bf16 {"
      "%0, %1, %2, %3, %4, %5, %6, %7, %8, %9, %10, %11, %12, %13, %14, %15, "
      "%16, %17, %18, %19, %20, %21, %22, %23, %24, %25, %26, %27, %28, %29, %30, %31, "
      "%32, %33, %34, %35, %36, %37, %38, %39"
      "}, a, b, t, 1, 1, 0, 1;\n"
    "mbarrier.test_wait.parity.shared::cta.b64 p, [%46], %47;\n"
    "add.u64 a, %40, 6;\nadd.u64 b, %41, 3*%48;\n"
    "wgmma.mma_async.sync.aligned.m64n80k16.f32.bf16.bf16 {"
      "%0, %1, %2, %3, %4, %5, %6, %7, %8, %9, %10, %11, %12, %13, %14, %15, "
      "%16, %17, %18, %19, %20, %21, %22, %23, %24, %25, %26, %27, %28, %29, %30, %31, "
      "%32, %33, %34, %35, %36, %37, %38, %39"
      "}, a, b, t, 1, 1, 0, 1;\n"
    "wgmma.commit_group.sync.aligned;\n"
    "@p bra.uni DN;\nmov.u32 n, 0;\nWT: mbarrier.try_wait.parity.shared::cta.b64 p, [%46], %47;\n@p bra.uni DN;\nadd.u32 n, n, 1;\nsetp.lt.u32 p, n, 0x100000;\n@p bra.uni WT;\nDN:\n"
    "}\n"
      :
      "+f"(d[0]), "+f"(d[1]), "+f"(d[2]), "+f"(d[3]), "+f"(d[4]), "+f"(d[5]), "+f"(d[6]), "+f"(d[7]),
      "+f"(d[8]), "+f"(d[9]), "+f"(d[10]), "+f"(d[11]), "+f"(d[12]), "+f"(d[13]), "+f"(d[14]), "+f"(d[15]),
      "+f"(d[16]), "+f"(d[17]), "+f"(d[18]), "+f"(d[19]), "+f"(d[20]), "+f"(d[21]), "+f"(d[22]), "+f"(d[23]),
      "+f"(d[24]), "+f"(d[25]), "+f"(d[26]), "+f"(d[27]), "+f"(d[28]), "+f"(d[29]), "+f"(d[30]), "+f"(d[31]),
      "+f"(d[32]), "+f"(d[33]), "+f"(d[34]), "+f"(d[35]), "+f"(d[36]), "+f"(d[37]), "+f"(d[38]), "+f"(d[39])
      : "l"(da), "l"(db), "r"(rel), "r"(doR), "r"(fa), "r"(pa), "r"(fb), "r"(pb), "n"(BSTEP), "r"(acc), "r"(rela) : "memory");
    else if constexpr (W == 1 && RC == 1 && RA == 0) asm volatile(
    "{\n.reg .pred p, q, r, t;\n.reg .b64 a, b;\n.reg .u32 n;\nsetp.ne.b32 t, 1, 0;\nsetp.ne.b32 r, %49, 0;\n"
    "wgmma.mma_async.sync.aligned.m64n80k16.f32.bf16.bf16 {"
      "%0, %1, %2, %3, %4, %5, %6, %7, %8, %9, %10, %11, %12, %13, %14, %15, "
      "%16, %17, %18, %19, %20, %21, %22, %23, %24, %25, %26, %27, %28, %29, %30, %31, "
      "%32, %33, %34, %35, %36, %37, %38, %39"
      "}, %40, %41, r, 1, 1, 0, 1;\n"
    "add.u64 a, %40, 2;\nadd.u64 b, %41, %48;\n"
    "wgmma.mma_async.sync.aligned.m64n80k16.f32.bf16.bf16 {"
      "%0, %1, %2, %3, %4, %5, %6, %7, %8, %9, %10, %11, %12, %13, %14, %15, "
      "%16, %17, %18, %19, %20, %21, %22, %23, %24, %25, %26, %27, %28, %29, %30, %31, "
      "%32, %33, %34, %35, %36, %37, %38, %39"
      "}, a, b, t, 1, 1, 0, 1;\n"
    "wgmma.commit_group.sync.aligned;\nwgmma.wait_group.sync.aligned 1;\n"
    "add.u64 a, %40, 4;\nadd.u64 b, %41, 2*%48;\n"
    "wgmma.mma_async.sync.aligned.m64n80k16.f32.bf16.bf16 {"
      "%0, %1, %2, %3, %4, %5, %6, %7, %8, %9, %10, %11, %12, %13, %14, %15, "
      "%16, %17, %18, %19, %20, %21, %22, %23, %24, %25, %26, %27, %28, %29, %30, %31, "
      "%32, %33, %34, %35, %36, %37, %38, %39"
      "}, a, b, t, 1, 1, 0, 1;\n"
    "setp.ne.u32 q, %43, 0;\n@q mbarrier.arrive.shared::cta.b64 _, [%42];\n"
    "mbarrier.test_wait.parity.shared::cta.b64 p, [%46], %47;\n"
    "add.u64 a, %40, 6;\nadd.u64 b, %41, 3*%48;\n"
    "wgmma.mma_async.sync.aligned.m64n80k16.f32.bf16.bf16 {"
      "%0, %1, %2, %3, %4, %5, %6, %7, %8, %9, %10, %11, %12, %13, %14, %15, "
      "%16, %17, %18, %19, %20, %21, %22, %23, %24, %25, %26, %27, %28, %29, %30, %31, "
      "%32, %33, %34, %35, %36, %37, %38, %39"
      "}, a, b, t, 1, 1, 0, 1;\n"
    "wgmma.commit_group.sync.aligned;\n"
    "@p bra.uni DN;\nmov.u32 n, 0;\nWT: mbarrier.try_wait.parity.shared::cta.b64 p, [%46], %47;\n@p bra.uni DN;\nadd.u32 n, n, 1;\nsetp.lt.u32 p, n, 0x100000;\n@p bra.uni WT;\nDN:\n"
    "}\n"
      :
      "+f"(d[0]), "+f"(d[1]), "+f"(d[2]), "+f"(d[3]), "+f"(d[4]), "+f"(d[5]), "+f"(d[6]), "+f"(d[7]),
      "+f"(d[8]), "+f"(d[9]), "+f"(d[10]), "+f"(d[11]), "+f"(d[12]), "+f"(d[13]), "+f"(d[14]), "+f"(d[15]),
      "+f"(d[16]), "+f"(d[17]), "+f"(d[18]), "+f"(d[19]), "+f"(d[20]), "+f"(d[21]), "+f"(d[22]), "+f"(d[23]),
      "+f"(d[24]), "+f"(d[25]), "+f"(d[26]), "+f"(d[27]), "+f"(d[28]), "+f"(d[29]), "+f"(d[30]), "+f"(d[31]),
      "+f"(d[32]), "+f"(d[33]), "+f"(d[34]), "+f"(d[35]), "+f"(d[36]), "+f"(d[37]), "+f"(d[38]), "+f"(d[39])
      : "l"(da), "l"(db), "r"(rel), "r"(doR), "r"(fa), "r"(pa), "r"(fb), "r"(pb), "n"(BSTEP), "r"(acc), "r"(rela) : "memory");
    else if constexpr (W == 2 && RC == 0 && RA == 0) asm volatile(
    "{\n.reg .pred p, q, r, t;\n.reg .b64 a, b;\n.reg .u32 n;\nsetp.ne.b32 t, 1, 0;\nsetp.ne.b32 r, %49, 0;\n"
    "wgmma.mma_async.sync.aligned.m64n80k16.f32.bf16.bf16 {"
      "%0, %1, %2, %3, %4, %5, %6, %7, %8, %9, %10, %11, %12, %13, %14, %15, "
      "%16, %17, %18, %19, %20, %21, %22, %23, %24, %25, %26, %27, %28, %29, %30, %31, "
      "%32, %33, %34, %35, %36, %37, %38, %39"
      "}, %40, %41, r, 1, 1, 0, 1;\n"
    "add.u64 a, %40, 2;\nadd.u64 b, %41, %48;\n"
    "wgmma.mma_async.sync.aligned.m64n80k16.f32.bf16.bf16 {"
      "%0, %1, %2, %3, %4, %5, %6, %7, %8, %9, %10, %11, %12, %13, %14, %15, "
      "%16, %17, %18, %19, %20, %21, %22, %23, %24, %25, %26, %27, %28, %29, %30, %31, "
      "%32, %33, %34, %35, %36, %37, %38, %39"
      "}, a, b, t, 1, 1, 0, 1;\n"
    "wgmma.commit_group.sync.aligned;\nwgmma.wait_group.sync.aligned 1;\n"
    "add.u64 a, %40, 4;\nadd.u64 b, %41, 2*%48;\n"
    "wgmma.mma_async.sync.aligned.m64n80k16.f32.bf16.bf16 {"
      "%0, %1, %2, %3, %4, %5, %6, %7, %8, %9, %10, %11, %12, %13, %14, %15, "
      "%16, %17, %18, %19, %20, %21, %22, %23, %24, %25, %26, %27, %28, %29, %30, %31, "
      "%32, %33, %34, %35, %36, %37, %38, %39"
      "}, a, b, t, 1, 1, 0, 1;\n"
    "mbarrier.test_wait.parity.shared::cta.b64 p, [%46], %47;\n"
    "mbarrier.test_wait.parity.shared::cta.b64 r, [%44], %45;\nand.pred p, p, r;\n"
    "add.u64 a, %40, 6;\nadd.u64 b, %41, 3*%48;\n"
    "wgmma.mma_async.sync.aligned.m64n80k16.f32.bf16.bf16 {"
      "%0, %1, %2, %3, %4, %5, %6, %7, %8, %9, %10, %11, %12, %13, %14, %15, "
      "%16, %17, %18, %19, %20, %21, %22, %23, %24, %25, %26, %27, %28, %29, %30, %31, "
      "%32, %33, %34, %35, %36, %37, %38, %39"
      "}, a, b, t, 1, 1, 0, 1;\n"
    "wgmma.commit_group.sync.aligned;\n"
    "@p bra.uni DN;\nmov.u32 n, 0;\nWT: mbarrier.try_wait.parity.shared::cta.b64 p, [%46], %47;\nmbarrier.try_wait.parity.shared::cta.b64 r, [%44], %45;\nand.pred p, p, r;\n@p bra.uni DN;\nadd.u32 n, n, 1;\nsetp.lt.u32 p, n, 0x100000;\n@p bra.uni WT;\nDN:\n"
    "}\n"
      :
      "+f"(d[0]), "+f"(d[1]), "+f"(d[2]), "+f"(d[3]), "+f"(d[4]), "+f"(d[5]), "+f"(d[6]), "+f"(d[7]),
      "+f"(d[8]), "+f"(d[9]), "+f"(d[10]), "+f"(d[11]), "+f"(d[12]), "+f"(d[13]), "+f"(d[14]), "+f"(d[15]),
      "+f"(d[16]), "+f"(d[17]), "+f"(d[18]), "+f"(d[19]), "+f"(d[20]), "+f"(d[21]), "+f"(d[22]), "+f"(d[23]),
      "+f"(d[24]), "+f"(d[25]), "+f"(d[26]), "+f"(d[27]), "+f"(d[28]), "+f"(d[29]), "+f"(d[30]), "+f"(d[31]),
      "+f"(d[32]), "+f"(d[33]), "+f"(d[34]), "+f"(d[35]), "+f"(d[36]), "+f"(d[37]), "+f"(d[38]), "+f"(d[39])
      : "l"(da), "l"(db), "r"(rel), "r"(doR), "r"(fa), "r"(pa), "r"(fb), "r"(pb), "n"(BSTEP), "r"(acc), "r"(rela) : "memory");
    else if constexpr (W == 2 && RC == 1 && RA == 0) asm volatile(
    "{\n.reg .pred p, q, r, t;\n.reg .b64 a, b;\n.reg .u32 n;\nsetp.ne.b32 t, 1, 0;\nsetp.ne.b32 r, %49, 0;\n"
    "wgmma.mma_async.sync.aligned.m64n80k16.f32.bf16.bf16 {"
      "%0, %1, %2, %3, %4, %5, %6, %7, %8, %9, %10, %11, %12, %13, %14, %15, "
      "%16, %17, %18, %19, %20, %21, %22, %23, %24, %25, %26, %27, %28, %29, %30, %31, "
      "%32, %33, %34, %35, %36, %37, %38, %39"
      "}, %40, %41, r, 1, 1, 0, 1;\n"
    "add.u64 a, %40, 2;\nadd.u64 b, %41, %48;\n"
    "wgmma.mma_async.sync.aligned.m64n80k16.f32.bf16.bf16 {"
      "%0, %1, %2, %3, %4, %5, %6, %7, %8, %9, %10, %11, %12, %13, %14, %15, "
      "%16, %17, %18, %19, %20, %21, %22, %23, %24, %25, %26, %27, %28, %29, %30, %31, "
      "%32, %33, %34, %35, %36, %37, %38, %39"
      "}, a, b, t, 1, 1, 0, 1;\n"
    "wgmma.commit_group.sync.aligned;\nwgmma.wait_group.sync.aligned 1;\n"
    "add.u64 a, %40, 4;\nadd.u64 b, %41, 2*%48;\n"
    "wgmma.mma_async.sync.aligned.m64n80k16.f32.bf16.bf16 {"
      "%0, %1, %2, %3, %4, %5, %6, %7, %8, %9, %10, %11, %12, %13, %14, %15, "
      "%16, %17, %18, %19, %20, %21, %22, %23, %24, %25, %26, %27, %28, %29, %30, %31, "
      "%32, %33, %34, %35, %36, %37, %38, %39"
      "}, a, b, t, 1, 1, 0, 1;\n"
    "setp.ne.u32 q, %43, 0;\n@q mbarrier.arrive.shared::cta.b64 _, [%42];\n"
    "mbarrier.test_wait.parity.shared::cta.b64 p, [%46], %47;\n"
    "mbarrier.test_wait.parity.shared::cta.b64 r, [%44], %45;\nand.pred p, p, r;\n"
    "add.u64 a, %40, 6;\nadd.u64 b, %41, 3*%48;\n"
    "wgmma.mma_async.sync.aligned.m64n80k16.f32.bf16.bf16 {"
      "%0, %1, %2, %3, %4, %5, %6, %7, %8, %9, %10, %11, %12, %13, %14, %15, "
      "%16, %17, %18, %19, %20, %21, %22, %23, %24, %25, %26, %27, %28, %29, %30, %31, "
      "%32, %33, %34, %35, %36, %37, %38, %39"
      "}, a, b, t, 1, 1, 0, 1;\n"
    "wgmma.commit_group.sync.aligned;\n"
    "@p bra.uni DN;\nmov.u32 n, 0;\nWT: mbarrier.try_wait.parity.shared::cta.b64 p, [%46], %47;\nmbarrier.try_wait.parity.shared::cta.b64 r, [%44], %45;\nand.pred p, p, r;\n@p bra.uni DN;\nadd.u32 n, n, 1;\nsetp.lt.u32 p, n, 0x100000;\n@p bra.uni WT;\nDN:\n"
    "}\n"
      :
      "+f"(d[0]), "+f"(d[1]), "+f"(d[2]), "+f"(d[3]), "+f"(d[4]), "+f"(d[5]), "+f"(d[6]), "+f"(d[7]),
      "+f"(d[8]), "+f"(d[9]), "+f"(d[10]), "+f"(d[11]), "+f"(d[12]), "+f"(d[13]), "+f"(d[14]), "+f"(d[15]),
      "+f"(d[16]), "+f"(d[17]), "+f"(d[18]), "+f"(d[19]), "+f"(d[20]), "+f"(d[21]), "+f"(d[22]), "+f"(d[23]),
      "+f"(d[24]), "+f"(d[25]), "+f"(d[26]), "+f"(d[27]), "+f"(d[28]), "+f"(d[29]), "+f"(d[30]), "+f"(d[31]),
      "+f"(d[32]), "+f"(d[33]), "+f"(d[34]), "+f"(d[35]), "+f"(d[36]), "+f"(d[37]), "+f"(d[38]), "+f"(d[39])
      : "l"(da), "l"(db), "r"(rel), "r"(doR), "r"(fa), "r"(pa), "r"(fb), "r"(pb), "n"(BSTEP), "r"(acc), "r"(rela) : "memory");
    else if constexpr (W == 2 && RC == 1 && RA == 1) asm volatile(
    "{\n.reg .pred p, q, r, t;\n.reg .b64 a, b;\n.reg .u32 n;\nsetp.ne.b32 t, 1, 0;\nsetp.ne.b32 r, %49, 0;\n"
    "wgmma.mma_async.sync.aligned.m64n80k16.f32.bf16.bf16 {"
      "%0, %1, %2, %3, %4, %5, %6, %7, %8, %9, %10, %11, %12, %13, %14, %15, "
      "%16, %17, %18, %19, %20, %21, %22, %23, %24, %25, %26, %27, %28, %29, %30, %31, "
      "%32, %33, %34, %35, %36, %37, %38, %39"
      "}, %40, %41, r, 1, 1, 0, 1;\n"
    "add.u64 a, %40, 2;\nadd.u64 b, %41, %48;\n"
    "wgmma.mma_async.sync.aligned.m64n80k16.f32.bf16.bf16 {"
      "%0, %1, %2, %3, %4, %5, %6, %7, %8, %9, %10, %11, %12, %13, %14, %15, "
      "%16, %17, %18, %19, %20, %21, %22, %23, %24, %25, %26, %27, %28, %29, %30, %31, "
      "%32, %33, %34, %35, %36, %37, %38, %39"
      "}, a, b, t, 1, 1, 0, 1;\n"
    "wgmma.commit_group.sync.aligned;\nwgmma.wait_group.sync.aligned 1;\n"
    "add.u64 a, %40, 4;\nadd.u64 b, %41, 2*%48;\n"
    "wgmma.mma_async.sync.aligned.m64n80k16.f32.bf16.bf16 {"
      "%0, %1, %2, %3, %4, %5, %6, %7, %8, %9, %10, %11, %12, %13, %14, %15, "
      "%16, %17, %18, %19, %20, %21, %22, %23, %24, %25, %26, %27, %28, %29, %30, %31, "
      "%32, %33, %34, %35, %36, %37, %38, %39"
      "}, a, b, t, 1, 1, 0, 1;\n"
    "setp.ne.u32 q, %43, 0;\n@q mbarrier.arrive.shared::cta.b64 _, [%42];\n@q mbarrier.arrive.shared::cta.b64 _, [%50];\n"
    "mbarrier.test_wait.parity.shared::cta.b64 p, [%46], %47;\n"
    "mbarrier.test_wait.parity.shared::cta.b64 r, [%44], %45;\nand.pred p, p, r;\n"
    "add.u64 a, %40, 6;\nadd.u64 b, %41, 3*%48;\n"
    "wgmma.mma_async.sync.aligned.m64n80k16.f32.bf16.bf16 {"
      "%0, %1, %2, %3, %4, %5, %6, %7, %8, %9, %10, %11, %12, %13, %14, %15, "
      "%16, %17, %18, %19, %20, %21, %22, %23, %24, %25, %26, %27, %28, %29, %30, %31, "
      "%32, %33, %34, %35, %36, %37, %38, %39"
      "}, a, b, t, 1, 1, 0, 1;\n"
    "wgmma.commit_group.sync.aligned;\n"
    "@p bra.uni DN;\nmov.u32 n, 0;\nWT: mbarrier.try_wait.parity.shared::cta.b64 p, [%46], %47;\nmbarrier.try_wait.parity.shared::cta.b64 r, [%44], %45;\nand.pred p, p, r;\n@p bra.uni DN;\nadd.u32 n, n, 1;\nsetp.lt.u32 p, n, 0x100000;\n@p bra.uni WT;\nDN:\n"
    "}\n"
      :
      "+f"(d[0]), "+f"(d[1]), "+f"(d[2]), "+f"(d[3]), "+f"(d[4]), "+f"(d[5]), "+f"(d[6]), "+f"(d[7]),
      "+f"(d[8]), "+f"(d[9]), "+f"(d[10]), "+f"(d[11]), "+f"(d[12]), "+f"(d[13]), "+f"(d[14]), "+f"(d[15]),
      "+f"(d[16]), "+f"(d[17]), "+f"(d[18]), "+f"(d[19]), "+f"(d[20]), "+f"(d[21]), "+f"(d[22]), "+f"(d[23]),
      "+f"(d[24]), "+f"(d[25]), "+f"(d[26]), "+f"(d[27]), "+f"(d[28]), "+f"(d[29]), "+f"(d[30]), "+f"(d[31]),
      "+f"(d[32]), "+f"(d[33]), "+f"(d[34]), "+f"(d[35]), "+f"(d[36]), "+f"(d[37]), "+f"(d[38]), "+f"(d[39])
      : "l"(da), "l"(db), "r"(rel), "r"(doR), "r"(fa), "r"(pa), "r"(fb), "r"(pb), "n"(BSTEP), "r"(acc), "r"(rela) : "memory");
    else static_assert(W < 0, "variant not generated");
  }
};
template <> struct KB<192> {
  template <int W, int RC, int RA, int BSTEP> static __device__ __forceinline__ void run(float* d, uint64_t da, uint64_t db, uint32_t rel, uint32_t rela, uint32_t doR, uint32_t fa, uint32_t pa, uint32_t fb, uint32_t pb, uint32_t acc) {
    if constexpr (W == 0 && RC == 2 && RA == 0) asm volatile(
    "{\n.reg .pred p, q, r, t;\n.reg .b64 a, b;\n.reg .u32 n;\nsetp.ne.b32 t, 1, 0;\nsetp.ne.b32 r, %105, 0;\n"
    "wgmma.mma_async.sync.aligned.m64n192k16.f32.bf16.bf16 {"
      "%0, %1, %2, %3, %4, %5, %6, %7, %8, %9, %10, %11, %12, %13, %14, %15, "
      "%16, %17, %18, %19, %20, %21, %22, %23, %24, %25, %26, %27, %28, %29, %30, %31, "
      "%32, %33, %34, %35, %36, %37, %38, %39, %40, %41, %42, %43, %44, %45, %46, %47, "
      "%48, %49, %50, %51, %52, %53, %54, %55, %56, %57, %58, %59, %60, %61, %62, %63, "
      "%64, %65, %66, %67, %68, %69, %70, %71, %72, %73, %74, %75, %76, %77, %78, %79, "
      "%80, %81, %82, %83, %84, %85, %86, %87, %88, %89, %90, %91, %92, %93, %94, %95"
      "}, %96, %97, r, 1, 1, 0, 1;\n"
    "add.u64 a, %96, 2;\nadd.u64 b, %97, %104;\n"
    "wgmma.mma_async.sync.aligned.m64n192k16.f32.bf16.bf16 {"
      "%0, %1, %2, %3, %4, %5, %6, %7, %8, %9, %10, %11, %12, %13, %14, %15, "
      "%16, %17, %18, %19, %20, %21, %22, %23, %24, %25, %26, %27, %28, %29, %30, %31, "
      "%32, %33, %34, %35, %36, %37, %38, %39, %40, %41, %42, %43, %44, %45, %46, %47, "
      "%48, %49, %50, %51, %52, %53, %54, %55, %56, %57, %58, %59, %60, %61, %62, %63, "
      "%64, %65, %66, %67, %68, %69, %70, %71, %72, %73, %74, %75, %76, %77, %78, %79, "
      "%80, %81, %82, %83, %84, %85, %86, %87, %88, %89, %90, %91, %92, %93, %94, %95"
      "}, a, b, t, 1, 1, 0, 1;\n"
    "wgmma.commit_group.sync.aligned;\nwgmma.wait_group.sync.aligned 1;\n"
    "add.u64 a, %96, 4;\nadd.u64 b, %97, 2*%104;\n"
    "wgmma.mma_async.sync.aligned.m64n192k16.f32.bf16.bf16 {"
      "%0, %1, %2, %3, %4, %5, %6, %7, %8, %9, %10, %11, %12, %13, %14, %15, "
      "%16, %17, %18, %19, %20, %21, %22, %23, %24, %25, %26, %27, %28, %29, %30, %31, "
      "%32, %33, %34, %35, %36, %37, %38, %39, %40, %41, %42, %43, %44, %45, %46, %47, "
      "%48, %49, %50, %51, %52, %53, %54, %55, %56, %57, %58, %59, %60, %61, %62, %63, "
      "%64, %65, %66, %67, %68, %69, %70, %71, %72, %73, %74, %75, %76, %77, %78, %79, "
      "%80, %81, %82, %83, %84, %85, %86, %87, %88, %89, %90, %91, %92, %93, %94, %95"
      "}, a, b, t, 1, 1, 0, 1;\n"
    "setp.ne.u32 q, %99, 0;\n@q mbarrier.arrive.shared::cta.b64 _, [%98];\n@q mbarrier.arrive.shared::cta.b64 _, [%98];\n"
    "add.u64 a, %96, 6;\nadd.u64 b, %97, 3*%104;\n"
    "wgmma.mma_async.sync.aligned.m64n192k16.f32.bf16.bf16 {"
      "%0, %1, %2, %3, %4, %5, %6, %7, %8, %9, %10, %11, %12, %13, %14, %15, "
      "%16, %17, %18, %19, %20, %21, %22, %23, %24, %25, %26, %27, %28, %29, %30, %31, "
      "%32, %33, %34, %35, %36, %37, %38, %39, %40, %41, %42, %43, %44, %45, %46, %47, "
      "%48, %49, %50, %51, %52, %53, %54, %55, %56, %57, %58, %59, %60, %61, %62, %63, "
      "%64, %65, %66, %67, %68, %69, %70, %71, %72, %73, %74, %75, %76, %77, %78, %79, "
      "%80, %81, %82, %83, %84, %85, %86, %87, %88, %89, %90, %91, %92, %93, %94, %95"
      "}, a, b, t, 1, 1, 0, 1;\n"
    "wgmma.commit_group.sync.aligned;\n"
    "}\n"
      :
      "+f"(d[0]), "+f"(d[1]), "+f"(d[2]), "+f"(d[3]), "+f"(d[4]), "+f"(d[5]), "+f"(d[6]), "+f"(d[7]),
      "+f"(d[8]), "+f"(d[9]), "+f"(d[10]), "+f"(d[11]), "+f"(d[12]), "+f"(d[13]), "+f"(d[14]), "+f"(d[15]),
      "+f"(d[16]), "+f"(d[17]), "+f"(d[18]), "+f"(d[19]), "+f"(d[20]), "+f"(d[21]), "+f"(d[22]), "+f"(d[23]),
      "+f"(d[24]), "+f"(d[25]), "+f"(d[26]), "+f"(d[27]), "+f"(d[28]), "+f"(d[29]), "+f"(d[30]), "+f"(d[31]),
      "+f"(d[32]), "+f"(d[33]), "+f"(d[34]), "+f"(d[35]), "+f"(d[36]), "+f"(d[37]), "+f"(d[38]), "+f"(d[39]),
      "+f"(d[40]), "+f"(d[41]), "+f"(d[42]), "+f"(d[43]), "+f"(d[44]), "+f"(d[45]), "+f"(d[46]), "+f"(d[47]),
      "+f"(d[48]), "+f"(d[49]), "+f"(d[50]), "+f"(d[51]), "+f"(d[52]), "+f"(d[53]), "+f"(d[54]), "+f"(d[55]),
      "+f"(d[56]), "+f"(d[57]), "+f"(d[58]), "+f"(d[59]), "+f"(d[60]), "+f"(d[61]), "+f"(d[62]), "+f"(d[63]),
      "+f"(d[64]), "+f"(d[65]), "+f"(d[66]), "+f"(d[67]), "+f"(d[68]), "+f"(d[69]), "+f"(d[70]), "+f"(d[71]),
      "+f"(d[72]), "+f"(d[73]), "+f"(d[74]), "+f"(d[75]), "+f"(d[76]), "+f"(d[77]), "+f"(d[78]), "+f"(d[79]),
      "+f"(d[80]), "+f"(d[81]), "+f"(d[82]), "+f"(d[83]), "+f"(d[84]), "+f"(d[85]), "+f"(d[86]), "+f"(d[87]),
      "+f"(d[88]), "+f"(d[89]), "+f"(d[90]), "+f"(d[91]), "+f"(d[92]), "+f"(d[93]), "+f"(d[94]), "+f"(d[95])
      : "l"(da), "l"(db), "r"(rel), "r"(doR), "r"(fa), "r"(pa), "r"(fb), "r"(pb), "n"(BSTEP), "r"(acc), "r"(rela) : "memory");
    else if constexpr (W == 0 && RC == 2 && RA == 2) asm volatile(
    "{\n.reg .pred p, q, r, t;\n.reg .b64 a, b;\n.reg .u32 n;\nsetp.ne.b32 t, 1, 0;\nsetp.ne.b32 r, %105, 0;\n"
    "wgmma.mma_async.sync.aligned.m64n192k16.f32.bf16.bf16 {"
      "%0, %1, %2, %3, %4, %5, %6, %7, %8, %9, %10, %11, %12, %13, %14, %15, "
      "%16, %17, %18, %19, %20, %21, %22, %23, %24, %25, %26, %27, %28, %29, %30, %31, "
      "%32, %33, %34, %35, %36, %37, %38, %39, %40, %41, %42, %43, %44, %45, %46, %47, "
      "%48, %49, %50, %51, %52, %53, %54, %55, %56, %57, %58, %59, %60, %61, %62, %63, "
      "%64, %65, %66, %67, %68, %69, %70, %71, %72, %73, %74, %75, %76, %77, %78, %79, "
      "%80, %81, %82, %83, %84, %85, %86, %87, %88, %89, %90, %91, %92, %93, %94, %95"
      "}, %96, %97, r, 1, 1, 0, 1;\n"
    "add.u64 a, %96, 2;\nadd.u64 b, %97, %104;\n"
    "wgmma.mma_async.sync.aligned.m64n192k16.f32.bf16.bf16 {"
      "%0, %1, %2, %3, %4, %5, %6, %7, %8, %9, %10, %11, %12, %13, %14, %15, "
      "%16, %17, %18, %19, %20, %21, %22, %23, %24, %25, %26, %27, %28, %29, %30, %31, "
      "%32, %33, %34, %35, %36, %37, %38, %39, %40, %41, %42, %43, %44, %45, %46, %47, "
      "%48, %49, %50, %51, %52, %53, %54, %55, %56, %57, %58, %59, %60, %61, %62, %63, "
      "%64, %65, %66, %67, %68, %69, %70, %71, %72, %73, %74, %75, %76, %77, %78, %79, "
      "%80, %81, %82, %83, %84, %85, %86, %87, %88, %89, %90, %91, %92, %93, %94, %95"
      "}, a, b, t, 1, 1, 0, 1;\n"
    "wgmma.commit_group.sync.aligned;\nwgmma.wait_group.sync.aligned 1;\n"
    "add.u64 a, %96, 4;\nadd.u64 b, %97, 2*%104;\n"
    "wgmma.mma_async.sync.aligned.m64n192k16.f32.bf16.bf16 {"
      "%0, %1, %2, %3, %4, %5, %6, %7, %8, %9, %10, %11, %12, %13, %14, %15, "
      "%16, %17, %18, %19, %20, %21, %22, %23, %24, %25, %26, %27, %28, %29, %30, %31, "
      "%32, %33, %34, %35, %36, %37, %38, %39, %40, %41, %42, %43, %44, %45, %46, %47, "
      "%48, %49, %50, %51, %52, %53, %54, %55, %56, %57, %58, %59, %60, %61, %62, %63, "
      "%64, %65, %66, %67, %68, %69, %70, %71, %72, %73, %74, %75, %76, %77, %78, %79, "
      "%80, %81, %82, %83, %84, %85, %86, %87, %88, %89, %90, %91, %92, %93, %94, %95"
      "}, a, b, t, 1, 1, 0, 1;\n"
    "setp.ne.u32 q, %99, 0;\n@q mbarrier.arrive.shared::cta.b64 _, [%98];\n@q mbarrier.arrive.shared::cta.b64 _, [%98];\n@q mbarrier.arrive.shared::cta.b64 _, [%106];\n@q mbarrier.arrive.shared::cta.b64 _, [%106];\n"
    "add.u64 a, %96, 6;\nadd.u64 b, %97, 3*%104;\n"
    "wgmma.mma_async.sync.aligned.m64n192k16.f32.bf16.bf16 {"
      "%0, %1, %2, %3, %4, %5, %6, %7, %8, %9, %10, %11, %12, %13, %14, %15, "
      "%16, %17, %18, %19, %20, %21, %22, %23, %24, %25, %26, %27, %28, %29, %30, %31, "
      "%32, %33, %34, %35, %36, %37, %38, %39, %40, %41, %42, %43, %44, %45, %46, %47, "
      "%48, %49, %50, %51, %52, %53, %54, %55, %56, %57, %58, %59, %60, %61, %62, %63, "
      "%64, %65, %66, %67, %68, %69, %70, %71, %72, %73, %74, %75, %76, %77, %78, %79, "
      "%80, %81, %82, %83, %84, %85, %86, %87, %88, %89, %90, %91, %92, %93, %94, %95"
      "}, a, b, t, 1, 1, 0, 1;\n"
    "wgmma.commit_group.sync.aligned;\n"
    "}\n"
      :
      "+f"(d[0]), "+f"(d[1]), "+f"(d[2]), "+f"(d[3]), "+f"(d[4]), "+f"(d[5]), "+f"(d[6]), "+f"(d[7]),
      "+f"(d[8]), "+f"(d[9]), "+f"(d[10]), "+f"(d[11]), "+f"(d[12]), "+f"(d[13]), "+f"(d[14]), "+f"(d[15]),
      "+f"(d[16]), "+f"(d[17]), "+f"(d[18]), "+f"(d[19]), "+f"(d[20]), "+f"(d[21]), "+f"(d[22]), "+f"(d[23]),
      "+f"(d[24]), "+f"(d[25]), "+f"(d[26]), "+f"(d[27]), "+f"(d[28]), "+f"(d[29]), "+f"(d[30]), "+f"(d[31]),
      "+f"(d[32]), "+f"(d[33]), "+f"(d[34]), "+f"(d[35]), "+f"(d[36]), "+f"(d[37]), "+f"(d[38]), "+f"(d[39]),
      "+f"(d[40]), "+f"(d[41]), "+f"(d[42]), "+f"(d[43]), "+f"(d[44]), "+f"(d[45]), "+f"(d[46]), "+f"(d[47]),
      "+f"(d[48]), "+f"(d[49]), "+f"(d[50]), "+f"(d[51]), "+f"(d[52]), "+f"(d[53]), "+f"(d[54]), "+f"(d[55]),
      "+f"(d[56]), "+f"(d[57]), "+f"(d[58]), "+f"(d[59]), "+f"(d[60]), "+f"(d[61]), "+f"(d[62]), "+f"(d[63]),
      "+f"(d[64]), "+f"(d[65]), "+f"(d[66]), "+f"(d[67]), "+f"(d[68]), "+f"(d[69]), "+f"(d[70]), "+f"(d[71]),
      "+f"(d[72]), "+f"(d[73]), "+f"(d[74]), "+f"(d[75]), "+f"(d[76]), "+f"(d[77]), "+f"(d[78]), "+f"(d[79]),
      "+f"(d[80]), "+f"(d[81]), "+f"(d[82]), "+f"(d[83]), "+f"(d[84]), "+f"(d[85]), "+f"(d[86]), "+f"(d[87]),
      "+f"(d[88]), "+f"(d[89]), "+f"(d[90]), "+f"(d[91]), "+f"(d[92]), "+f"(d[93]), "+f"(d[94]), "+f"(d[95])
      : "l"(da), "l"(db), "r"(rel), "r"(doR), "r"(fa), "r"(pa), "r"(fb), "r"(pb), "n"(BSTEP), "r"(acc), "r"(rela) : "memory");
    else if constexpr (W == 1 && RC == 2 && RA == 2) asm volatile(
    "{\n.reg .pred p, q, r, t;\n.reg .b64 a, b;\n.reg .u32 n;\nsetp.ne.b32 t, 1, 0;\nsetp.ne.b32 r, %105, 0;\n"
    "wgmma.mma_async.sync.aligned.m64n192k16.f32.bf16.bf16 {"
      "%0, %1, %2, %3, %4, %5, %6, %7, %8, %9, %10, %11, %12, %13, %14, %15, "
      "%16, %17, %18, %19, %20, %21, %22, %23, %24, %25, %26, %27, %28, %29, %30, %31, "
      "%32, %33, %34, %35, %36, %37, %38, %39, %40, %41, %42, %43, %44, %45, %46, %47, "
      "%48, %49, %50, %51, %52, %53, %54, %55, %56, %57, %58, %59, %60, %61, %62, %63, "
      "%64, %65, %66, %67, %68, %69, %70, %71, %72, %73, %74, %75, %76, %77, %78, %79, "
      "%80, %81, %82, %83, %84, %85, %86, %87, %88, %89, %90, %91, %92, %93, %94, %95"
      "}, %96, %97, r, 1, 1, 0, 1;\n"
    "add.u64 a, %96, 2;\nadd.u64 b, %97, %104;\n"
    "wgmma.mma_async.sync.aligned.m64n192k16.f32.bf16.bf16 {"
      "%0, %1, %2, %3, %4, %5, %6, %7, %8, %9, %10, %11, %12, %13, %14, %15, "
      "%16, %17, %18, %19, %20, %21, %22, %23, %24, %25, %26, %27, %28, %29, %30, %31, "
      "%32, %33, %34, %35, %36, %37, %38, %39, %40, %41, %42, %43, %44, %45, %46, %47, "
      "%48, %49, %50, %51, %52, %53, %54, %55, %56, %57, %58, %59, %60, %61, %62, %63, "
      "%64, %65, %66, %67, %68, %69, %70, %71, %72, %73, %74, %75, %76, %77, %78, %79, "
      "%80, %81, %82, %83, %84, %85, %86, %87, %88, %89, %90, %91, %92, %93, %94, %95"
      "}, a, b, t, 1, 1, 0, 1;\n"
    "wgmma.commit_group.sync.aligned;\nwgmma.wait_group.sync.aligned 1;\n"
    "add.u64 a, %96, 4;\nadd.u64 b, %97, 2*%104;\n"
    "wgmma.mma_async.sync.aligned.m64n192k16.f32.bf16.bf16 {"
      "%0, %1, %2, %3, %4, %5, %6, %7, %8, %9, %10, %11, %12, %13, %14, %15, "
      "%16, %17, %18, %19, %20, %21, %22, %23, %24, %25, %26, %27, %28, %29, %30, %31, "
      "%32, %33, %34, %35, %36, %37, %38, %39, %40, %41, %42, %43, %44, %45, %46, %47, "
      "%48, %49, %50, %51, %52, %53, %54, %55, %56, %57, %58, %59, %60, %61, %62, %63, "
      "%64, %65, %66, %67, %68, %69, %70, %71, %72, %73, %74, %75, %76, %77, %78, %79, "
      "%80, %81, %82, %83, %84, %85, %86, %87, %88, %89, %90, %91, %92, %93, %94, %95"
      "}, a, b, t, 1, 1, 0, 1;\n"
    "setp.ne.u32 q, %99, 0;\n@q mbarrier.arrive.shared::cta.b64 _, [%98];\n@q mbarrier.arrive.shared::cta.b64 _, [%98];\n@q mbarrier.arrive.shared::cta.b64 _, [%106];\n@q mbarrier.arrive.shared::cta.b64 _, [%106];\n"
    "mbarrier.test_wait.parity.shared::cta.b64 p, [%102], %103;\n"
    "add.u64 a, %96, 6;\nadd.u64 b, %97, 3*%104;\n"
    "wgmma.mma_async.sync.aligned.m64n192k16.f32.bf16.bf16 {"
      "%0, %1, %2, %3, %4, %5, %6, %7, %8, %9, %10, %11, %12, %13, %14, %15, "
      "%16, %17, %18, %19, %20, %21, %22, %23, %24, %25, %26, %27, %28, %29, %30, %31, "
      "%32, %33, %34, %35, %36, %37, %38, %39, %40, %41, %42, %43, %44, %45, %46, %47, "
      "%48, %49, %50, %51, %52, %53, %54, %55, %56, %57, %58, %59, %60, %61, %62, %63, "
      "%64, %65, %66, %67, %68, %69, %70, %71, %72, %73, %74, %75, %76, %77, %78, %79, "
      "%80, %81, %82, %83, %84, %85, %86, %87, %88, %89, %90, %91, %92, %93, %94, %95"
      "}, a, b, t, 1, 1, 0, 1;\n"
    "wgmma.commit_group.sync.aligned;\n"
    "@p bra.uni DN;\nmov.u32 n, 0;\nWT: mbarrier.try_wait.parity.shared::cta.b64 p, [%102], %103;\n@p bra.uni DN;\nadd.u32 n, n, 1;\nsetp.lt.u32 p, n, 0x100000;\n@p bra.uni WT;\nDN:\n"
    "}\n"
      :
      "+f"(d[0]), "+f"(d[1]), "+f"(d[2]), "+f"(d[3]), "+f"(d[4]), "+f"(d[5]), "+f"(d[6]), "+f"(d[7]),
      "+f"(d[8]), "+f"(d[9]), "+f"(d[10]), "+f"(d[11]), "+f"(d[12]), "+f"(d[13]), "+f"(d[14]), "+f"(d[15]),
      "+f"(d[16]), "+f"(d[17]), "+f"(d[18]), "+f"(d[19]), "+f"(d[20]), "+f"(d[21]), "+f"(d[22]), "+f"(d[23]),
      "+f"(d[24]), "+f"(d[25]), "+f"(d[26]), "+f"(d[27]), "+f"(d[28]), "+f"(d[29]), "+f"(d[30]), "+f"(d[31]),
      "+f"(d[32]), "+f"(d[33]), "+f"(d[34]), "+f"(d[35]), "+f"(d[36]), "+f"(d[37]), "+f"(d[38]), "+f"(d[39]),
      "+f"(d[40]), "+f"(d[41]), "+f"(d[42]), "+f"(d[43]), "+f"(d[44]), "+f"(d[45]), "+f"(d[46]), "+f"(d[47]),
      "+f"(d[48]), "+f"(d[49]), "+f"(d[50]), "+f"(d[51]), "+f"(d[52]), "+f"(d[53]), "+f"(d[54]), "+f"(d[55]),
      "+f"(d[56]), "+f"(d[57]), "+f"(d[58]), "+f"(d[59]), "+f"(d[60]), "+f"(d[61]), "+f"(d[62]), "+f"(d[63]),
      "+f"(d[64]), "+f"(d[65]), "+f"(d[66]), "+f"(d[67]), "+f"(d[68]), "+f"(d[69]), "+f"(d[70]), "+f"(d[71]),
      "+f"(d[72]), "+f"(d[73]), "+f"(d[74]), "+f"(d[75]), "+f"(d[76]), "+f"(d[77]), "+f"(d[78]), "+f"(d[79]),
      "+f"(d[80]), "+f"(d[81]), "+f"(d[82]), "+f"(d[83]), "+f"(d[84]), "+f"(d[85]), "+f"(d[86]), "+f"(d[87]),
      "+f"(d[88]), "+f"(d[89]), "+f"(d[90]), "+f"(d[91]), "+f"(d[92]), "+f"(d[93]), "+f"(d[94]), "+f"(d[95])
      : "l"(da), "l"(db), "r"(rel), "r"(doR), "r"(fa), "r"(pa), "r"(fb), "r"(pb), "n"(BSTEP), "r"(acc), "r"(rela) : "memory");
    else if constexpr (W == 2 && RC == 2 && RA == 0) asm volatile(
    "{\n.reg .pred p, q, r, t;\n.reg .b64 a, b;\n.reg .u32 n;\nsetp.ne.b32 t, 1, 0;\nsetp.ne.b32 r, %105, 0;\n"
    "wgmma.mma_async.sync.aligned.m64n192k16.f32.bf16.bf16 {"
      "%0, %1, %2, %3, %4, %5, %6, %7, %8, %9, %10, %11, %12, %13, %14, %15, "
      "%16, %17, %18, %19, %20, %21, %22, %23, %24, %25, %26, %27, %28, %29, %30, %31, "
      "%32, %33, %34, %35, %36, %37, %38, %39, %40, %41, %42, %43, %44, %45, %46, %47, "
      "%48, %49, %50, %51, %52, %53, %54, %55, %56, %57, %58, %59, %60, %61, %62, %63, "
      "%64, %65, %66, %67, %68, %69, %70, %71, %72, %73, %74, %75, %76, %77, %78, %79, "
      "%80, %81, %82, %83, %84, %85, %86, %87, %88, %89, %90, %91, %92, %93, %94, %95"
      "}, %96, %97, r, 1, 1, 0, 1;\n"
    "add.u64 a, %96, 2;\nadd.u64 b, %97, %104;\n"
    "wgmma.mma_async.sync.aligned.m64n192k16.f32.bf16.bf16 {"
      "%0, %1, %2, %3, %4, %5, %6, %7, %8, %9, %10, %11, %12, %13, %14, %15, "
      "%16, %17, %18, %19, %20, %21, %22, %23, %24, %25, %26, %27, %28, %29, %30, %31, "
      "%32, %33, %34, %35, %36, %37, %38, %39, %40, %41, %42, %43, %44, %45, %46, %47, "
      "%48, %49, %50, %51, %52, %53, %54, %55, %56, %57, %58, %59, %60, %61, %62, %63, "
      "%64, %65, %66, %67, %68, %69, %70, %71, %72, %73, %74, %75, %76, %77, %78, %79, "
      "%80, %81, %82, %83, %84, %85, %86, %87, %88, %89, %90, %91, %92, %93, %94, %95"
      "}, a, b, t, 1, 1, 0, 1;\n"
    "wgmma.commit_group.sync.aligned;\nwgmma.wait_group.sync.aligned 1;\n"
    "add.u64 a, %96, 4;\nadd.u64 b, %97, 2*%104;\n"
    "wgmma.mma_async.sync.aligned.m64n192k16.f32.bf16.bf16 {"
      "%0, %1, %2, %3, %4, %5, %6, %7, %8, %9, %10, %11, %12, %13, %14, %15, "
      "%16, %17, %18, %19, %20, %21, %22, %23, %24, %25, %26, %27, %28, %29, %30, %31, "
      "%32, %33, %34, %35, %36, %37, %38, %39, %40, %41, %42, %43, %44, %45, %46, %47, "
      "%48, %49, %50, %51, %52, %53, %54, %55, %56, %57, %58, %59, %60, %61, %62, %63, "
      "%64, %65, %66, %67, %68, %69, %70, %71, %72, %73, %74, %75, %76, %77, %78, %79, "
      "%80, %81, %82, %83, %84, %85, %86, %87, %88, %89, %90, %91, %92, %93, %94, %95"
      "}, a, b, t, 1, 1, 0, 1;\n"
    "setp.ne.u32 q, %99, 0;\n@q mbarrier.arrive.shared::cta.b64 _, [%98];\n@q mbarrier.arrive.shared::cta.b64 _, [%98];\n"
    "mbarrier.test_wait.parity.shared::cta.b64 p, [%102], %103;\n"
    "mbarrier.test_wait.parity.shared::cta.b64 r, [%100], %101;\nand.pred p, p, r;\n"
    "add.u64 a, %96, 6;\nadd.u64 b, %97, 3*%104;\n"
    "wgmma.mma_async.sync.aligned.m64n192k16.f32.bf16.bf16 {"
      "%0, %1, %2, %3, %4, %5, %6, %7, %8, %9, %10, %11, %12, %13, %14, %15, "
      "%16, %17, %18, %19, %20, %21, %22, %23, %24, %25, %26, %27, %28, %29, %30, %31, "
      "%32, %33, %34, %35, %36, %37, %38, %39, %40, %41, %42, %43, %44, %45, %46, %47, "
      "%48, %49, %50, %51, %52, %53, %54, %55, %56, %57, %58, %59, %60, %61, %62, %63, "
      "%64, %65, %66, %67, %68, %69, %70, %71, %72, %73, %74, %75, %76, %77, %78, %79, "
      "%80, %81, %82, %83, %84, %85, %86, %87, %88, %89, %90, %91, %92, %93, %94, %95"
      "}, a, b, t, 1, 1, 0, 1;\n"
    "wgmma.commit_group.sync.aligned;\n"
    "@p bra.uni DN;\nmov.u32 n, 0;\nWT: mbarrier.try_wait.parity.shared::cta.b64 p, [%102], %103;\nmbarrier.try_wait.parity.shared::cta.b64 r, [%100], %101;\nand.pred p, p, r;\n@p bra.uni DN;\nadd.u32 n, n, 1;\nsetp.lt.u32 p, n, 0x100000;\n@p bra.uni WT;\nDN:\n"
    "}\n"
      :
      "+f"(d[0]), "+f"(d[1]), "+f"(d[2]), "+f"(d[3]), "+f"(d[4]), "+f"(d[5]), "+f"(d[6]), "+f"(d[7]),
      "+f"(d[8]), "+f"(d[9]), "+f"(d[10]), "+f"(d[11]), "+f"(d[12]), "+f"(d[13]), "+f"(d[14]), "+f"(d[15]),
      "+f"(d[16]), "+f"(d[17]), "+f"(d[18]), "+f"(d[19]), "+f"(d[20]), "+f"(d[21]), "+f"(d[22]), "+f"(d[23]),
      "+f"(d[24]), "+f"(d[25]), "+f"(d[26]), "+f"(d[27]), "+f"(d[28]), "+f"(d[29]), "+f"(d[30]), "+f"(d[31]),
      "+f"(d[32]), "+f"(d[33]), "+f"(d[34]), "+f"(d[35]), "+f"(d[36]), "+f"(d[37]), "+f"(d[38]), "+f"(d[39]),
      "+f"(d[40]), "+f"(d[41]), "+f"(d[42]), "+f"(d[43]), "+f"(d[44]), "+f"(d[45]), "+f"(d[46]), "+f"(d[47]),
      "+f"(d[48]), "+f"(d[49]), "+f"(d[50]), "+f"(d[51]), "+f"(d[52]), "+f"(d[53]), "+f"(d[54]), "+f"(d[55]),
      "+f"(d[56]), "+f"(d[57]), "+f"(d[58]), "+f"(d[59]), "+f"(d[60]), "+f"(d[61]), "+f"(d[62]), "+f"(d[63]),
      "+f"(d[64]), "+f"(d[65]), "+f"(d[66]), "+f"(d[67]), "+f"(d[68]), "+f"(d[69]), "+f"(d[70]), "+f"(d[71]),
      "+f"(d[72]), "+f"(d[73]), "+f"(d[74]), "+f"(d[75]), "+f"(d[76]), "+f"(d[77]), "+f"(d[78]), "+f"(d[79]),
      "+f"(d[80]), "+f"(d[81]), "+f"(d[82]), "+f"(d[83]), "+f"(d[84]), "+f"(d[85]), "+f"(d[86]), "+f"(d[87]),
      "+f"(d[88]), "+f"(d[89]), "+f"(d[90]), "+f"(d[91]), "+f"(d[92]), "+f"(d[93]), "+f"(d[94]), "+f"(d[95])
      : "l"(da), "l"(db), "r"(rel), "r"(doR), "r"(fa), "r"(pa), "r"(fb), "r"(pb), "n"(BSTEP), "r"(acc), "r"(rela) : "memory");
    else if constexpr (W == 2 && RC == 2 && RA == 2) asm volatile(
    "{\n.reg .pred p, q, r, t;\n.reg .b64 a, b;\n.reg .u32 n;\nsetp.ne.b32 t, 1, 0;\nsetp.ne.b32 r, %105, 0;\n"
    "wgmma.mma_async.sync.aligned.m64n192k16.f32.bf16.bf16 {"
      "%0, %1, %2, %3, %4, %5, %6, %7, %8, %9, %10, %11, %12, %13, %14, %15, "
      "%16, %17, %18, %19, %20, %21, %22, %23, %24, %25, %26, %27, %28, %29, %30, %31, "
      "%32, %33, %34, %35, %36, %37, %38, %39, %40, %41, %42, %43, %44, %45, %46, %47, "
      "%48, %49, %50, %51, %52, %53, %54, %55, %56, %57, %58, %59, %60, %61, %62, %63, "
      "%64, %65, %66, %67, %68, %69, %70, %71, %72, %73, %74, %75, %76, %77, %78, %79, "
      "%80, %81, %82, %83, %84, %85, %86, %87, %88, %89, %90, %91, %92, %93, %94, %95"
      "}, %96, %97, r, 1, 1, 0, 1;\n"
    "add.u64 a, %96, 2;\nadd.u64 b, %97, %104;\n"
    "wgmma.mma_async.sync.aligned.m64n192k16.f32.bf16.bf16 {"
      "%0, %1, %2, %3, %4, %5, %6, %7, %8, %9, %10, %11, %12, %13, %14, %15, "
      "%16, %17, %18, %19, %20, %21, %22, %23, %24, %25, %26, %27, %28, %29, %30, %31, "
      "%32, %33, %34, %35, %36, %37, %38, %39, %40, %41, %42, %43, %44, %45, %46, %47, "
      "%48, %49, %50, %51, %52, %53, %54, %55, %56, %57, %58, %59, %60, %61, %62, %63, "
      "%64, %65, %66, %67, %68, %69, %70, %71, %72, %73, %74, %75, %76, %77, %78, %79, "
      "%80, %81, %82, %83, %84, %85, %86, %87, %88, %89, %90, %91, %92, %93, %94, %95"
      "}, a, b, t, 1, 1, 0, 1;\n"
    "wgmma.commit_group.sync.aligned;\nwgmma.wait_group.sync.aligned 1;\n"
    "add.u64 a, %96, 4;\nadd.u64 b, %97, 2*%104;\n"
    "wgmma.mma_async.sync.aligned.m64n192k16.f32.bf16.bf16 {"
      "%0, %1, %2, %3, %4, %5, %6, %7, %8, %9, %10, %11, %12, %13, %14, %15, "
      "%16, %17, %18, %19, %20, %21, %22, %23, %24, %25, %26, %27, %28, %29, %30, %31, "
      "%32, %33, %34, %35, %36, %37, %38, %39, %40, %41, %42, %43, %44, %45, %46, %47, "
      "%48, %49, %50, %51, %52, %53, %54, %55, %56, %57, %58, %59, %60, %61, %62, %63, "
      "%64, %65, %66, %67, %68, %69, %70, %71, %72, %73, %74, %75, %76, %77, %78, %79, "
      "%80, %81, %82, %83, %84, %85, %86, %87, %88, %89, %90, %91, %92, %93, %94, %95"
      "}, a, b, t, 1, 1, 0, 1;\n"
    "setp.ne.u32 q, %99, 0;\n@q mbarrier.arrive.shared::cta.b64 _, [%98];\n@q mbarrier.arrive.shared::cta.b64 _, [%98];\n@q mbarrier.arrive.shared::cta.b64 _, [%106];\n@q mbarrier.arrive.shared::cta.b64 _, [%106];\n"
    "mbarrier.test_wait.parity.shared::cta.b64 p, [%102], %103;\n"
    "mbarrier.test_wait.parity.shared::cta.b64 r, [%100], %101;\nand.pred p, p, r;\n"
    "add.u64 a, %96, 6;\nadd.u64 b, %97, 3*%104;\n"
    "wgmma.mma_async.sync.aligned.m64n192k16.f32.bf16.bf16 {"
      "%0, %1, %2, %3, %4, %5, %6, %7, %8, %9, %10, %11, %12, %13, %14, %15, "
      "%16, %17, %18, %19, %20, %21, %22, %23, %24, %25, %26, %27, %28, %29, %30, %31, "
      "%32, %33, %34, %35, %36, %37, %38, %39, %40, %41, %42, %43, %44, %45, %46, %47, "
      "%48, %49, %50, %51, %52, %53, %54, %55, %56, %57, %58, %59, %60, %61, %62, %63, "
      "%64, %65, %66, %67, %68, %69, %70, %71, %72, %73, %74, %75, %76, %77, %78, %79, "
      "%80, %81, %82, %83, %84, %85, %86, %87, %88, %89, %90, %91, %92, %93, %94, %95"
      "}, a, b, t, 1, 1, 0, 1;\n"
    "wgmma.commit_group.sync.aligned;\n"
    "@p bra.uni DN;\nmov.u32 n, 0;\nWT: mbarrier.try_wait.parity.shared::cta.b64 p, [%102], %103;\nmbarrier.try_wait.parity.shared::cta.b64 r, [%100], %101;\nand.pred p, p, r;\n@p bra.uni DN;\nadd.u32 n, n, 1;\nsetp.lt.u32 p, n, 0x100000;\n@p bra.uni WT;\nDN:\n"
    "}\n"
      :
      "+f"(d[0]), "+f"(d[1]), "+f"(d[2]), "+f"(d[3]), "+f"(d[4]), "+f"(d[5]), "+f"(d[6]), "+f"(d[7]),
      "+f"(d[8]), "+f"(d[9]), "+f"(d[10]), "+f"(d[11]), "+f"(d[12]), "+f"(d[13]), "+f"(d[14]), "+f"(d[15]),
      "+f"(d[16]), "+f"(d[17]), "+f"(d[18]), "+f"(d[19]), "+f"(d[20]), "+f"(d[21]), "+f"(d[22]), "+f"(d[23]),
      "+f"(d[24]), "+f"(d[25]), "+f"(d[26]), "+f"(d[27]), "+f"(d[28]), "+f"(d[29]), "+f"(d[30]), "+f"(d[31]),
      "+f"(d[32]), "+f"(d[33]), "+f"(d[34]), "+f"(d[35]), "+f"(d[36]), "+f"(d[37]), "+f"(d[38]), "+f"(d[39]),
      "+f"(d[40]), "+f"(d[41]), "+f"(d[42]), "+f"(d[43]), "+f"(d[44]), "+f"(d[45]), "+f"(d[46]), "+f"(d[47]),
      "+f"(d[48]), "+f"(d[49]), "+f"(d[50]), "+f"(d[51]), "+f"(d[52]), "+f"(d[53]), "+f"(d[54]), "+f"(d[55]),
      "+f"(d[56]), "+f"(d[57]), "+f"(d[58]), "+f"(d[59]), "+f"(d[60]), "+f"(d[61]), "+f"(d[62]), "+f"(d[63]),
      "+f"(d[64]), "+f"(d[65]), "+f"(d[66]), "+f"(d[67]), "+f"(d[68]), "+f"(d[69]), "+f"(d[70]), "+f"(d[71]),
      "+f"(d[72]), "+f"(d[73]), "+f"(d[74]), "+f"(d[75]), "+f"(d[76]), "+f"(d[77]), "+f"(d[78]), "+f"(d[79]),
      "+f"(d[80]), "+f"(d[81]), "+f"(d[82]), "+f"(d[83]), "+f"(d[84]), "+f"(d[85]), "+f"(d[86]), "+f"(d[87]),
      "+f"(d[88]), "+f"(d[89]), "+f"(d[90]), "+f"(d[91]), "+f"(d[92]), "+f"(d[93]), "+f"(d[94]), "+f"(d[95])
      : "l"(da), "l"(db), "r"(rel), "r"(doR), "r"(fa), "r"(pa), "r"(fb), "r"(pb), "n"(BSTEP), "r"(acc), "r"(rela) : "memory");
    else static_assert(W < 0, "variant not generated");
  }
};

#define NPRE 2
#define KV_T0 4000
#define KV2T 2000
#define XSD 400
#define CSD 600
#define ZW 300
#define TP_T 5000
#define PF2_D 200
#define PF_D 600
#define LKI 14
#define LEAD 4
#define HD 300
#define YD 600
#define HP0 3500
#define HPD 450
#define NSLEEP 100
#define MAP 4
#define EARLY 0

namespace {

constexpr int kS = 2048, kD = 640, kF = 1536;
constexpr int A_SLOT = 8192, B_SLOT = 24576, W_SLOT = 20480;
constexpr int OFF_A = 0;
constexpr int OFF_B = OFF_A + 10 * A_SLOT;
constexpr int XB_PL = 2112;
constexpr int CV_KE = 4224, CV_KO = CV_KE + 4160;
constexpr int CV_SZ = CV_KO + 4160;
constexpr int OFF_CV = OFF_B + 5 * B_SLOT;
constexpr int OFF_CS = OFF_CV + 2 * CV_SZ;
constexpr int OFF_XS = OFF_CS + 1536;
constexpr int OFF_BAR = OFF_XS + 512;
constexpr int SMEM_BYTES = OFF_BAR + 512;
static_assert(SMEM_BYTES <= 232448, "smem");
constexpr int OFF_RT = OFF_CS + 768;
constexpr int BAR_AF = OFF_BAR, BAR_BF = OFF_BAR + 8 * 10, BAR_WF = OFF_BAR + 8 * 15, BAR_ST = OFF_BAR + 8 * 21, BAR_XF = OFF_BAR + 8 * 23;
constexpr int BAR_ZP = OFF_BAR + 8 * 25, BAR_DUMMY = OFF_BAR + 8 * 27, BAR_PART = OFF_BAR + 8 * 28, BAR_WO = OFF_BAR + 8 * 29;
constexpr int BAR_YT = OFF_BAR + 8 * 30, BAR_KV2 = OFF_BAR + 8 * 31, BAR_XS = OFF_BAR + 8 * 32, BAR_HOLD = OFF_BAR + 8 * 33, BAR_ZG = OFF_BAR + 8 * 34;
constexpr int OFF_TAG = OFF_BAR + 8 * 35;
constexpr int BAR_HV = OFF_BAR + 8 * 36;
constexpr int BAR_HR = BAR_HV + 64, BAR_B2 = OFF_BAR + 8 * 26;
constexpr int BAR_XL = OFF_CS - 16;
constexpr int BAR_AE = OFF_BAR + 8 * 45, BAR_BE = OFF_BAR + 8 * 53, BAR_WE = OFF_BAR + 8 * 58;
constexpr int NB_WG = 1, NB_G1 = 3, NB_WO = 4, NB_CD = 5, NB_Z = 6, NB_C = 7, NB_KU = 8, NB_SV = 9, NB_KF = 12, NB_G1D = 13, NB_KU2 = 14, NB_KL = 15;

#define NB_SV2(h) ((h) ? NB_KU2 : NB_KU)

constexpr int CNT_KV = 0, CNT_WO = 4, CNT_Z = 8;
struct Scratch {
  uint8_t kvx[kD * 4096];
  uint8_t z2[4 * 32 * 24576];
  uint8_t h[32 * 12 * 8192];
  uint8_t wo[4 * 12 * 20480];
  uint8_t y[kD * 4096];
  uint4 zstat[32 * 128];
  uint2 xstat[kS];
  uint32_t colsum[kF];
  uint32_t cnt[32];
  uint32_t hflag[32 * 32];
  uint32_t epoch[136];

};
__device__ __align__(1024) Scratch g_scr;
#define TSP
#define TSA
#define TR(i)
#define STAMP(i)
#define STAMPE(i)
#define STAMP2(i)
#define STAMPW(i)

struct Params {
  Scratch* scr;
  int by_smid;
  const __nv_bfloat16 *x, *k, *v, *shift, *ssmk, *ssmD, *wsp, *bsp, *wout;
  __nv_bfloat16* out;
  CUtensorMap tmX, tmW, tmWsp, tmY, tmKV;
  uint16_t job[132];
};

__device__ __forceinline__ uint64_t mkdesc(uint32_t addr, uint32_t lbo, uint32_t sbo, uint32_t swz) {
  return (uint64_t)((addr & 0x3FFFF) >> 4) | ((uint64_t)(lbo >> 4) << 16) | ((uint64_t)(sbo >> 4) << 32) | ((uint64_t)swz << 62);
}
#define WG_FENCE() asm volatile("wgmma.fence.sync.aligned;" ::: "memory")
#define WG_COMMIT() asm volatile("wgmma.commit_group.sync.aligned;" ::: "memory")
#define WG_WAIT(n) asm volatile("wgmma.wait_group.sync.aligned %0;" ::"n"(n) : "memory")
template <int N> __device__ __forceinline__ void acc_fence(float* d) {
#pragma unroll
  for (int i = 0; i < N; i++) asm volatile("" : "+f"(d[i])::"memory");
}
__device__ __forceinline__ void mbar_init(uint32_t bar, int cnt) { asm volatile("mbarrier.init.shared::cta.b64 [%0], %1;" ::"r"(bar), "r"(cnt) : "memory"); }
__device__ __forceinline__ void mbar_expect(uint32_t bar, uint32_t bytes) { asm volatile("mbarrier.arrive.expect_tx.shared::cta.b64 _, [%0], %1;" ::"r"(bar), "r"(bytes) : "memory"); }
__device__ __forceinline__ void mbar_arrive(uint32_t bar) { asm volatile("mbarrier.arrive.shared::cta.b64 _, [%0];" ::"r"(bar) : "memory"); }
__device__ __forceinline__ void mbar_arrive_if(uint32_t bar, bool c) {
  asm volatile("{\n.reg .pred p;\nsetp.ne.u32 p, %1, 0;\n@p mbarrier.arrive.shared::cta.b64 _, [%0];\n}\n" ::"r"(bar), "r"((uint32_t)c) : "memory");
}
__device__ __forceinline__ bool mbar_try(uint32_t bar, uint32_t parity) {
  uint32_t ok;
  asm volatile("{\n.reg .pred p;\nmbarrier.try_wait.parity.shared::cta.b64 p, [%1], %2;\nselp.u32 %0, 1, 0, p;\n}\n" : "=r"(ok) : "r"(bar), "r"(parity) : "memory");
  return ok;
}
__device__ __forceinline__ void die() { asm volatile("st.volatile.global.u32 [%0], %1;" ::"l"(0ull), "r"(0) : "memory"); }
template <bool G = false> __device__ __forceinline__ void spin_guard(uint32_t& n, uint32_t = 0) { if (G && ++n == (1u << 20)) die(); }
template <bool G = false> __device__ __forceinline__ void mbar_wait(uint32_t bar, uint32_t parity) {
  uint32_t t0 = 0;
#pragma unroll 1
  while (!mbar_try(bar, parity)) spin_guard<G>(t0, bar);
}
__device__ __forceinline__ void mbar_wait2(uint32_t b0, uint32_t p0, uint32_t b1, uint32_t p1) { mbar_wait(b0, p0); mbar_wait(b1, p1); }
__device__ __forceinline__ int tid_now() { int v; asm volatile("mov.u32 %0, %%tid.x;" : "=r"(v)); return v & 127; }
__device__ __forceinline__ bool elect_one() {
  uint32_t p;
  asm volatile("{\n.reg .pred P;\nelect.sync _|P, 0xffffffff;\nselp.u32 %0, 1, 0, P;\n}\n" : "=r"(p));
  return p;
}
__device__ __forceinline__ void bar_sync(int id, int n) { asm volatile("bar.sync %0, %1;" ::"r"(id), "r"(n) : "memory"); }
__device__ __forceinline__ void bar_arrive(int id, int n) { asm volatile("bar.arrive %0, %1;" ::"r"(id), "r"(n) : "memory"); }
__device__ __forceinline__ void fence_async_smem() { asm volatile("fence.proxy.async.shared::cta;" ::: "memory"); }
__device__ __forceinline__ void bulk_g2s(uint32_t dst, const void* src, uint32_t bytes, uint32_t bar) {
  asm volatile("cp.async.bulk.shared::cluster.global.mbarrier::complete_tx::bytes [%0], [%1], %2, [%3];" ::"r"(dst), "l"(src), "r"(bytes), "r"(bar) : "memory");
}
__device__ __forceinline__ void bulk_s2g(void* dst, uint32_t src, uint32_t bytes) {
  asm volatile("cp.async.bulk.global.shared::cta.bulk_group [%0], [%1], %2;" ::"l"(dst), "r"(src), "r"(bytes) : "memory");
}
__device__ __forceinline__ void tma2d(uint32_t dst, const CUtensorMap* m, int c0, int c1, uint32_t bar) {
  asm volatile("cp.async.bulk.tensor.2d.shared::cluster.global.mbarrier::complete_tx::bytes [%0], [%1, {%3, %4}], [%2];" ::"r"(dst), "l"(m), "r"(bar), "r"(c0), "r"(c1) : "memory");
}
__device__ __forceinline__ void tma3d(uint32_t dst, const CUtensorMap* m, int c0, int c1, int c2, uint32_t bar) {
  asm volatile("cp.async.bulk.tensor.3d.shared::cluster.global.mbarrier::complete_tx::bytes [%0], [%1, {%3, %4, %5}], [%2];" ::"r"(dst), "l"(m), "r"(bar), "r"(c0), "r"(c1), "r"(c2) : "memory");
}
__device__ __forceinline__ uint4 ld_ll4(const void* p) {
  uint64_t a, b;
  asm volatile("ld.relaxed.gpu.global.v2.u64 {%0,%1}, [%2];" : "=l"(a), "=l"(b) : "l"(p) : "memory");
  return make_uint4((uint32_t)a, (uint32_t)(a >> 32), (uint32_t)b, (uint32_t)(b >> 32));
}
__device__ __forceinline__ void st_ll4(void* p, uint32_t a, uint32_t b, uint32_t c, uint32_t d) {
  asm volatile("st.relaxed.gpu.global.v2.u64 [%0], {%1,%2};" ::"l"(p), "l"(a | ((uint64_t)b << 32)), "l"(c | ((uint64_t)d << 32)) : "memory");
}
__device__ __forceinline__ void st_ll2(void* p, uint32_t a, uint32_t b) { asm volatile("st.relaxed.gpu.global.u64 [%0], %1;" ::"l"(p), "l"(a | ((uint64_t)b << 32)) : "memory"); }
__device__ __forceinline__ void wgmma_colsum(float* d, uint64_t da, uint64_t db) {
  asm volatile("{\n.reg .pred p;\nsetp.ne.b32 p, 1, 0;\nwgmma.mma_async.sync.aligned.m64n8k16.f32.bf16.bf16 {%0, %1, %2, %3}, %4, %5, p, 1, 1, 1, 0;\n}\n"
               : "+f"(d[0]), "+f"(d[1]), "+f"(d[2]), "+f"(d[3]) : "l"(da), "l"(db));
}
__device__ __forceinline__ void prefetch_l2(const void* p) { asm volatile("prefetch.global.L2 [%0];" ::"l"(p)); }
template <bool SLEEP = true> __device__ __forceinline__ void pace(uint32_t& t, uint32_t dt) {
  t += dt;
  while ((int32_t)((uint32_t)clock() - t) < 0) { if (SLEEP) __nanosleep(NSLEEP); }
}
__device__ __forceinline__ void red_release(uint32_t* p) { asm volatile("red.release.gpu.global.add.u32 [%0], 1;" ::"l"(p) : "memory"); }
__device__ __forceinline__ uint4 ldg4(const void* p) { uint4 v; asm volatile("ld.global.v4.u32 {%0,%1,%2,%3}, [%4];" : "=r"(v.x), "=r"(v.y), "=r"(v.z), "=r"(v.w) : "l"(p) : "memory"); return v; }
__device__ __forceinline__ uint32_t ldg1(const void* p) { uint32_t v; asm volatile("ld.global.u32 %0, [%1];" : "=r"(v) : "l"(p) : "memory"); return v; }
__device__ __forceinline__ void stg4_if(void* p, uint32_t a, uint32_t b, uint32_t c, uint32_t d, bool on) {
  asm volatile("{\n.reg .pred p;\nsetp.ne.u32 p, %5, 0;\n@p st.global.v4.u32 [%0], {%1,%2,%3,%4};\n}\n" ::"l"(p), "r"(a), "r"(b), "r"(c), "r"(d), "r"((uint32_t)on) : "memory");
}
template <int OFF> __device__ __forceinline__ uint32_t lds32(uint32_t a) { uint32_t v; asm volatile("ld.shared.u32 %0, [%1+%2];" : "=r"(v) : "r"(a), "n"(OFF)); return v; }
__device__ __forceinline__ uint4 lds128(uint32_t a) { uint4 v; asm volatile("ld.shared.v4.u32 {%0,%1,%2,%3}, [%4];" : "=r"(v.x), "=r"(v.y), "=r"(v.z), "=r"(v.w) : "r"(a) : "memory"); return v; }
__device__ __forceinline__ float2 lds64f(uint32_t a) { float2 v; asm volatile("ld.shared.v2.f32 {%0,%1}, [%2];" : "=f"(v.x), "=f"(v.y) : "r"(a) : "memory"); return v; }
__device__ __forceinline__ void sts64f(uint32_t a, float x, float y) { asm volatile("st.shared.v2.f32 [%0], {%1,%2};" ::"r"(a), "f"(x), "f"(y) : "memory"); }
__device__ __forceinline__ void sts32(uint32_t a, uint32_t x) { asm volatile("st.shared.u32 [%0], %1;" ::"r"(a), "r"(x) : "memory"); }
__device__ __forceinline__ void sts128(uint32_t a, uint32_t x, uint32_t y, uint32_t z, uint32_t w) { asm volatile("st.shared.v4.u32 [%0], {%1,%2,%3,%4};" ::"r"(a), "r"(x), "r"(y), "r"(z), "r"(w) : "memory"); }
__device__ __forceinline__ void stsm4(uint32_t a, uint32_t r0, uint32_t r1, uint32_t r2, uint32_t r3) {
  asm volatile("stmatrix.sync.aligned.m8n8.x4.shared.b16 [%0], {%1,%2,%3,%4};" ::"r"(a), "r"(r0), "r"(r1), "r"(r2), "r"(r3) : "memory");
}
__device__ __forceinline__ void stsm4t(uint32_t a, uint32_t r0, uint32_t r1, uint32_t r2, uint32_t r3) {
  asm volatile("stmatrix.sync.aligned.m8n8.x4.trans.shared.b16 [%0], {%1,%2,%3,%4};" ::"r"(a), "r"(r0), "r"(r1), "r"(r2), "r"(r3) : "memory");
}
__device__ __forceinline__ void ldsm4t(uint32_t* r, uint32_t a) {
  asm volatile("ldmatrix.sync.aligned.m8n8.x4.trans.shared.b16 {%0,%1,%2,%3}, [%4];" : "=r"(r[0]), "=r"(r[1]), "=r"(r[2]), "=r"(r[3]) : "r"(a) : "memory");
}
__device__ __forceinline__ uint32_t pack2(float lo, float hi) { uint32_t r; asm("cvt.rn.bf16x2.f32 %0, %1, %2;" : "=r"(r) : "f"(hi), "f"(lo)); return r; }
__device__ __forceinline__ float bf_lo(uint32_t u) { return __uint_as_float(u << 16); }
__device__ __forceinline__ float bf_hi(uint32_t u) { return __uint_as_float(u & 0xffff0000u); }
__device__ __forceinline__ uint32_t hmul2(uint32_t a, uint32_t b) { uint32_t r; asm("mul.rn.bf16x2 %0, %1, %2;" : "=r"(r) : "r"(a), "r"(b)); return r; }
__device__ __forceinline__ uint32_t hfma2(uint32_t a, uint32_t b, uint32_t c) { uint32_t r; asm("fma.rn.bf16x2 %0, %1, %2, %3;" : "=r"(r) : "r"(a), "r"(b), "r"(c)); return r; }
__device__ __forceinline__ uint32_t prmt(uint32_t a, uint32_t b, uint32_t s) { return __byte_perm(a, b, s); }

__device__ __forceinline__ uint32_t ld_relaxed(const uint32_t* p) { uint32_t v; asm volatile("ld.relaxed.gpu.global.u32 %0, [%1];" : "=r"(v) : "l"(p) : "memory"); return v; }
__device__ __forceinline__ void acquire_fence() { asm volatile("fence.acquire.gpu;\nfence.proxy.async.global;" ::: "memory"); }
__device__ __forceinline__ uint32_t load_epoch(const Params& p, int idx, int lane) { return ld_relaxed(&p.scr->epoch[idx + (((lane * lane) & 3) == 2 ? 1 : 0)]); }
template <bool G, class L, class C>
__device__ __forceinline__ auto poll(L load, C ok) {
  uint32_t t0 = 0;
  auto a = load();
#pragma unroll 1
  while (!__all_sync(0xffffffff, ok(a))) { spin_guard<G>(t0); a = load(); }
  return a;
}
__device__ __forceinline__ void poll_flags4(const uint32_t* flags, uint32_t tag, int lane) {
  poll<false>([&]() { return ld_relaxed(flags + (lane & 3) * 8); }, [&](uint32_t v) { return v == tag; });
  acquire_fence();
}
__device__ __forceinline__ void st_relaxed(uint32_t* p, uint32_t v) { asm volatile("st.relaxed.gpu.global.u32 [%0], %1;" ::"l"(p), "r"(v) : "memory"); }
__device__ __forceinline__ uint32_t tag8(uint32_t tag) { return (tag & 127) | 128; }
__device__ __forceinline__ uint32_t tagged(float v, uint32_t t8) { return (__float_as_uint(v) & ~255u) | t8; }
__device__ __forceinline__ void reset_sector(uint32_t* f) { st_ll4(f, 0, 0, 0, 0); st_ll4(f + 4, 0, 0, 0, 0); }
template <bool G = false> __device__ __forceinline__ void poll_counter(const uint32_t* cnt, uint32_t target) {
  poll<G>([&]() { return ld_relaxed(cnt); }, [&](uint32_t v) { return v == target; });
  acquire_fence();
}

__device__ __forceinline__ uint32_t hadd2(uint32_t a, uint32_t b) { uint32_t r; asm("add.rn.bf16x2 %0, %1, %2;" : "=r"(r) : "r"(a), "r"(b)); return r; }
__device__ __forceinline__ uint32_t htanh2(uint32_t a) { uint32_t r; asm("tanh.approx.bf16x2 %0, %1;" : "=r"(r) : "r"(a)); return r; }
__device__ __forceinline__ void red_relaxed(uint32_t* p) { asm volatile("red.relaxed.gpu.global.add.u32 [%0], 1;" ::"l"(p) : "memory"); }
__device__ __forceinline__ void bulk_commit_wait() { asm volatile("cp.async.bulk.commit_group;\ncp.async.bulk.wait_group 0;" ::: "memory"); }

__host__ __device__ constexpr uint32_t w_pos(int j) { j -= j >= 6 ? 6 : 0; return OFF_B + (j >= 3 ? j - 3 : j + 3) * W_SLOT; }
__host__ __device__ constexpr uint32_t w_full(int j) { return BAR_WF + 8 * (j >= 6 ? j - 6 : j); }
__host__ __device__ constexpr uint32_t h_pos(int i) { return (i >= 9 ? i - 9 : i) * A_SLOT; }
__device__ __forceinline__ int g3_block(int cb, int it) { return it < 3 ? cb * 3 + it : (it - 3 < cb * 3 ? it - 3 : it); }

#define GSTAMP(m, i)
struct NoHook { __device__ __forceinline__ void operator()() const {} };
template <int MODE, class F = NoHook>
__device__ __forceinline__ void gemm192(float* d, uint32_t sb, uint32_t doR TSP, F hook = F()) {
  constexpr int NKB = MODE == 1 ? 32 : 10, W = MODE == 3 ? 1 : 2, RA = MODE == 0 ? 0 : 2;
  const uint64_t da0 = mkdesc(sb + OFF_A, 16, 1024, 1), db0 = mkdesc(sb + OFF_B, 8192, 1024, 1);
  auto sa = [](int i) { return MODE == 1 ? (i + 3) & 7 : i; };
  auto pa = [](int i) { return MODE == 1 ? ((i >> 3) & 1) ^ 1 : 0; };
  const uint32_t dummy = sb + BAR_DUMMY;
  auto ea = [&](int i) { return MODE == 3 && i >= 8 ? dummy : sb + BAR_AE + 8 * sa(i); };
  uint32_t rel = dummy, rela = dummy;
  uint32_t pb = 0, acc = MODE == 1;
  int s = 0;
  acc_fence<96>(d);
  if (W == 2) mbar_wait(sb + BAR_AF + 8 * sa(0), pa(0));
  mbar_wait(sb + BAR_BF, 0);
  WG_FENCE();
#pragma unroll 1
  for (int i = 0; i < NKB - 1; i++) {
    GSTAMP(MODE, i);
    const int n = s == 4 ? 0 : s + 1;
    if (n == 0) pb ^= 1;
    KB<192>::run<W, 2, RA, 128>(d, da0 + sa(i) * (A_SLOT >> 4), db0 + s * (B_SLOT >> 4), rel, rela, doR, sb + BAR_AF + 8 * sa(i + 1), pa(i + 1), sb + BAR_BF + 8 * n, pb, acc);
    rel = sb + BAR_BE + 8 * s;
    rela = ea(i);
    s = n;
    acc = 1;
  }
  hook();
  GSTAMP(MODE, NKB - 1);
  KB<192>::run<0, 2, RA, 128>(d, da0 + sa(NKB - 1) * (A_SLOT >> 4), db0 + s * (B_SLOT >> 4), rel, rela, doR, 0, 0, 0, 0, 1);
  WG_WAIT(0);
  GSTAMP(MODE, NKB);
  acc_fence<96>(d);
  mbar_arrive_if(sb + BAR_BE + 8 * s, doR);
  mbar_arrive_if(sb + BAR_BE + 8 * s, doR);
  if (RA) { mbar_arrive_if(ea(NKB - 1), doR); mbar_arrive_if(ea(NKB - 1), doR); }
}
template <int I, int I1, bool OWN>
__device__ __forceinline__ void gemm3(float* d, uint32_t sb, uint64_t da0, uint64_t db0, uint32_t doR, uint32_t doR3 TSP) {
  if constexpr (I < I1) {
    GSTAMP(2, I);
    constexpr int W = (I == 11 || (OWN && I == 2)) ? 0 : (I < 2 ? 1 : 2), RC = I >= 1 && I <= 6;
    KB<80>::run<W, RC, I == 3, 320>(d, da0 + (h_pos(I) >> 4), db0 + (w_pos(I) >> 4), sb + (BAR_WE - 8 + 8 * I), sb + BAR_B2, I == 3 ? doR3 : doR,
                                    sb + (BAR_HV - 16 + 8 * I), I + 1 >= 9, sb + w_full(I + 1), I + 1 >= 6, I > 0);
    gemm3<I + 1, I1, OWN>(d, sb, da0, db0, doR, doR3 TSA);
  }
}

__device__ __forceinline__ uint32_t val_off(int lane) { return lane * 32 + ((lane >> 2) & 1) * 16 + (lane >> 3) * 4; }
template <int NK, int PAD = 0, class F>
__device__ __forceinline__ void validate(uint32_t a, uint32_t par, uint32_t rt, F reload) {
  uint32_t t0 = 0;
#pragma unroll 1
  while (true) {
    uint32_t v[NK], any = 0;
#pragma unroll
    for (int i = 0; i < NK; i++) asm volatile("ld.shared.u32 %0, [%1];" : "=r"(v[i]) : "r"(a + i * 1024 + (i >> 1) * PAD) : "memory");
#pragma unroll
    for (int i = 0; i < NK; i++) any |= v[i] ^ par;
    if (!__any_sync(0xffffffff, any & 1)) break;
    spin_guard(t0);
    fence_async_smem();
    __syncwarp();
    if (elect_one()) { mbar_init(rt, 1); fence_async_smem(); mbar_expect(rt, NK * 1024); reload(); }
    __syncwarp();
    mbar_wait(rt, 0);
    __syncwarp();
    if (elect_one()) asm volatile("mbarrier.inval.shared::cta.b64 [%0];" ::"r"(rt) : "memory");
  }
}
__device__ __forceinline__ uint32_t part_addr(uint32_t sb, int j, int t) { const int q = j * 128 + t; return sb + OFF_B + 5 * W_SLOT + (q / 80) * 2560 + (q % 80) * 16; }
__device__ __forceinline__ uint32_t swz_base(uint32_t img, int w, int lane) { return img + (w * 16 + (lane & 15)) * 128 + (((lane >> 4) ^ lane) & 7) * 16; }

template <bool STATS>
__device__ __forceinline__ void gelu_tile(const float* d, uint32_t* z, float* st, uint32_t cs0, float2 s0, float2 s1, uint32_t done) {
  const float kA = 0.7978845608028654f, kB = 0.7978845608028654f * 0.044715f;
  const float ra = s0.y, rb = s1.y;
  const float a1 = kA * ra, a3 = kB * ra * ra * ra, b1 = kA * rb, b3 = kB * rb * rb * rb;
  const uint32_t c1[2] = {pack2(a1, a1), pack2(b1, b1)}, c3[2] = {pack2(a3, a3), pack2(b3, b3)};
  const float m[2] = {-s0.x, -s1.x};
  uint32_t S[2][2], Q[2][2];
#pragma unroll
  for (int j = 0; j < 24; j++) {
    if (!STATS && j && j % 6 == 0) mbar_wait(done, 0);
    const float2 cs = lds64f(cs0 + j * 32);
#pragma unroll
    for (int r = 0; r < 2; r++) {
      const uint32_t v = pack2(fmaf(m[r], cs.x, d[4 * j + 2 * r]), fmaf(m[r], cs.y, d[4 * j + 2 * r + 1]));
      uint32_t y = hfma2(v, htanh2(hmul2(v, hfma2(hmul2(v, v), c3[r], c1[r]))), v);
      asm volatile("" : "+r"(y));
      z[2 * j + r] = y;
      if (STATS) {
        S[r][j & 1] = j < 2 ? y : hadd2(S[r][j & 1], y);
        Q[r][j & 1] = j < 2 ? hmul2(y, y) : hfma2(y, y, Q[r][j & 1]);
      }
    }
  }
  if (STATS) {
#pragma unroll
    for (int r = 0; r < 2; r++) {
      st[2 * r] = (bf_lo(S[r][0]) + bf_hi(S[r][0])) + (bf_lo(S[r][1]) + bf_hi(S[r][1]));
      st[2 * r + 1] = (bf_lo(Q[r][0]) + bf_hi(Q[r][0])) + (bf_lo(Q[r][1]) + bf_hi(Q[r][1]));
    }
  }
}

__device__ __forceinline__ float2 quad_sum(const float* st, int t) {
  const bool o = t & 1;
  float s = (o ? st[2] : st[0]) + __shfl_xor_sync(0xffffffff, o ? st[0] : st[2], 1);
  float q = (o ? st[3] : st[1]) + __shfl_xor_sync(0xffffffff, o ? st[1] : st[3], 1);
  s += __shfl_xor_sync(0xffffffff, s, 2);
  q += __shfl_xor_sync(0xffffffff, q, 2);
  return make_float2(s, q);
}
template <int Q> __device__ __forceinline__ void conv_load(uint32_t* a, uint32_t ab) {
  a[0] = lds32<512 * Q>(ab);       a[1] = lds32<512 * Q + 256>(ab);  a[2] = lds32<512 * Q + 16>(ab);   a[3] = lds32<512 * Q + 272>(ab);
  a[4] = lds32<512 * Q + 32>(ab);  a[5] = lds32<512 * Q + 288>(ab);  a[6] = lds32<512 * Q + 48>(ab);   a[7] = lds32<512 * Q + 304>(ab);
  a[8] = lds32<512 * Q + 64>(ab);  a[9] = lds32<512 * Q + 320>(ab);  a[10] = lds32<512 * Q + 80>(ab);  a[11] = lds32<512 * Q + 336>(ab);
  a[12] = lds32<512 * Q + 96>(ab); a[13] = lds32<512 * Q + 352>(ab); a[14] = lds32<512 * Q + 112>(ab); a[15] = lds32<512 * Q + 368>(ab);
}
template <int Q, int L> __device__ __forceinline__ void conv_step(float* d, uint32_t (*a)[16], uint32_t ab, uint64_t db) {
  WG_FENCE();
#pragma unroll
  for (int s = 0; s < 4; s++) WG<128 - 16 * Q>::rs(d, a[Q] + 4 * s, db + s + 16 * Q);
  WG_COMMIT();
  WG_WAIT(1);
  if (L >= 0) conv_load<(L >= 0 ? L : 0)>(a[L >= 0 ? L : 0], ab);
  if (Q == 0) WG_WAIT(0);
}

__device__ __forceinline__ void final_load_x(uint32_t (*xw)[10], const __nv_bfloat16* x0, int t) {
#pragma unroll
  for (int r = 0; r < 2; r++) {
    const __nv_bfloat16* q = x0 + r * 8 * kD;
    const uint4 u = ldg4(q + t * 8), v = ldg4(q + 32 + t * 8);
    asm volatile("ld.global.v2.u32 {%0,%1}, [%2];" : "=r"(xw[r][8]), "=r"(xw[r][9]) : "l"(q + 64 + t * 4) : "memory");
    xw[r][0] = u.x; xw[r][1] = u.y; xw[r][2] = u.z; xw[r][3] = u.w;
    xw[r][4] = v.x; xw[r][5] = v.y; xw[r][6] = v.z; xw[r][7] = v.w;
  }
}
template <class F>
__device__ __forceinline__ void final_out(const float* d, const uint32_t (*xw)[10], const uint32_t* rn, const float* c, uint32_t yt, __nv_bfloat16* o0, int w, int lane, F wait_y) {
  const int r8 = lane & 7, mi = lane >> 3, t = lane & 3;
  const uint32_t ya = yt + ((mi >> 1) * 8 + r8) * 128 + (((2 * w + (mi & 1)) ^ r8) << 4);
#pragma unroll
  for (int q = 0; q < 3; q++) {
    const int n = q < 2 ? 8 : 4;
    uint32_t gt[8], y[8];
#pragma unroll
    for (int e = 0; e < n; e++) {
      const int i = q * 8 + e;
      const uint32_t h = pack2(d[2 * i] * c[i & 1], d[2 * i + 1] * c[i & 1]);
      gt[e] = hmul2(hfma2(h, htanh2(h), h), hfma2(xw[i & 1][i >> 1], rn[i & 1], rn[2 + (i & 1)]));
      if (q == 0) asm volatile("" : "+r"(gt[e]));
    }
    if (q == 0) wait_y();
    ldsm4t(y, ya + q * 4096);
    if (q < 2) ldsm4t(y + 4, ya + q * 4096 + 2048);
#pragma unroll
    for (int e = 0; e < n; e++) y[e] = hfma2(gt[e], y[e], xw[e & 1][q * 4 + (e >> 1)]);
#pragma unroll
    for (int r = 0; r < 2; r++) {
      __nv_bfloat16* o = o0 + r * 8 * kD;
      if (q < 2) stg4_if(o + q * 32 + t * 8, y[r], y[2 + r], y[4 + r], y[6 + r], true);
      else asm volatile("st.global.v2.u32 [%0], {%1,%2};" ::"l"(o + 64 + t * 4), "r"(y[r]), "r"(y[2 + r]) : "memory");
    }
  }
}

struct Taps { uint4 r0, r1; uint32_t n0, n1, dd; };
__device__ __forceinline__ void load_taps(Taps& k, const Params& p, int ch, int tid) {
  const uint4* kp = (const uint4*)(p.ssmk + (size_t)ch * kS);
  k.r0 = ldg4(kp + tid); k.r1 = ldg4(kp + 128 + tid);
  k.n0 = ldg1(kp + tid + 1); k.n1 = tid < 127 ? ldg1(kp + 129 + tid) : 0u;
  k.dd = __bfloat16_as_ushort(p.ssmD[ch]);
}
__device__ __forceinline__ void convx_copy(const Params& p, uint32_t cv, uint32_t bar, int ch) {
  bulk_g2s(cv, p.scr->kvx + (size_t)ch * 4096, 2048, bar);
  bulk_g2s(cv + XB_PL, p.scr->kvx + (size_t)ch * 4096 + 2048, 2048, bar);
}
__device__ __forceinline__ void convx_issue(const Params& p, uint32_t sb, int h, int ch) {
  if (elect_one()) { mbar_expect(sb + BAR_XL + 8 * h, 4096); convx_copy(p, sb + OFF_CV + (1 - h) * CV_SZ, sb + BAR_XL + 8 * h, ch); }
}
__device__ __forceinline__ void convx_finish(const Params& p, uint32_t sb, int h, int ch, int i, uint32_t par, int lane) {
  const uint32_t cv = sb + OFF_CV + (1 - h) * CV_SZ, rt = sb + BAR_XL - 16 + 8 * h;
  mbar_wait(sb + BAR_XL + 8 * h, i & 1);
  validate<4, XB_PL - 2048>(cv + lane * 32, par, rt, [&]() { convx_copy(p, cv, rt, ch); });
  if (elect_one()) mbar_arrive(sb + BAR_XF + 8 * h);
}
__device__ __forceinline__ void zero_pads(uint32_t cv, int lane) {
  if (lane < 8) sts128(cv + (lane >> 2) * XB_PL + 2048 + (lane & 3) * 16, 0, 0, 0, 0);
  else if (lane < 12) sts128(cv + ((lane & 2) ? CV_KO : CV_KE) + (lane & 1) * 16, 0, 0, 0, 0);
  fence_async_smem();
  __syncwarp();
}
__device__ __forceinline__ int y_row(int c) {
  const int cc = c % 80;
  return c - cc + (cc & 1) + (cc < 64 ? (cc & 32) + ((cc >> 1) & 3) * 8 + ((cc >> 3) & 3) * 2 : 64 + ((cc >> 1) & 1) * 8 + ((cc >> 2) & 3) * 2);
}
struct KvRegs { uint32_t k[11], v[8]; uint4 sh; };
__device__ __forceinline__ void kv_load(KvRegs& q, const __nv_bfloat16* kp, const __nv_bfloat16* vp, const __nv_bfloat16* sp, bool halo) {
#pragma unroll
  for (int i = 0; i < 11; i++) q.k[i] = (i >= 3 || halo) ? ldg1(kp + i * kD) : 0u;
#pragma unroll
  for (int i = 0; i < 8; i++) q.v[i] = ldg1(vp + i * kD);
  q.sh = ldg4(sp);
}
__device__ __forceinline__ void kv_calc(const KvRegs& q, uint32_t* o) {
  const uint32_t w0 = prmt(q.sh.x, q.sh.z, 0x5410), w1 = prmt(q.sh.x, q.sh.z, 0x7632), w2 = prmt(q.sh.y, q.sh.w, 0x5410), w3 = prmt(q.sh.y, q.sh.w, 0x7632);
  uint32_t r[8];
#pragma unroll
  for (int i = 0; i < 8; i++) r[i] = hmul2(hfma2(q.k[i + 3], w0, hfma2(q.k[i + 2], w1, hfma2(q.k[i + 1], w2, hmul2(q.k[i], w3)))), q.v[i]);
#pragma unroll
  for (int i = 0; i < 4; i++) { o[i] = prmt(r[7 - 2 * i], r[6 - 2 * i], 0x5410); o[4 + i] = prmt(r[7 - 2 * i], r[6 - 2 * i], 0x7632); }
}
__device__ __forceinline__ void kv_put(const uint32_t* o, uint32_t oa, uint32_t tm, uint32_t tb) {
  sts128(oa, (o[0] & tm) | tb, o[1], o[2], o[3]);
  sts128(oa + 2048, (o[4] & tm) | tb, o[5], o[6], o[7]);
}

__device__ __forceinline__ void kv_store(const Params& p, uint32_t src, int tb, int unit) {
  asm volatile("cp.async.bulk.tensor.3d.global.shared::cta.bulk_group [%0, {%2, %3, %4}], [%1];" ::"l"(&p.tmKV), "r"(src), "r"((63 - tb) * 16), "r"(unit * 32), "r"(0) : "memory");
}
__device__ __forceinline__ uint32_t kv_stage_addr(int w, int lane) { return ((3 - w) & 1) * 1024 + lane * 32 + ((((3 - w) >> 1) ^ (lane >> 2)) & 1) * 16; }

template <class F>
__device__ __forceinline__ void conv_service(const Params& p, uint32_t sb, int h, int ch, uint32_t par, int lane, F mid) {
#pragma unroll 1
  for (int i = 0; i < 2 + h; i++, ch += 128) {
    bar_sync(NB_SV + h, 160);
    if (i < h) convx_issue(p, sb, h, ch + 128);
    uint8_t* dst = p.scr->y + (size_t)y_row(ch) * 4096;
    bar_sync(NB_SV2(h), 160);
    if (elect_one()) {
      bulk_s2g(dst, sb + OFF_A + 9 * A_SLOT + h * 4096, 4096);
      bulk_commit_wait();
    }
    __syncwarp();
    if (i > h) break;
    if (i == h) { mid(); mbar_wait(sb + BAR_KV2, 0); convx_issue(p, sb, h, ch + 128); }
    convx_finish(p, sb, h, ch + 128, i + 1, par, lane);
  }
}
__device__ __forceinline__ void conv_worker(const Params& p, Taps& k, uint32_t sb, int h, int ch0, int w, int lane, int tid, int rb, int cb TSP) {
  const uint32_t cv = sb + OFF_CV + (1 - h) * CV_SZ, yb0 = sb + OFF_A + 9 * A_SLOT + h * 4096, xbar = sb + BAR_XF + 8 * h;
  const int n = 2 + h, nbar = NB_WG + h;
  const int g = lane >> 2, t = lane & 3, w0 = w & 1, w1 = w >> 1;
  const uint32_t ab = cv + ((g & 1) ? CV_KE : CV_KO) + 32 + 2 * (64 * w0 + 8 * w1 + ((g - 15) & ~1) + 2 * t);
  const uint32_t scA = cv + (w1 ? CV_KO : CV_KE) + 32, scB = scA + 2048;
  const int dl = (t >> 1) ^ 1, col = lane & 7, mi = lane >> 3;
  if (h == 0) mbar_wait(xbar, 0);
  TR(26);
#pragma unroll 1
  for (int i = 0; i < n; i++) {
    if (tid == 0) {
      k.r0.x = (k.r0.x & 0xffff0000u) | (pack2(bf_lo(k.r0.x) + bf_lo(k.dd), 0.f) & 0xffffu);
      sts32(cv + CV_KO + 28, k.r0.x << 16);
    }
    sts128(cv + CV_KE + 32 + tid * 16, k.r0.x, k.r0.y, k.r0.z, k.r0.w);
    sts128(cv + CV_KO + 32 + tid * 16, prmt(k.r0.x, k.r0.y, 0x5432), prmt(k.r0.y, k.r0.z, 0x5432), prmt(k.r0.z, k.r0.w, 0x5432), prmt(k.r0.w, k.n0, 0x5432));
    sts128(cv + CV_KE + 2080 + tid * 16, k.r1.x, k.r1.y, k.r1.z, k.r1.w);
    sts128(cv + CV_KO + 2080 + tid * 16, prmt(k.r1.x, k.r1.y, 0x5432), prmt(k.r1.y, k.r1.z, 0x5432), prmt(k.r1.z, k.r1.w, 0x5432), prmt(k.r1.w, k.n1, 0x5432));
    TR(30 + i * 10);
    if (i + 1 < n) load_taps(k, p, ch0 + (i + 1) * 128, tid);
    bar_sync(nbar, 128);
    TR(31 + i * 10);
    const uint64_t db = mkdesc(cv + (i & 0x1000), XB_PL, 128, 0);
    float d[64];
    uint32_t a[8][16];
    conv_load<7>(a[7], ab);
    conv_load<6>(a[6], ab);
    conv_load<5>(a[5], ab);
    conv_load<4>(a[4], ab);
#pragma unroll
    for (int j = 0; j < 64; j++) d[j] = 0.f;
    if (i == 0) STAMPW(h ? 43 : 8);
    TR(32 + i * 10);
    mbar_wait2(xbar, i & 1, sb + (i + 1 < n ? BAR_ZG : (h ? BAR_HOLD : BAR_HR)), 0);
    if (i == 0) STAMPW(h ? 51 : 7);
    TR(33 + i * 10);
    conv_step<7, -1>(d, a, ab, db); conv_step<6, -1>(d, a, ab, db); conv_step<5, -1>(d, a, ab, db); conv_step<4, 3>(d, a, ab, db);
    conv_step<3, 2>(d, a, ab, db); conv_step<2, 1>(d, a, ab, db); conv_step<1, 0>(d, a, ab, db); conv_step<0, -1>(d, a, ab, db);
    acc_fence<64>(d);
    TR(34 + i * 10);
    bar_arrive(NB_SV + h, 160);
    if (i == 0) mbar_wait(sb + BAR_YT, 0);
    const uint32_t par = lds32<0>(sb + OFF_TAG);
    TR(35 + i * 10);
    float E[16][2];
#pragma unroll
    for (int j = 0; j < 15; j++) { E[j][0] = d[4 * j] + d[4 * j + 6]; E[j][1] = d[4 * j + 1] + d[4 * j + 7]; }
    E[15][0] = d[60]; E[15][1] = d[61];
    if (w0 == 0) {
#pragma unroll
      for (int j = 8; j < 16; j++) sts64f(scA + (j - 8) * 256 + lane * 8, E[j][0], E[j][1]);
    } else {
      const uint32_t a = scB - dl * 256 + (lane ^ 2) * 8;
#pragma unroll
      for (int j = 1; j < 8; j++) sts64f(a + j * 256, E[j][0], E[j][1]);
      sts64f(scB + (dl ? 7 * 256 : 0) + (lane ^ 2) * 8, dl ? E[8][0] : E[0][0], dl ? E[8][1] : E[0][1]);
    }
    TR(36 + i * 10);
    bar_sync(nbar, 128);
    uint32_t pk[8];
    const bool tg = w1 == 0 && g == 0;
    const uint32_t tm = tg ? ~0x10001u : ~0u, tb = tg && (par & 1) ? 0x10001u : 0;
    if (w0 == 0) {
#pragma unroll
      for (int j = 0; j < 8; j++) { const float2 v = lds64f(scB + j * 256 + lane * 8); pk[j] = (pack2(E[j][0] + v.x, E[j][1] + v.y) & tm) | tb; }
      const uint32_t ya = yb0 + 32 * (127 - (8 * mi + col)) + 16 * w1;
      stsm4t(ya, pk[0], pk[1], pk[2], pk[3]);
      stsm4t(ya - 1024, pk[4], pk[5], pk[6], pk[7]);
    } else {
      const uint32_t a0 = scA - dl * 256 + (lane ^ 2) * 8;
#pragma unroll
      for (int j = 9; j < 16; j++) { const float2 v = lds64f(a0 + (j - 8) * 256); pk[j - 8] = (pack2(E[j][0] + v.x, E[j][1] + v.y) & tm) | tb; }
      const float2 v = lds64f(scA + (dl ? 7 * 256 : 0) + (lane ^ 2) * 8);
      pk[0] = (pack2((dl ? 0.f : E[8][0]) + v.x, (dl ? 0.f : E[8][1]) + v.y) & tm) | tb;
      const uint32_t yb = yb0 + 32 * (127 - (92 + 8 * mi + col)) + 16 * w1;
      const uint32_t ya = (mi == 0 && col < 4) ? yb0 + 32 * (3 - col) + 16 * w1 : yb + 1024;
      stsm4t(ya, pk[0], pk[1], pk[2], pk[3]);
      stsm4t(yb, pk[4], pk[5], pk[6], pk[7]);
    }
    TR(37 + i * 10);
    fence_async_smem();
    bar_arrive(NB_SV2(h), 160);
    if (i + 1 < n) bar_sync(nbar, 128);
    TR(38 + i * 10);
    STAMPW((h ? 40 : 5) + i);
    if (i == 0 && h == 0) {
      const int tn = tid_now();
      {
        const int ln = tn & 31, t0 = (rb * 2 + (cb & 1)) * 32 + w * 8, c0 = (cb >> 1) * 320 + 192 + ln * 2;
        KvRegs q0, q1;
        uint32_t o[8];
        kv_load(q0, p.k + (size_t)(t0 - 3) * kD + c0, p.v + (size_t)t0 * kD + c0, p.shift + c0 * 4, t0 > 0);
        kv_load(q1, p.k + (size_t)(t0 - 3) * kD + c0 + 64, p.v + (size_t)t0 * kD + c0 + 64, p.shift + c0 * 4 + 256, t0 > 0);
        const uint32_t oa = sb + OFF_A + 8 * A_SLOT + kv_stage_addr(w, ln), km = w >= 2 ? ~1u : ~0u, kb = w >= 2 ? lds32<0>(sb + OFF_TAG) & 1 : 0;
        kv_calc(q0, o);
        kv_put(o, oa, km, kb);
        kv_calc(q1, o);
        kv_put(o, oa + 4096, km, kb);
        fence_async_smem();
        bar_arrive(NB_KL, 160);
      }
      STAMPW(56);
      const int u = (tn >> 3) % 5, kg = rb * 3 + (tn < 120 ? (tn >> 3) / 5 : 0), c = u < 4 ? (u >> 1) * 10 + (u & 1) * 4 : 8, o2 = u < 4 ? 2 : 10;
      const uint4* wp = (const uint4*)(p.wout + (size_t)(kg * 8 + (tn & 7)) * kD + cb * 160) + c;
      const uint4 w0 = ldg4(wp), w1 = ldg4(wp + 1), w2 = ldg4(wp + o2), w3 = ldg4(wp + o2 + 1);
      uint8_t* dst = p.scr->wo + (size_t)cb * (12 * W_SLOT) + kg * 2560 + c * 128 + (tn & 7) * 16;
      const bool f = u < 4, on = tn < 120;
      stg4_if(dst, w0.x, f ? w1.x : w0.z, f ? w2.x : w1.x, f ? w3.x : w1.z, on);
      stg4_if(dst + 128, w0.y, f ? w1.y : w0.w, f ? w2.y : w1.y, f ? w3.y : w1.w, on);
      stg4_if(dst + o2 * 128, f ? w0.z : w2.x, f ? w1.z : w2.z, f ? w2.z : w3.x, w3.z, on);
      stg4_if(dst + o2 * 128 + 128, f ? w0.w : w2.y, f ? w1.w : w2.w, f ? w2.w : w3.y, w3.w, on);
      bar_arrive(NB_WO, 160);
    }
  }
}

struct U6 { uint64_t a, b, c; };
__device__ __forceinline__ uint64_t ld_ll2(const void* p) { uint64_t a; asm volatile("ld.relaxed.gpu.global.u64 %0, [%1];" : "=l"(a) : "l"(p) : "memory"); return a; }
__device__ __forceinline__ void gather_colsum(const Params& p, uint32_t sb, int part, int cb, uint32_t tag8, int lane) {
  const uint32_t* src = p.scr->colsum + (uint32_t)((part ? 0 : 768) + cb * 192 + lane * 2);
  const uint64_t t2 = tag8 * 0x100000001ull;
  const U6 v = poll<false>([&]() { return U6{ld_ll2(src), ld_ll2(src + 64), ld_ll2(src + 128)}; },
                                    [&](const U6& u) { return (((u.a ^ t2) | (u.b ^ t2) | (u.c ^ t2)) & 0xff000000ffull) == 0; });
  const uint32_t dst = sb + OFF_CS + (part ? 0 : 768) + lane * 8;
  asm volatile("st.shared.u64 [%0], %1;\nst.shared.u64 [%0+256], %2;\nst.shared.u64 [%0+512], %3;" ::"r"(dst), "l"(v.a), "l"(v.b), "l"(v.c) : "memory");
  __syncwarp();
  mbar_arrive_if(sb + BAR_ST + 8 * part, lane == 0);
}

__device__ __forceinline__ void helper_cta(const Params& p, uint32_t sb, int cb, int warp, int lane TSP) {
  constexpr int NS = 9, ONES = NS * B_SLOT, BF = ONES + 256, BE = BF + 8 * NS;
  if (warp < NS && elect_one()) {
    mbar_init(sb + BF + 8 * warp, 1); mbar_init(sb + BE + 8 * warp, 1);
    fence_async_smem();
    if (warp == 0) { mbar_expect(sb + BF, B_SLOT); tma3d(sb, &p.tmW, 0, 0, 12 + cb * 3, sb + BF); }
  }
  if (warp == 15) { sts32(sb + ONES + lane * 4, 0x3f803f80u); sts32(sb + ONES + 128 + lane * 4, 0x3f803f80u); fence_async_smem(); }
  __syncthreads();
  if (warp == 4) {
    int s = 1, ph = 1;
    uint32_t tp = clock() + HP0;
#pragma unroll 1
    for (int it = 1; it < 20; it++) {
      if (it >= 10) pace(tp, HPD);
      mbar_wait(sb + BE + 8 * s, ph);
      if (elect_one()) { mbar_expect(sb + BF + 8 * s, B_SLOT); tma3d(sb + s * B_SLOT, &p.tmW, 0, (it < 10 ? it : it - 10) * 64, (it < 10 ? 12 : 0) + cb * 3, sb + BF + 8 * s); }
      if (++s == NS) { s = 0; ph ^= 1; }
    }
  } else if (warp < 4) {
    const uint32_t tag = load_epoch(p, 128 + cb, lane) + 1;
    const uint64_t db = mkdesc(sb + ONES, 128, 128, 0);
    uint32_t* dst = p.scr->colsum + cb * 192 + warp * 16 + (lane >> 2);
    if ((lane & 3) == 0) {
#pragma unroll 1
      for (int j = 0; j < 12; j++) st_relaxed(dst + (j < 6 ? 768 : 0) + ((j % 6) >> 1) * 64 + (j & 1) * 8, 0);
    }
    int s = 0, ph = 0;
#pragma unroll 1
    for (int part = 0; part < 2; part++) {
      float d[12];
#pragma unroll
      for (int i = 0; i < 12; i++) d[i] = 0.f;
#pragma unroll 1
      for (int it = 0; it < 10; it++) {
        mbar_wait(sb + BF + 8 * s, ph);
        const uint64_t da = mkdesc(sb + s * B_SLOT, 8192, 1024, 1);
        WG_FENCE();
#pragma unroll
        for (int j = 0; j < 12; j++) wgmma_colsum(d + 4 * (j % 3), da + (j % 3) * 512 + (j / 3) * 128, db);
        WG_COMMIT();
        WG_WAIT(1);
        mbar_arrive_if(sb + BE + 8 * (s == 0 ? NS - 1 : s - 1), threadIdx.x == 0 && (it | part) != 0);
        if (++s == NS) { s = 0; ph ^= 1; }
      }
      WG_WAIT(0);
      acc_fence<12>(d);
      if ((lane & 3) == 0) {
#pragma unroll
        for (int j = 0; j < 6; j++) st_relaxed(dst + (part ? 0 : 768) + (j >> 1) * 64 + (j & 1) * 8, tagged(d[2 * j], tag8(tag)));
      }
      STAMPW(1 + part);
    }
    if (threadIdx.x == 0) *(volatile uint32_t*)&p.scr->epoch[128 + cb] = tag;
  }
}

__global__ void __launch_bounds__(512, 1) fused_kernel(const __grid_constant__ Params p) {
  extern __shared__ __align__(1024) uint8_t smem[];
  const int warp = __shfl_sync(0xffffffff, (int)(threadIdx.x >> 5), 0);
  const int lane = threadIdx.x & 31;
  const uint32_t sb = __shfl_sync(0xffffffff, (uint32_t)__cvta_generic_to_shared(smem), 0);
  const uint32_t tstart = clock();
  int b = blockIdx.x;
  if (p.by_smid) asm volatile("mov.u32 %0, %%smid;" : "=r"(b));
  b = __shfl_sync(0xffffffff, b, 0);
  const int job = p.job[b], lin = job & 255, cb = job >> 8 & 3, rb = job >> 10;
  if (elect_one()) {
    mbar_init(sb + OFF_BAR + 8 * warp, 1);
    if (lin < 128) {
      if (warp < NPRE) { fence_async_smem(); mbar_expect(sb + BAR_AF + 8 * warp, A_SLOT); tma2d(sb + OFF_A + warp * A_SLOT, &p.tmX, warp * 64, rb * 64, sb + BAR_AF + 8 * warp); }
      if (warp >= 10 && warp < 10 + NPRE) { fence_async_smem(); mbar_expect(sb + OFF_BAR + 8 * warp, B_SLOT); tma3d(sb + OFF_B + (warp - 10) * B_SLOT, &p.tmW, 0, (warp - 10) * 64, 12 + cb * 3, sb + OFF_BAR + 8 * warp); }
    }
    if (warp >= 2 && warp < 5) asm volatile("prefetch.tensormap [%0];" ::"l"(&p.tmX + warp) : "memory");
    mbar_init(sb + OFF_BAR + 128 + 8 * warp, 1);
    if (warp != 3) mbar_init(sb + OFF_BAR + 256 + 8 * warp, (0x2224444444441111ull >> (4 * warp)) & 15);
    mbar_init(sb + OFF_BAR + 384 + 8 * warp, 2);
    if (warp < 2) mbar_init(sb + BAR_XL + 8 * warp, 1);
    asm volatile("fence.mbarrier_init.release.cluster;" ::: "memory");
  }
  if (lin >= 128) { helper_cta(p, sb, cb, warp, lane TSA); return; }
  const int chb = (cb >> 1) * 320 + rb * 2 + (cb & 1);
  if (sb & 1023) die();
  __syncthreads();

  if (warp >= 12) {
    asm volatile("setmaxnreg.dec.sync.aligned.u32 32;");
    const uint8_t* z2s = p.scr->z2 + (size_t)cb * 32 * B_SLOT;
    const char* wq = (const char*)p.wsp + (rb * 64 + cb * 16 + (lane >> 1)) * (kS * 2) + (lane & 1) * 128;
    if (warp == 12) {
      int s = NPRE, ph = 1;
#pragma unroll 1
      for (int it = NPRE; it < 20; it++) {
        if (it >= 5) mbar_wait<true>(sb + BAR_BE + 8 * s, ph);
        if (it < 5 && elect_one()) { mbar_expect(sb + BAR_AF + 8 * it, A_SLOT); tma2d(sb + OFF_A + it * A_SLOT, &p.tmX, it * 64, rb * 64, sb + BAR_AF + 8 * it); }
        if (elect_one()) {
          mbar_expect(sb + BAR_BF + 8 * s, B_SLOT);
          tma3d(sb + OFF_B + s * B_SLOT, &p.tmW, 0, (it < 10 ? it : it - 10) * 64, (it < 10 ? 12 : 0) + cb * 3, sb + BAR_BF + 8 * s);
        }
        if (it == 4) {
#pragma unroll 1
          for (int i = 5; i < 10; i++)
            if (elect_one()) { mbar_expect(sb + BAR_AF + 8 * i, A_SLOT); tma2d(sb + OFF_A + i * A_SLOT, &p.tmX, i * 64, rb * 64, sb + BAR_AF + 8 * i); }
          bar_arrive(NB_KF, 160);
        }
        STAMP2(32 + it);
        if (++s == 5) { s = 0; ph ^= 1; }
      }
      const uint32_t ztarget = (load_epoch(p, lin, lane) + 1) * 128;
#pragma unroll 1
      for (int i = 0; i < LEAD; i++) {
        mbar_wait<true>(sb + BAR_AE + 8 * (3 + i), 0);
        if (elect_one()) { mbar_expect(sb + BAR_AF + 8 * (3 + i), A_SLOT); tma2d(sb + OFF_A + (3 + i) * A_SLOT, &p.tmWsp, i * 64, rb * 64, sb + BAR_AF + 8 * (3 + i)); }
      }
      mbar_wait<true>(sb + BAR_ZP, 0);
      poll_counter<true>(p.scr->cnt + CNT_Z, ztarget);
      STAMP(24);
#pragma unroll 1
      for (int it = 0; it < 32; it++) {
        mbar_wait<true>(sb + BAR_BE + 8 * s, ph);
        if (elect_one()) {
          mbar_expect(sb + BAR_BF + 8 * s, B_SLOT);
          bulk_g2s(sb + OFF_B + s * B_SLOT, z2s + it * B_SLOT, B_SLOT, sb + BAR_BF + 8 * s);
        }
        if (it == 0) STAMP(22);
        const int ia = it + LEAD - 1, sa = (ia + 3) & 7;
        if (it >= 1 && ia < 32) {
          mbar_wait<true>(sb + BAR_AE + 8 * sa, (ia >> 3) & 1);
          if (elect_one()) { mbar_expect(sb + BAR_AF + 8 * sa, A_SLOT); tma2d(sb + OFF_A + sa * A_SLOT, &p.tmWsp, ia * 64, rb * 64, sb + BAR_AF + 8 * sa); }
        }
        STAMP2(52 + it);
        if (++s == 5) { s = 0; ph ^= 1; }
      }
      mbar_wait<true>(sb + BAR_WO, 0);
      acquire_fence();
#pragma unroll 1
      for (int it = 0; it < 12; it++) {
        if (it < 6) mbar_wait<true>(sb + BAR_BE + 8 * ((0x110443 >> (4 * it)) & 7), it < 3 ? 1 : 0);
        else mbar_wait<true>(sb + BAR_WE + 8 * (it - 6), 0);
        mbar_arrive_if(sb + BAR_HOLD, it == 0 && lane == 0);
        if (elect_one()) {
          mbar_expect(sb + w_full(it), W_SLOT);
          bulk_g2s(sb + w_pos(it), p.scr->wo + (size_t)(cb * 12 + g3_block(cb, it)) * W_SLOT, W_SLOT, sb + w_full(it));
        }
        STAMP2(84 + it);
      }
      mbar_wait<true>(sb + BAR_WE, 1);
    } else if (warp == 13) {
      const uint32_t tag = load_epoch(p, lin, lane) + 1;
      if (elect_one()) reset_sector(&p.scr->hflag[rb * 32 + cb * 8]);
      if (lane == 0) sts32(sb + OFF_TAG, tag8(tag));
      mbar_wait(sb + BAR_AF + 72, 0);
      { uint32_t tp = clock(); pace(tp, CSD); }
      gather_colsum(p, sb, 0, cb, tag8(tag), lane);
      STAMP(27);
      bar_sync(NB_Z, 160);
      if (elect_one()) {
        mbar_arrive(sb + BAR_ZG);
        bulk_s2g((void*)(z2s + rb * B_SLOT), sb + OFF_A, B_SLOT);
        bulk_commit_wait();
        mbar_arrive(sb + BAR_ZP);
        STAMPE(58);
        red_release(p.scr->cnt + CNT_Z);
      }
      __syncwarp();
      STAMP(28);
      {
        uint32_t tp = clock();
#pragma unroll 1
        for (int i = 1; i < 16; i++) {
          pace(tp, PF_D);
          prefetch_l2(wq + i * 256);
          if (i == LKI) bar_sync(NB_KL, 160);
          if ((i == LKI || i == LKI + 1) && elect_one()) {
            kv_store(p, sb + OFF_A + 8 * A_SLOT + (i - LKI) * 4096, rb * 2 + (cb & 1), (cb >> 1) * 5 + 3 + i - LKI);
            bulk_commit_wait();
            if (i > LKI) red_relaxed(p.scr->cnt + CNT_KV + 2 + (cb >> 1));
          }
          __syncwarp();
          if (i == LKI + 1) STAMP(59);
        }
      }
      if (!EARLY) poll_counter(p.scr->cnt + CNT_KV + 2 + (cb >> 1), tag * 64);
      if (elect_one()) mbar_arrive(sb + BAR_KV2);
      STAMP(34);
      const uint8_t* hs = p.scr->h + (size_t)rb * 12 * A_SLOT;
#pragma unroll 1
      for (int i = 0; i < 3; i++) {
        mbar_wait(sb + BAR_HR - 16 + 8 * i, 0);
        if (elect_one()) bulk_s2g((void*)(hs + (cb * 3 + i) * A_SLOT), sb + OFF_A + i * A_SLOT, A_SLOT);
      }
      if (elect_one()) {
        st_relaxed(&p.scr->hflag[rb * 32 + cb * 8], tag);
        bulk_commit_wait();
      }
      __syncwarp();
      STAMP(20);
      if (!EARLY) poll_flags4(p.scr->hflag + rb * 32, tag, lane);
      { uint32_t tp = clock(); pace<false>(tp, HD); }
      STAMP(37);
#pragma unroll 1
      for (int it = 3; it < 12; it++) {
        const uint32_t land = sb + BAR_AF + 8 * (it < 9 ? it : it - 9);
        if (it == 9) mbar_wait2(sb + BAR_PART, 0, sb + BAR_B2, 0);
        if (elect_one()) { mbar_expect(land, A_SLOT); bulk_g2s(sb + h_pos(it), hs + g3_block(cb, it) * A_SLOT, A_SLOT, land); }
      }
      STAMP(21);
    } else if (warp == 14) {
      const uint32_t tag = load_epoch(p, lin, lane) + 1;
      const int tb = rb * 2 + (cb & 1), u0 = (cb >> 1) * 5;
      const uint32_t ks = sb + OFF_CV + CV_SZ, par = __shfl_sync(0xffffffff, tag, 0);
      {
        uint32_t tp = tstart;
        pace(tp, TP_T);
        const char* q = (const char*)p.ssmk + chb * 4096 + lane * 128;
        prefetch_l2(q); prefetch_l2(q + 64 * 4096);
      }
      mbar_wait2(sb + BAR_XS, 0, sb + BAR_ST, 0);
      bar_sync(NB_KU, 160);
      if (elect_one()) { kv_store(p, ks, tb, u0); kv_store(p, ks + 4096, tb, u0 + 1); bulk_commit_wait(); red_relaxed(p.scr->cnt + CNT_KV + (cb >> 1)); }
      __syncwarp();
      STAMP(35);
      bar_sync(NB_KU2, 160);
      if (elect_one()) { kv_store(p, ks + 8192, tb, u0 + 2); bulk_commit_wait(); }
      __syncwarp();
      zero_pads(ks, lane);
      bar_arrive(NB_G1D, 64);
      STAMP(30);
      {
        uint32_t tp = clock();
        const size_t o = (size_t)(tb * 32 + lane) * (kD * 2) + (u0 + 3) * 128;
        const char* r = (const char*)p.wout + (rb * 24 + min(lane, 23)) * (kD * 2) + cb * 320;
        const char* q = (const char*)p.ssmk + (chb + 128) * 4096 + lane * 128;
#pragma unroll 1
        for (int i = 0; i < 10; i++) {
          pace(tp, PF2_D);
          prefetch_l2(i < 3 ? q + i * 64 * 4096 : (i < 7 ? (const char*)((i & 1) ? p.k : p.v) + o + ((i - 3) >> 1) * 128 : r + (i - 7) * 128));
        }
      }
      conv_service(p, sb, 0, chb + 64, par, lane, NoHook());
      bar_sync(NB_CD, 64);
      STAMP(47);
      if (!EARLY) mbar_wait(sb + BAR_WE + 40, 0);
      { uint32_t tp = clock(); pace<false>(tp, YD); }
      if (elect_one()) {
        mbar_expect(sb + BAR_YT, 20480);
#pragma unroll 1
        for (int i = 0; i < 4; i++) tma2d(sb + OFF_CV + i * 5120, &p.tmY, rb * 64, cb * 160 + i * 40, sb + BAR_YT);
      }
      if (lane == 0) *(volatile uint32_t*)&p.scr->epoch[lin] = tag;
      STAMP(23);
    } else {
      const uint32_t tag = load_epoch(p, lin, lane) + 1;
      mbar_wait(sb + BAR_AF + 72, 0);
      { uint32_t tp = clock(); pace(tp, XSD); }
      {
        const uint32_t t8 = tag8(tag);
        const uint4 u = poll<false>([&]() { return ld_ll4(&p.scr->xstat[rb * 64 + lane * 2]); },
                                                [&](const uint4& v) { return (((v.x ^ t8) | (v.y ^ t8) | (v.z ^ t8) | (v.w ^ t8)) & 255u) == 0; });
        sts128(sb + OFF_XS + lane * 16, u.x, u.y, u.z, u.w);
      }
      __syncwarp();
      if (lane == 0) mbar_arrive(sb + BAR_XS);
      STAMP(25);
      const uint32_t par = __shfl_sync(0xffffffff, tag, 0);
      bar_sync(NB_G1D, 64);
      if (!EARLY) poll_counter(p.scr->cnt + CNT_KV + (cb >> 1), tag * 64);
      convx_issue(p, sb, 1, chb);
      convx_issue(p, sb, 0, chb + 64);
#pragma unroll 1
      for (int h = 1; h >= 0; h--) convx_finish(p, sb, h, chb + 64 - 64 * h, 0, par, lane);
      STAMP(48);
      gather_colsum(p, sb, 1, cb, tag8(tag), lane);
      STAMP(38);
      conv_service(p, sb, 1, chb, par, lane, [&]() {
        bar_sync(NB_WO, 160);
        if (elect_one()) red_release(p.scr->cnt + CNT_WO + cb);
        STAMP(49);
        poll_counter(p.scr->cnt + CNT_WO + cb, tag * 32);
        if (elect_one()) mbar_arrive(sb + BAR_WO);
        STAMP(46);
      });
      bar_arrive(NB_CD, 64);
    }
  } else if (warp >= 8) {
    const int w = warp & 3;
    {
      const int tid = tid_now();
      uint2* xs = &p.scr->xstat[rb * 64 + cb * 16 + (tid >> 3)];
      if ((tid & 7) == 0) st_ll2(xs, 0, 0);
      const uint32_t epoch = load_epoch(p, lin, lane);
      float sa[4] = {0.f, 0.f, 0.f, 0.f}, qa[4] = {0.f, 0.f, 0.f, 0.f};
#pragma unroll 1
      for (int i = 0; i < 10; i++) {
        mbar_wait(sb + BAR_AF + 8 * i, 0);
        const uint4 x4 = lds128(sb + OFF_A + i * A_SLOT + cb * 2048 + tid * 16);
        const uint32_t u[4] = {x4.x, x4.y, x4.z, x4.w};
#pragma unroll
        for (int e = 0; e < 4; e++) { const float a = bf_lo(u[e]), c = bf_hi(u[e]); sa[e] += a + c; qa[e] = fmaf(a, a, fmaf(c, c, qa[e])); }
      }
      float s = (sa[0] + sa[1]) + (sa[2] + sa[3]), q = (qa[0] + qa[1]) + (qa[2] + qa[3]);
#pragma unroll
      for (int o = 1; o <= 4; o <<= 1) { s += __shfl_xor_sync(0xffffffff, s, o); q += __shfl_xor_sync(0xffffffff, q, o); }
      const float m = s * (1.f / kD);
      const float r = rsqrtf(fmaxf(fmaf(-m, m, q * (1.f / kD)), 0.f) + 1e-5f);
      if ((tid & 7) == 0) st_ll2(xs, tagged(m, tag8(epoch + 1)), tagged(r, tag8(epoch + 1)));
      STAMPW(12); TR(70);
      fence_async_smem();
    }
    asm volatile("setmaxnreg.inc.sync.aligned.u32 160;");
    const unsigned short* bp = (const unsigned short*)p.bsp + rb * 64 + w * 16 + (lane >> 2);
    const uint32_t bias = bp[0] | ((uint32_t)bp[8] << 16);
    float d[96];
    uint32_t z[48];
    {
#pragma unroll
      for (int i = 0; i < 96; i++) d[i] = 0.f;
      bar_sync(NB_G1, 256);
      TR(71);
      gemm192<3>(d, sb, tid_now() == 0 TSA);
      mbar_arrive_if(sb + BAR_YT, tid_now() == 0);
      STAMPW(14); TR(74);
      mbar_wait2(sb + BAR_XS, 0, sb + BAR_ST + 8, 0);
      const uint32_t xa1 = sb + OFF_XS + (w * 16 + (lane >> 2)) * 8;
      gelu_tile<false>(d, z, nullptr, sb + OFF_CS + (lane & 3) * 8, lds64f(xa1), lds64f(xa1 + 64), sb + BAR_XS);
    }
#pragma unroll
    for (int j = 0; j < 96; j++) d[j] = (j & 2) ? bf_hi(bias) : bf_lo(bias);
    STAMPW(15); TR(76);
    gemm192<1>(d, sb, tid_now() == 0 TSA);
    STAMPW(16); TR(77);
    {
      const int l2 = tid_now() & 31;
      const uint32_t ha = swz_base(sb + OFF_A, w, l2);
      const bool tg = (l2 & 3) == (l2 >> 3);
      const uint32_t tm = tg ? ~1u : ~0u, tb = tg ? lds32<0>(sb + OFF_TAG) & 1 : 0;
#pragma unroll
      for (int j = 0; j < 24; j += 2) {
#pragma unroll
        for (int e = 0; e < 4; e++) z[2 * j + e] = hmul2(z[2 * j + e], pack2(d[4 * j + 2 * e], d[4 * j + 2 * e + 1]));
        stsm4((ha ^ ((j & 7) * 16)) + (j >> 3) * A_SLOT, (z[2 * j] & tm) | tb, (z[2 * j + 1] & tm) | tb, z[2 * j + 2], z[2 * j + 3]);
        if ((j & 7) == 6) {
          fence_async_smem();
          __syncwarp();
          mbar_arrive_if(sb + BAR_HR - 16 + (j >> 3) * 8, l2 == 0);
        }
      }
    }
    STAMPW(17); TR(78);
    const int t3 = tid_now();
    {
      acc_fence<40>(d);
      mbar_wait2(sb + BAR_HR, 0, sb + BAR_WF, 0);
      WG_FENCE();
      gemm3<0, 3, true>(d, sb, mkdesc(sb, 16, 1024, 1), mkdesc(sb, 2560, 128, 0), t3 == 0, 0 TSA);
      WG_WAIT(0);
      acc_fence<40>(d);
      TR(79);
#pragma unroll
      for (int j = 0; j < 5; j++)
        sts128(part_addr(sb, j, t3), pack2(d[8 * j], d[8 * j + 1]), pack2(d[8 * j + 2], d[8 * j + 3]), pack2(d[8 * j + 4], d[8 * j + 5]), pack2(d[8 * j + 6], d[8 * j + 7]));
      bar_sync(NB_C, 128);
      mbar_arrive_if(sb + BAR_PART, t3 == 0);
      STAMPW(45); TR(80);
    }
    {
      const uint32_t par = __shfl_sync(0xffffffff, lds32<0>(sb + OFF_TAG), 0), a = sb + w * 2048 + val_off(t3 & 31);
      const uint8_t* hs = p.scr->h + (size_t)rb * 12 * A_SLOT + w * 2048;
      const uint32_t rt = sb + OFF_RT + 8 * w;
#pragma unroll 1
      for (int it = 3; it < 12; it++) {
        mbar_wait(sb + BAR_AF + 8 * (it < 9 ? it : it - 9), 1);
        validate<2>(a + h_pos(it), par, rt, [&]() { bulk_g2s(sb + h_pos(it) + w * 2048, hs + g3_block(cb, it) * A_SLOT, 2048, rt); });
        if (elect_one()) mbar_arrive(sb + BAR_HV + 8 * (it - 3));
        if (it == 3) STAMPW(26);
      }
      {
        const int l = t3 & 31;
        mbar_wait(sb + BAR_YT, 1);
        validate<5>(sb + OFF_CV + w * 5120 + (l >> 2) * 128 + ((2 * (l & 3)) ^ (l >> 2)) * 16, par, rt, [&]() { tma2d(sb + OFF_CV + w * 5120, &p.tmY, rb * 64, cb * 160 + w * 40, rt); });
        bar_sync(NB_C, 128);
        mbar_arrive_if(sb + BAR_PART, t3 == 0);
        STAMPW(57);
      }
    }
  } else {
    const int h = warp >> 2, w = warp & 3;
    Taps k;
    asm volatile("setmaxnreg.inc.sync.aligned.u32 160;");
    if (h == 0) {
      uint4* zs = &p.scr->zstat[rb * 128 + w * 8 + (lane >> 2)];
      if ((lane & 3) == 0) st_ll4(zs + cb * 32, 0, 0, 0, 0);
      float d[96];
      uint32_t z[48];
#pragma unroll
      for (int i = 0; i < 96; i++) d[i] = 0.f;
      gemm192<0>(d, sb, tid_now() == 0 TSA, [&]() { bar_arrive(NB_G1, 256); });
      STAMPW(1); TR(0);
      const int tid = tid_now(), lane = tid & 31, g = lane >> 2, t = lane & 3;
      mbar_wait2(sb + BAR_XS, 0, sb + BAR_ST, 0);
      STAMPW(52); TR(1);
      const uint32_t xa1 = sb + OFF_XS + (w * 16 + g) * 8;
      const uint32_t tag = lds32<0>(sb + OFF_TAG);
      const float2 s0 = lds64f(xa1), s1 = lds64f(xa1 + 64);
      float st[4];
      gelu_tile<true>(d, z, st, sb + OFF_CS + 768 + t * 8, s0, s1, 0);
      TR(2);
      float2 sq = quad_sum(st, t);
      if (t < 2) st_ll2((uint2*)(zs + cb * 32) + t, tagged(sq.x, tag), __float_as_uint(sq.y));
      STAMPW(2); TR(3);
      { uint32_t tp = clock(); pace<false>(tp, ZW); }
      const uint4 u = poll<false>([&]() { return ld_ll4(zs + t * 32); }, [&](const uint4& v) { return (((v.x ^ tag) | (v.z ^ tag)) & 255u) == 0; });
      STAMPW(3); TR(10);
      st[0] = __uint_as_float(u.x); st[1] = __uint_as_float(u.y); st[2] = __uint_as_float(u.z); st[3] = __uint_as_float(u.w);
      sq = quad_sum(st, t);
      const float ca = 0.5f * ((t & 1) ? s1.y : s0.y), ma = sq.x * (1.f / 768.f);
      const float ra = ca * rsqrtf(fmaf(fmaxf(fmaf(-ma, ma, sq.y * (1.f / 768.f)), 0.f), ca * ca, 1e-5f));
      const uint32_t r2 = pack2(ra, ra);
      const float na = -ma * bf_lo(r2);
      const uint32_t n2 = pack2(na, na), r2o = __shfl_xor_sync(0xffffffff, r2, 1), n2o = __shfl_xor_sync(0xffffffff, n2, 1);
      const uint32_t fr[2] = {(t & 1) ? r2o : r2, (t & 1) ? r2 : r2o}, fn[2] = {(t & 1) ? n2o : n2, (t & 1) ? n2 : n2o};
      const uint32_t za = swz_base(sb + OFF_A, w, lane);
      TR(11);
      mbar_wait(sb + BAR_AE + 16, 0);
      TR(12);
#pragma unroll
      for (int j = 0; j < 24; j += 2)
        stsm4((za ^ ((j & 7) * 16)) + (j >> 3) * A_SLOT, hfma2(z[2 * j], fr[0], fn[0]), hfma2(z[2 * j + 1], fr[1], fn[1]), hfma2(z[2 * j + 2], fr[0], fn[0]), hfma2(z[2 * j + 3], fr[1], fn[1]));
      TR(14);
      fence_async_smem();
      bar_arrive(NB_Z, 160);
      STAMPW(4); TR(15);
      load_taps(k, p, chb + 64, tid);
    } else {
      if (w == 0) zero_pads(sb + OFF_CV, lane);
      const uint32_t epoch = load_epoch(p, lin, lane);
      const int t0 = (rb * 2 + (cb & 1)) * 32 + w * 8, c0 = (cb >> 1) * 320 + lane * 2;
      const __nv_bfloat16* kp = p.k + (size_t)(t0 - 3) * kD + c0;
      const __nv_bfloat16* vp = p.v + (size_t)t0 * kD + c0;
      const __nv_bfloat16* sp = p.shift + c0 * 4;
      const uint32_t oa = sb + OFF_CV + CV_SZ + kv_stage_addr(w, lane);
      bar_sync(NB_KF, 160);
      uint32_t tp = tstart;
      pace(tp, KV_T0);
      KvRegs n0, n1;
      uint32_t o[8];
      kv_load(n0, kp, vp, sp, t0 > 0);
      kv_load(n1, kp + 64, vp + 64, sp + 256, t0 > 0);
      const uint32_t tm = w >= 2 ? ~1u : ~0u, tb = w >= 2 ? (epoch + 1) & 1 : 0;
      kv_calc(n0, o);
      kv_put(o, oa, tm, tb);
      kv_calc(n1, o);
      kv_put(o, oa + 4096, tm, tb);
      fence_async_smem();
      bar_arrive(NB_KU, 160);
      TR(0);
      pace(tp, KV2T);
      kv_load(n0, kp + 128, vp + 128, sp + 512, t0 > 0);
      load_taps(k, p, chb, tid_now());
      kv_calc(n0, o);
      kv_put(o, oa + 8192, tm, tb);
      fence_async_smem();
      bar_arrive(NB_KU2, 160);
      STAMPW(13); TR(1);
    }
    uint32_t xw[2][10];
    {
      const int tid = tid_now();
      final_load_x(xw, p.x + (rb * 64 + w * 16 + ((tid & 31) >> 2)) * kD + cb * 160 + h * 80, tid & 3);
      conv_worker(p, k, sb, h, chb + 64 - 64 * h, w, tid & 31, tid, rb, cb TSA);
    }
    float d[40];
    const int t3 = tid_now();
    const uint32_t o0 = (rb * 64 + w * 16 + ((t3 & 31) >> 2)) * kD + cb * 160 + h * 80;
    float cf[2];
    uint32_t rn[4];
    const uint32_t xs_addr = sb + OFF_XS + (w * 16 + ((t3 & 31) >> 2)) * 8;
    TR(60);
    {
      const float2 s0 = lds64f(xs_addr), s1 = lds64f(xs_addr + 64);
      cf[0] = 0.25f * s0.y; cf[1] = 0.25f * s1.y;
      rn[0] = pack2(s0.y, s0.y); rn[1] = pack2(s1.y, s1.y);
      rn[2] = pack2(-s0.x * bf_lo(rn[0]), -s0.x * bf_lo(rn[0])); rn[3] = pack2(-s1.x * bf_lo(rn[1]), -s1.x * bf_lo(rn[1]));
    }
    const uint64_t da3 = mkdesc(sb, 16, 1024, 1), db3 = mkdesc(sb + h * 1280, 2560, 128, 0);
    if (h == 0) {
      mbar_wait(sb + BAR_PART, 0);
      TR(61);
#pragma unroll
      for (int j = 0; j < 5; j++) {
        const uint4 v = lds128(part_addr(sb, j, t3));
        d[8 * j] = bf_lo(v.x); d[8 * j + 1] = bf_hi(v.x); d[8 * j + 2] = bf_lo(v.y); d[8 * j + 3] = bf_hi(v.y);
        d[8 * j + 4] = bf_lo(v.z); d[8 * j + 5] = bf_hi(v.z); d[8 * j + 6] = bf_lo(v.w); d[8 * j + 7] = bf_hi(v.w);
      }
      fence_async_smem();
      bar_sync(NB_WG, 128);
      mbar_arrive_if(sb + BAR_WE + 16, t3 == 0);
      acc_fence<40>(d);
      mbar_wait2(sb + BAR_HV, 0, sb + w_full(3), 0);
    } else {
#pragma unroll
      for (int j = 0; j < 40; j++) d[j] = 0.f;
      acc_fence<40>(d);
      mbar_wait2(sb + BAR_HR, 0, sb + BAR_WF, 0);
      WG_FENCE();
      gemm3<0, 3, false>(d, sb, da3, db3, t3 == 0, 0 TSA);
    }
    TR(62);
    if (h == 0) STAMPW(36);
    WG_FENCE();
    gemm3<3, 12, false>(d, sb, da3, db3, t3 == 0, h && t3 == 0 TSA);
    WG_WAIT(0);
    GSTAMP(2, 12);
    acc_fence<40>(d);
    STAMPW(h ? 18 : 10);
    TR(63);
    const int l3 = tid_now() & 31;
    final_out(d, xw, rn, cf, sb + OFF_CV + h * 10240, p.out + o0, w, l3, [&]() {
      STAMPW(h ? 44 : 9);
      TR(64);
      mbar_wait(sb + BAR_PART, 1);
      TR(65);
    });
    TR(66);
    mbar_arrive_if(sb + BAR_WE, t3 == 0);
  }
}

typedef CUresult (*EncodeFn)(CUtensorMap*, CUtensorMapDataType, cuuint32_t, void*, const cuuint64_t*, const cuuint64_t*, const cuuint32_t*,
                             const cuuint32_t*, CUtensorMapInterleave, CUtensorMapSwizzle, CUtensorMapL2promotion, CUtensorMapFloatOOBfill);

void encode(EncodeFn fn, CUtensorMap* m, const void* ptr, int rank, const cuuint64_t* dims, const cuuint64_t* strides, const cuuint32_t* box,
            CUtensorMapSwizzle swz = CU_TENSOR_MAP_SWIZZLE_128B) {
  const cuuint32_t es[3] = {1, 1, 1};
  fn(m, CU_TENSOR_MAP_DATA_TYPE_BFLOAT16, rank, const_cast<void*>(ptr), dims, strides, box, es, CU_TENSOR_MAP_INTERLEAVE_NONE,
     swz, CU_TENSOR_MAP_L2_PROMOTION_L2_128B, CU_TENSOR_MAP_FLOAT_OOB_FILL_NONE);
}

}

extern "C" void kernel_launch(void* const* d_in, const int* in_sizes, int n_in, void* d_out, int out_size) {
  (void)in_sizes; (void)n_in; (void)out_size;
  static EncodeFn enc = nullptr;
  static Scratch* scr = nullptr;
  static int sms = 0;
  if (!enc) {
    void* fn = nullptr;
    cudaDriverEntryPointQueryResult qr;
    cudaGetDriverEntryPoint("cuTensorMapEncodeTiled", &fn, cudaEnableDefault, &qr);
    enc = (EncodeFn)fn;
    cudaFuncSetAttribute(fused_kernel, cudaFuncAttributeMaxDynamicSharedMemorySize, SMEM_BYTES);
    cudaGetSymbolAddress((void**)&scr, g_scr);
    int dev = 0;
    cudaGetDevice(&dev);
    cudaDeviceGetAttribute(&sms, cudaDevAttrMultiProcessorCount, dev);
  }
  Params p;
  p.scr = scr;
  p.by_smid = sms == 132;
  for (int b = 0; b < 132; b++) {
    const int tp = b >> 1, t7 = (tp - 32) / 7;
    const int lin = tp < 32 ? ((tp & 7) ? (tp & 7) * 16 : 8) + (tp >> 3) * 2 + (b & 1)
                            : (tp < 60 ? (tp - 31 - t7 * 7) * 16 + 8 + t7 * 2 + (b & 1) : (tp < 62 ? 128 + (b & 3) : b - 124));
    const int cb = ((lin >> 4) & 1) * 2 + (lin & 1), rb = (lin >> 5) * 8 + ((lin >> 1) & 7);
    p.job[b] = lin < 128 ? lin | cb << 8 | rb << 10 : lin | (lin & 3) << 8;
  }
  p.x = (const __nv_bfloat16*)d_in[0];
  p.k = (const __nv_bfloat16*)d_in[1];
  p.v = (const __nv_bfloat16*)d_in[2];
  p.shift = (const __nv_bfloat16*)d_in[3];
  p.ssmk = (const __nv_bfloat16*)d_in[4];
  p.ssmD = (const __nv_bfloat16*)d_in[5];
  p.wsp = (const __nv_bfloat16*)d_in[8];
  p.bsp = (const __nv_bfloat16*)d_in[9];
  p.wout = (const __nv_bfloat16*)d_in[10];
  p.out = (__nv_bfloat16*)d_out;
  {
    const cuuint64_t dims[2] = {kD, kS}, st[1] = {kD * 2};
    const cuuint32_t box[2] = {64, 64};
    encode(enc, &p.tmX, d_in[0], 2, dims, st, box);
  }
  {
    const cuuint64_t dims[3] = {64, kD, kF / 64}, st[2] = {kF * 2, 128};
    const cuuint32_t box[3] = {64, 64, 3};
    encode(enc, &p.tmW, d_in[7], 3, dims, st, box);
  }
  {
    const cuuint64_t dims[2] = {kS, kS}, st[1] = {kS * 2};
    const cuuint32_t box[2] = {64, 64};
    encode(enc, &p.tmWsp, d_in[8], 2, dims, st, box);
  }
  {
    const cuuint64_t dims[2] = {kS, kD}, st[1] = {kS * 2};
    const cuuint32_t box[2] = {64, 40};
    encode(enc, &p.tmY, scr->y, 2, dims, st, box);
  }
  {
    const cuuint64_t dims[3] = {1024, kD / 2, 4}, st[2] = {8192, 2048};
    const cuuint32_t box[3] = {16, 32, 4};
    encode(enc, &p.tmKV, scr->kvx, 3, dims, st, box, CU_TENSOR_MAP_SWIZZLE_32B);
  }
  fused_kernel<<<132, 512, SMEM_BYTES, cudaStreamPerThread>>>(p);
}
```

```cpp
#include <cuda_runtime.h>
#include <cuda.h>
#include <cuda_bf16.h>
#include <stdint.h>

template <int N> struct WG;
template <> struct WG<16> {
  static __device__ __forceinline__ void rs(float* d, const uint32_t* a, uint64_t db) {
    asm volatile("{\n.reg .pred p;\nsetp.ne.b32 p, 1, 0;\nwgmma.mma_async.sync.aligned.m64n16k16.f32.bf16.bf16 {"
      "%0, %1, %2, %3, %4, %5, %6, %7"
      "}, {%8, %9, %10, %11}, %12, p, 1, 1, 0;\n}\n"
      :
      "+f"(d[0]), "+f"(d[1]), "+f"(d[2]), "+f"(d[3]), "+f"(d[4]), "+f"(d[5]), "+f"(d[6]), "+f"(d[7])
      : "r"(a[0]), "r"(a[1]), "r"(a[2]), "r"(a[3]), "l"(db));
  }
};
template <> struct WG<32> {
  static __device__ __forceinline__ void rs(float* d, const uint32_t* a, uint64_t db) {
    asm volatile("{\n.reg .pred p;\nsetp.ne.b32 p, 1, 0;\nwgmma.mma_async.sync.aligned.m64n32k16.f32.bf16.bf16 {"
      "%0, %1, %2, %3, %4, %5, %6, %7, %8, %9, %10, %11, %12, %13, %14, %15"
      "}, {%16, %17, %18, %19}, %20, p, 1, 1, 0;\n}\n"
      :
      "+f"(d[0]), "+f"(d[1]), "+f"(d[2]), "+f"(d[3]), "+f"(d[4]), "+f"(d[5]), "+f"(d[6]), "+f"(d[7]),
      "+f"(d[8]), "+f"(d[9]), "+f"(d[10]), "+f"(d[11]), "+f"(d[12]), "+f"(d[13]), "+f"(d[14]), "+f"(d[15])
      : "r"(a[0]), "r"(a[1]), "r"(a[2]), "r"(a[3]), "l"(db));
  }
};
template <> struct WG<48> {
  static __device__ __forceinline__ void rs(float* d, const uint32_t* a, uint64_t db) {
    asm volatile("{\n.reg .pred p;\nsetp.ne.b32 p, 1, 0;\nwgmma.mma_async.sync.aligned.m64n48k16.f32.bf16.bf16 {"
      "%0, %1, %2, %3, %4, %5, %6, %7, %8, %9, %10, %11, %12, %13, %14, %15, "
      "%16, %17, %18, %19, %20, %21, %22, %23"
      "}, {%24, %25, %26, %27}, %28, p, 1, 1, 0;\n}\n"
      :
      "+f"(d[0]), "+f"(d[1]), "+f"(d[2]), "+f"(d[3]), "+f"(d[4]), "+f"(d[5]), "+f"(d[6]), "+f"(d[7]),
      "+f"(d[8]), "+f"(d[9]), "+f"(d[10]), "+f"(d[11]), "+f"(d[12]), "+f"(d[13]), "+f"(d[14]), "+f"(d[15]),
      "+f"(d[16]), "+f"(d[17]), "+f"(d[18]), "+f"(d[19]), "+f"(d[20]), "+f"(d[21]), "+f"(d[22]), "+f"(d[23])
      : "r"(a[0]), "r"(a[1]), "r"(a[2]), "r"(a[3]), "l"(db));
  }
};
template <> struct WG<64> {
  static __device__ __forceinline__ void rs(float* d, const uint32_t* a, uint64_t db) {
    asm volatile("{\n.reg .pred p;\nsetp.ne.b32 p, 1, 0;\nwgmma.mma_async.sync.aligned.m64n64k16.f32.bf16.bf16 {"
      "%0, %1, %2, %3, %4, %5, %6, %7, %8, %9, %10, %11, %12, %13, %14, %15, "
      "%16, %17, %18, %19, %20, %21, %22, %23, %24, %25, %26, %27, %28, %29, %30, %31"
      "}, {%32, %33, %34, %35}, %36, p, 1, 1, 0;\n}\n"
      :
      "+f"(d[0]), "+f"(d[1]), "+f"(d[2]), "+f"(d[3]), "+f"(d[4]), "+f"(d[5]), "+f"(d[6]), "+f"(d[7]),
      "+f"(d[8]), "+f"(d[9]), "+f"(d[10]), "+f"(d[11]), "+f"(d[12]), "+f"(d[13]), "+f"(d[14]), "+f"(d[15]),
      "+f"(d[16]), "+f"(d[17]), "+f"(d[18]), "+f"(d[19]), "+f"(d[20]), "+f"(d[21]), "+f"(d[22]), "+f"(d[23]),
      "+f"(d[24]), "+f"(d[25]), "+f"(d[26]), "+f"(d[27]), "+f"(d[28]), "+f"(d[29]), "+f"(d[30]), "+f"(d[31])
      : "r"(a[0]), "r"(a[1]), "r"(a[2]), "r"(a[3]), "l"(db));
  }
};
template <> struct WG<80> {
  static __device__ __forceinline__ void rs(float* d, const uint32_t* a, uint64_t db) {
    asm volatile("{\n.reg .pred p;\nsetp.ne.b32 p, 1, 0;\nwgmma.mma_async.sync.aligned.m64n80k16.f32.bf16.bf16 {"
      "%0, %1, %2, %3, %4, %5, %6, %7, %8, %9, %10, %11, %12, %13, %14, %15, "
      "%16, %17, %18, %19, %20, %21, %22, %23, %24, %25, %26, %27, %28, %29, %30, %31, "
      "%32, %33, %34, %35, %36, %37, %38, %39"
      "}, {%40, %41, %42, %43}, %44, p, 1, 1, 0;\n}\n"
      :
      "+f"(d[0]), "+f"(d[1]), "+f"(d[2]), "+f"(d[3]), "+f"(d[4]), "+f"(d[5]), "+f"(d[6]), "+f"(d[7]),
      "+f"(d[8]), "+f"(d[9]), "+f"(d[10]), "+f"(d[11]), "+f"(d[12]), "+f"(d[13]), "+f"(d[14]), "+f"(d[15]),
      "+f"(d[16]), "+f"(d[17]), "+f"(d[18]), "+f"(d[19]), "+f"(d[20]), "+f"(d[21]), "+f"(d[22]), "+f"(d[23]),
      "+f"(d[24]), "+f"(d[25]), "+f"(d[26]), "+f"(d[27]), "+f"(d[28]), "+f"(d[29]), "+f"(d[30]), "+f"(d[31]),
      "+f"(d[32]), "+f"(d[33]), "+f"(d[34]), "+f"(d[35]), "+f"(d[36]), "+f"(d[37]), "+f"(d[38]), "+f"(d[39])
      : "r"(a[0]), "r"(a[1]), "r"(a[2]), "r"(a[3]), "l"(db));
  }
};
template <> struct WG<96> {
  static __device__ __forceinline__ void rs(float* d, const uint32_t* a, uint64_t db) {
    asm volatile("{\n.reg .pred p;\nsetp.ne.b32 p, 1, 0;\nwgmma.mma_async.sync.aligned.m64n96k16.f32.bf16.bf16 {"
      "%0, %1, %2, %3, %4, %5, %6, %7, %8, %9, %10, %11, %12, %13, %14, %15, "
      "%16, %17, %18, %19, %20, %21, %22, %23, %24, %25, %26, %27, %28, %29, %30, %31, "
      "%32, %33, %34, %35, %36, %37, %38, %39, %40, %41, %42, %43, %44, %45, %46, %47"
      "}, {%48, %49, %50, %51}, %52, p, 1, 1, 0;\n}\n"
      :
      "+f"(d[0]), "+f"(d[1]), "+f"(d[2]), "+f"(d[3]), "+f"(d[4]), "+f"(d[5]), "+f"(d[6]), "+f"(d[7]),
      "+f"(d[8]), "+f"(d[9]), "+f"(d[10]), "+f"(d[11]), "+f"(d[12]), "+f"(d[13]), "+f"(d[14]), "+f"(d[15]),
      "+f"(d[16]), "+f"(d[17]), "+f"(d[18]), "+f"(d[19]), "+f"(d[20]), "+f"(d[21]), "+f"(d[22]), "+f"(d[23]),
      "+f"(d[24]), "+f"(d[25]), "+f"(d[26]), "+f"(d[27]), "+f"(d[28]), "+f"(d[29]), "+f"(d[30]), "+f"(d[31]),
      "+f"(d[32]), "+f"(d[33]), "+f"(d[34]), "+f"(d[35]), "+f"(d[36]), "+f"(d[37]), "+f"(d[38]), "+f"(d[39]),
      "+f"(d[40]), "+f"(d[41]), "+f"(d[42]), "+f"(d[43]), "+f"(d[44]), "+f"(d[45]), "+f"(d[46]), "+f"(d[47])
      : "r"(a[0]), "r"(a[1]), "r"(a[2]), "r"(a[3]), "l"(db));
  }
};
template <> struct WG<112> {
  static __device__ __forceinline__ void rs(float* d, const uint32_t* a, uint64_t db) {
    asm volatile("{\n.reg .pred p;\nsetp.ne.b32 p, 1, 0;\nwgmma.mma_async.sync.aligned.m64n112k16.f32.bf16.bf16 {"
      "%0, %1, %2, %3, %4, %5, %6, %7, %8, %9, %10, %11, %12, %13, %14, %15, "
      "%16, %17, %18, %19, %20, %21, %22, %23, %24, %25, %26, %27, %28, %29, %30, %31, "
      "%32, %33, %34, %35, %36, %37, %38, %39, %40, %41, %42, %43, %44, %45, %46, %47, "
      "%48, %49, %50, %51, %52, %53, %54, %55"
      "}, {%56, %57, %58, %59}, %60, p, 1, 1, 0;\n}\n"
      :
      "+f"(d[0]), "+f"(d[1]), "+f"(d[2]), "+f"(d[3]), "+f"(d[4]), "+f"(d[5]), "+f"(d[6]), "+f"(d[7]),
      "+f"(d[8]), "+f"(d[9]), "+f"(d[10]), "+f"(d[11]), "+f"(d[12]), "+f"(d[13]), "+f"(d[14]), "+f"(d[15]),
      "+f"(d[16]), "+f"(d[17]), "+f"(d[18]), "+f"(d[19]), "+f"(d[20]), "+f"(d[21]), "+f"(d[22]), "+f"(d[23]),
      "+f"(d[24]), "+f"(d[25]), "+f"(d[26]), "+f"(d[27]), "+f"(d[28]), "+f"(d[29]), "+f"(d[30]), "+f"(d[31]),
      "+f"(d[32]), "+f"(d[33]), "+f"(d[34]), "+f"(d[35]), "+f"(d[36]), "+f"(d[37]), "+f"(d[38]), "+f"(d[39]),
      "+f"(d[40]), "+f"(d[41]), "+f"(d[42]), "+f"(d[43]), "+f"(d[44]), "+f"(d[45]), "+f"(d[46]), "+f"(d[47]),
      "+f"(d[48]), "+f"(d[49]), "+f"(d[50]), "+f"(d[51]), "+f"(d[52]), "+f"(d[53]), "+f"(d[54]), "+f"(d[55])
      : "r"(a[0]), "r"(a[1]), "r"(a[2]), "r"(a[3]), "l"(db));
  }
};
template <> struct WG<128> {
  static __device__ __forceinline__ void rs(float* d, const uint32_t* a, uint64_t db) {
    asm volatile("{\n.reg .pred p;\nsetp.ne.b32 p, 1, 0;\nwgmma.mma_async.sync.aligned.m64n128k16.f32.bf16.bf16 {"
      "%0, %1, %2, %3, %4, %5, %6, %7, %8, %9, %10, %11, %12, %13, %14, %15, "
      "%16, %17, %18, %19, %20, %21, %22, %23, %24, %25, %26, %27, %28, %29, %30, %31, "
      "%32, %33, %34, %35, %36, %37, %38, %39, %40, %41, %42, %43, %44, %45, %46, %47, "
      "%48, %49, %50, %51, %52, %53, %54, %55, %56, %57, %58, %59, %60, %61, %62, %63"
      "}, {%64, %65, %66, %67}, %68, p, 1, 1, 0;\n}\n"
      :
      "+f"(d[0]), "+f"(d[1]), "+f"(d[2]), "+f"(d[3]), "+f"(d[4]), "+f"(d[5]), "+f"(d[6]), "+f"(d[7]),
      "+f"(d[8]), "+f"(d[9]), "+f"(d[10]), "+f"(d[11]), "+f"(d[12]), "+f"(d[13]), "+f"(d[14]), "+f"(d[15]),
      "+f"(d[16]), "+f"(d[17]), "+f"(d[18]), "+f"(d[19]), "+f"(d[20]), "+f"(d[21]), "+f"(d[22]), "+f"(d[23]),
      "+f"(d[24]), "+f"(d[25]), "+f"(d[26]), "+f"(d[27]), "+f"(d[28]), "+f"(d[29]), "+f"(d[30]), "+f"(d[31]),
      "+f"(d[32]), "+f"(d[33]), "+f"(d[34]), "+f"(d[35]), "+f"(d[36]), "+f"(d[37]), "+f"(d[38]), "+f"(d[39]),
      "+f"(d[40]), "+f"(d[41]), "+f"(d[42]), "+f"(d[43]), "+f"(d[44]), "+f"(d[45]), "+f"(d[46]), "+f"(d[47]),
      "+f"(d[48]), "+f"(d[49]), "+f"(d[50]), "+f"(d[51]), "+f"(d[52]), "+f"(d[53]), "+f"(d[54]), "+f"(d[55]),
      "+f"(d[56]), "+f"(d[57]), "+f"(d[58]), "+f"(d[59]), "+f"(d[60]), "+f"(d[61]), "+f"(d[62]), "+f"(d[63])
      : "r"(a[0]), "r"(a[1]), "r"(a[2]), "r"(a[3]), "l"(db));
  }
};
template <int N> struct KB;
template <> struct KB<80> {
  template <int W, int RC, int RA, int BSTEP> static __device__ __forceinline__ void run(float* d, uint64_t da, uint64_t db, uint32_t rel, uint32_t rela, uint32_t doR, uint32_t fa, uint32_t pa, uint32_t fb, uint32_t pb, uint32_t acc) {
    if constexpr (W == 0 && RC == 0 && RA == 0) asm volatile(
    "{\n.reg .pred p, q, r, t;\n.reg .b64 a, b;\n.reg .u32 n;\nsetp.ne.b32 t, 1, 0;\nsetp.ne.b32 r, %49, 0;\n"
    "wgmma.mma_async.sync.aligned.m64n80k16.f32.bf16.bf16 {"
      "%0, %1, %2, %3, %4, %5, %6, %7, %8, %9, %10, %11, %12, %13, %14, %15, "
      "%16, %17, %18, %19, %20, %21, %22, %23, %24, %25, %26, %27, %28, %29, %30, %31, "
      "%32, %33, %34, %35, %36, %37, %38, %39"
      "}, %40, %41, r, 1, 1, 0, 1;\n"
    "add.u64 a, %40, 2;\nadd.u64 b, %41, %48;\n"
    "wgmma.mma_async.sync.aligned.m64n80k16.f32.bf16.bf16 {"
      "%0, %1, %2, %3, %4, %5, %6, %7, %8, %9, %10, %11, %12, %13, %14, %15, "
      "%16, %17, %18, %19, %20, %21, %22, %23, %24, %25, %26, %27, %28, %29, %30, %31, "
      "%32, %33, %34, %35, %36, %37, %38, %39"
      "}, a, b, t, 1, 1, 0, 1;\n"
    "wgmma.commit_group.sync.aligned;\nwgmma.wait_group.sync.aligned 1;\n"
    "add.u64 a, %40, 4;\nadd.u64 b, %41, 2*%48;\n"
    "wgmma.mma_async.sync.aligned.m64n80k16.f32.bf16.bf16 {"
      "%0, %1, %2, %3, %4, %5, %6, %7, %8, %9, %10, %11, %12, %13, %14, %15, "
      "%16, %17, %18, %19, %20, %21, %22, %23, %24, %25, %26, %27, %28, %29, %30, %31, "
      "%32, %33, %34, %35, %36, %37, %38, %39"
      "}, a, b, t, 1, 1, 0, 1;\n"
    "add.u64 a, %40, 6;\nadd.u64 b, %41, 3*%48;\n"
    "wgmma.mma_async.sync.aligned.m64n80k16.f32.bf16.bf16 {"
      "%0, %1, %2, %3, %4, %5, %6, %7, %8, %9, %10, %11, %12, %13, %14, %15, "
      "%16, %17, %18, %19, %20, %21, %22, %23, %24, %25, %26, %27, %28, %29, %30, %31, "
      "%32, %33, %34, %35, %36, %37, %38, %39"
      "}, a, b, t, 1, 1, 0, 1;\n"
    "wgmma.commit_group.sync.aligned;\n"
    "}\n"
      :
      "+f"(d[0]), "+f"(d[1]), "+f"(d[2]), "+f"(d[3]), "+f"(d[4]), "+f"(d[5]), "+f"(d[6]), "+f"(d[7]),
      "+f"(d[8]), "+f"(d[9]), "+f"(d[10]), "+f"(d[11]), "+f"(d[12]), "+f"(d[13]), "+f"(d[14]), "+f"(d[15]),
      "+f"(d[16]), "+f"(d[17]), "+f"(d[18]), "+f"(d[19]), "+f"(d[20]), "+f"(d[21]), "+f"(d[22]), "+f"(d[23]),
      "+f"(d[24]), "+f"(d[25]), "+f"(d[26]), "+f"(d[27]), "+f"(d[28]), "+f"(d[29]), "+f"(d[30]), "+f"(d[31]),
      "+f"(d[32]), "+f"(d[33]), "+f"(d[34]), "+f"(d[35]), "+f"(d[36]), "+f"(d[37]), "+f"(d[38]), "+f"(d[39])
      : "l"(da), "l"(db), "r"(rel), "r"(doR), "r"(fa), "r"(pa), "r"(fb), "r"(pb), "n"(BSTEP), "r"(acc), "r"(rela) : "memory");
    else if constexpr (W == 0 && RC == 1 && RA == 0) asm volatile(
    "{\n.reg .pred p, q, r, t;\n.reg .b64 a, b;\n.reg .u32 n;\nsetp.ne.b32 t, 1, 0;\nsetp.ne.b32 r, %49, 0;\n"
    "wgmma.mma_async.sync.aligned.m64n80k16.f32.bf16.bf16 {"
      "%0, %1, %2, %3, %4, %5, %6, %7, %8, %9, %10, %11, %12, %13, %14, %15, "
      "%16, %17, %18, %19, %20, %21, %22, %23, %24, %25, %26, %27, %28, %29, %30, %31, "
      "%32, %33, %34, %35, %36, %37, %38, %39"
      "}, %40, %41, r, 1, 1, 0, 1;\n"
    "add.u64 a, %40, 2;\nadd.u64 b, %41, %48;\n"
    "wgmma.mma_async.sync.aligned.m64n80k16.f32.bf16.bf16 {"
      "%0, %1, %2, %3, %4, %5, %6, %7, %8, %9, %10, %11, %12, %13, %14, %15, "
      "%16, %17, %18, %19, %20, %21, %22, %23, %24, %25, %26, %27, %28, %29, %30, %31, "
      "%32, %33, %34, %35, %36, %37, %38, %39"
      "}, a, b, t, 1, 1, 0, 1;\n"
    "wgmma.commit_group.sync.aligned;\nwgmma.wait_group.sync.aligned 1;\n"
    "add.u64 a, %40, 4;\nadd.u64 b, %41, 2*%48;\n"
    "wgmma.mma_async.sync.aligned.m64n80k16.f32.bf16.bf16 {"
      "%0, %1, %2, %3, %4, %5, %6, %7, %8, %9, %10, %11, %12, %13, %14, %15, "
      "%16, %17, %18, %19, %20, %21, %22, %23, %24, %25, %26, %27, %28, %29, %30, %31, "
      "%32, %33, %34, %35, %36, %37, %38, %39"
      "}, a, b, t, 1, 1, 0, 1;\n"
    "setp.ne.u32 q, %43, 0;\n@q mbarrier.arrive.shared::cta.b64 _, [%42];\n"
    "add.u64 a, %40, 6;\nadd.u64 b, %41, 3*%48;\n"
    "wgmma.mma_async.sync.aligned.m64n80k16.f32.bf16.bf16 {"
      "%0, %1, %2, %3, %4, %5, %6, %7, %8, %9, %10, %11, %12, %13, %14, %15, "
      "%16, %17, %18, %19, %20, %21, %22, %23, %24, %25, %26, %27, %28, %29, %30, %31, "
      "%32, %33, %34, %35, %36, %37, %38, %39"
      "}, a, b, t, 1, 1, 0, 1;\n"
    "wgmma.commit_group.sync.aligned;\n"
    "}\n"
      :
      "+f"(d[0]), "+f"(d[1]), "+f"(d[2]), "+f"(d[3]), "+f"(d[4]), "+f"(d[5]), "+f"(d[6]), "+f"(d[7]),
      "+f"(d[8]), "+f"(d[9]), "+f"(d[10]), "+f"(d[11]), "+f"(d[12]), "+f"(d[13]), "+f"(d[14]), "+f"(d[15]),
      "+f"(d[16]), "+f"(d[17]), "+f"(d[18]), "+f"(d[19]), "+f"(d[20]), "+f"(d[21]), "+f"(d[22]), "+f"(d[23]),
      "+f"(d[24]), "+f"(d[25]), "+f"(d[26]), "+f"(d[27]), "+f"(d[28]), "+f"(d[29]), "+f"(d[30]), "+f"(d[31]),
      "+f"(d[32]), "+f"(d[33]), "+f"(d[34]), "+f"(d[35]), "+f"(d[36]), "+f"(d[37]), "+f"(d[38]), "+f"(d[39])
      : "l"(da), "l"(db), "r"(rel), "r"(doR), "r"(fa), "r"(pa), "r"(fb), "r"(pb), "n"(BSTEP), "r"(acc), "r"(rela) : "memory");
    else if constexpr (W == 1 && RC == 0 && RA == 0) asm volatile(
    "{\n.reg .pred p, q, r, t;\n.reg .b64 a, b;\n.reg .u32 n;\nsetp.ne.b32 t, 1, 0;\nsetp.ne.b32 r, %49, 0;\n"
    "wgmma.mma_async.sync.aligned.m64n80k16.f32.bf16.bf16 {"
      "%0, %1, %2, %3, %4, %5, %6, %7, %8, %9, %10, %11, %12, %13, %14, %15, "
      "%16, %17, %18, %19, %20, %21, %22, %23, %24, %25, %26, %27, %28, %29, %30, %31, "
      "%32, %33, %34, %35, %36, %37, %38, %39"
      "}, %40, %41, r, 1, 1, 0, 1;\n"
    "add.u64 a, %40, 2;\nadd.u64 b, %41, %48;\n"
    "wgmma.mma_async.sync.aligned.m64n80k16.f32.bf16.bf16 {"
      "%0, %1, %2, %3, %4, %5, %6, %7, %8, %9, %10, %11, %12, %13, %14, %15, "
      "%16, %17, %18, %19, %20, %21, %22, %23, %24, %25, %26, %27, %28, %29, %30, %31, "
      "%32, %33, %34, %35, %36, %37, %38, %39"
      "}, a, b, t, 1, 1, 0, 1;\n"
    "wgmma.commit_group.sync.aligned;\nwgmma.wait_group.sync.aligned 1;\n"
    "add.u64 a, %40, 4;\nadd.u64 b, %41, 2*%48;\n"
    "wgmma.mma_async.sync.aligned.m64n80k16.f32.bf16.bf16 {"
      "%0, %1, %2, %3, %4, %5, %6, %7, %8, %9, %10, %11, %12, %13, %14, %15, "
      "%16, %17, %18, %19, %20, %21, %22, %23, %24, %25, %26, %27, %28, %29, %30, %31, "
      "%32, %33, %34, %35, %36, %37, %38, %39"
      "}, a, b, t, 1, 1, 0, 1;\n"
    "mbarrier.test_wait.parity.shared::cta.b64 p, [%46], %47;\n"
    "add.u64 a, %40, 6;\nadd.u64 b, %41, 3*%48;\n"
    "wgmma.mma_async.sync.aligned.m64n80k16.f32.bf16.bf16 {"
      "%0, %1, %2, %3, %4, %5, %6, %7, %8, %9, %10, %11, %12, %13, %14, %15, "
      "%16, %17, %18, %19, %20, %21, %22, %23, %24, %25, %26, %27, %28, %29, %30, %31, "
      "%32, %33, %34, %35, %36, %37, %38, %39"
      "}, a, b, t, 1, 1, 0, 1;\n"
    "wgmma.commit_group.sync.aligned;\n"
    "@p bra.uni DN;\nmov.u32 n, 0;\nWT: mbarrier.try_wait.parity.shared::cta.b64 p, [%46], %47;\n@p bra.uni DN;\nadd.u32 n, n, 1;\nsetp.lt.u32 p, n, 0x100000;\n@p bra.uni WT;\nDN:\n"
    "}\n"
      :
      "+f"(d[0]), "+f"(d[1]), "+f"(d[2]), "+f"(d[3]), "+f"(d[4]), "+f"(d[5]), "+f"(d[6]), "+f"(d[7]),
      "+f"(d[8]), "+f"(d[9]), "+f"(d[10]), "+f"(d[11]), "+f"(d[12]), "+f"(d[13]), "+f"(d[14]), "+f"(d[15]),
      "+f"(d[16]), "+f"(d[17]), "+f"(d[18]), "+f"(d[19]), "+f"(d[20]), "+f"(d[21]), "+f"(d[22]), "+f"(d[23]),
      "+f"(d[24]), "+f"(d[25]), "+f"(d[26]), "+f"(d[27]), "+f"(d[28]), "+f"(d[29]), "+f"(d[30]), "+f"(d[31]),
      "+f"(d[32]), "+f"(d[33]), "+f"(d[34]), "+f"(d[35]), "+f"(d[36]), "+f"(d[37]), "+f"(d[38]), "+f"(d[39])
      : "l"(da), "l"(db), "r"(rel), "r"(doR), "r"(fa), "r"(pa), "r"(fb), "r"(pb), "n"(BSTEP), "r"(acc), "r"(rela) : "memory");
    else if constexpr (W == 1 && RC == 1 && RA == 0) asm volatile(
    "{\n.reg .pred p, q, r, t;\n.reg .b64 a, b;\n.reg .u32 n;\nsetp.ne.b32 t, 1, 0;\nsetp.ne.b32 r, %49, 0;\n"
    "wgmma.mma_async.sync.aligned.m64n80k16.f32.bf16.bf16 {"
      "%0, %1, %2, %3, %4, %5, %6, %7, %8, %9, %10, %11, %12, %13, %14, %15, "
      "%16, %17, %18, %19, %20, %21, %22, %23, %24, %25, %26, %27, %28, %29, %30, %31, "
      "%32, %33, %34, %35, %36, %37, %38, %39"
      "}, %40, %41, r, 1, 1, 0, 1;\n"
    "add.u64 a, %40, 2;\nadd.u64 b, %41, %48;\n"
    "wgmma.mma_async.sync.aligned.m64n80k16.f32.bf16.bf16 {"
      "%0, %1, %2, %3, %4, %5, %6, %7, %8, %9, %10, %11, %12, %13, %14, %15, "
      "%16, %17, %18, %19, %20, %21, %22, %23, %24, %25, %26, %27, %28, %29, %30, %31, "
      "%32, %33, %34, %35, %36, %37, %38, %39"
      "}, a, b, t, 1, 1, 0, 1;\n"
    "wgmma.commit_group.sync.aligned;\nwgmma.wait_group.sync.aligned 1;\n"
    "add.u64 a, %40, 4;\nadd.u64 b, %41, 2*%48;\n"
    "wgmma.mma_async.sync.aligned.m64n80k16.f32.bf16.bf16 {"
      "%0, %1, %2, %3, %4, %5, %6, %7, %8, %9, %10, %11, %12, %13, %14, %15, "
      "%16, %17, %18, %19, %20, %21, %22, %23, %24, %25, %26, %27, %28, %29, %30, %31, "
      "%32, %33, %34, %35, %36, %37, %38, %39"
      "}, a, b, t, 1, 1, 0, 1;\n"
    "setp.ne.u32 q, %43, 0;\n@q mbarrier.arrive.shared::cta.b64 _, [%42];\n"
    "mbarrier.test_wait.parity.shared::cta.b64 p, [%46], %47;\n"
    "add.u64 a, %40, 6;\nadd.u64 b, %41, 3*%48;\n"
    "wgmma.mma_async.sync.aligned.m64n80k16.f32.bf16.bf16 {"
      "%0, %1, %2, %3, %4, %5, %6, %7, %8, %9, %10, %11, %12, %13, %14, %15, "
      "%16, %17, %18, %19, %20, %21, %22, %23, %24, %25, %26, %27, %28, %29, %30, %31, "
      "%32, %33, %34, %35, %36, %37, %38, %39"
      "}, a, b, t, 1, 1, 0, 1;\n"
    "wgmma.commit_group.sync.aligned;\n"
    "@p bra.uni DN;\nmov.u32 n, 0;\nWT: mbarrier.try_wait.parity.shared::cta.b64 p, [%46], %47;\n@p bra.uni DN;\nadd.u32 n, n, 1;\nsetp.lt.u32 p, n, 0x100000;\n@p bra.uni WT;\nDN:\n"
    "}\n"
      :
      "+f"(d[0]), "+f"(d[1]), "+f"(d[2]), "+f"(d[3]), "+f"(d[4]), "+f"(d[5]), "+f"(d[6]), "+f"(d[7]),
      "+f"(d[8]), "+f"(d[9]), "+f"(d[10]), "+f"(d[11]), "+f"(d[12]), "+f"(d[13]), "+f"(d[14]), "+f"(d[15]),
      "+f"(d[16]), "+f"(d[17]), "+f"(d[18]), "+f"(d[19]), "+f"(d[20]), "+f"(d[21]), "+f"(d[22]), "+f"(d[23]),
      "+f"(d[24]), "+f"(d[25]), "+f"(d[26]), "+f"(d[27]), "+f"(d[28]), "+f"(d[29]), "+f"(d[30]), "+f"(d[31]),
      "+f"(d[32]), "+f"(d[33]), "+f"(d[34]), "+f"(d[35]), "+f"(d[36]), "+f"(d[37]), "+f"(d[38]), "+f"(d[39])
      : "l"(da), "l"(db), "r"(rel), "r"(doR), "r"(fa), "r"(pa), "r"(fb), "r"(pb), "n"(BSTEP), "r"(acc), "r"(rela) : "memory");
    else if constexpr (W == 2 && RC == 0 && RA == 0) asm volatile(
    "{\n.reg .pred p, q, r, t;\n.reg .b64 a, b;\n.reg .u32 n;\nsetp.ne.b32 t, 1, 0;\nsetp.ne.b32 r, %49, 0;\n"
    "wgmma.mma_async.sync.aligned.m64n80k16.f32.bf16.bf16 {"
      "%0, %1, %2, %3, %4, %5, %6, %7, %8, %9, %10, %11, %12, %13, %14, %15, "
      "%16, %17, %18, %19, %20, %21, %22, %23, %24, %25, %26, %27, %28, %29, %30, %31, "
      "%32, %33, %34, %35, %36, %37, %38, %39"
      "}, %40, %41, r, 1, 1, 0, 1;\n"
    "add.u64 a, %40, 2;\nadd.u64 b, %41, %48;\n"
    "wgmma.mma_async.sync.aligned.m64n80k16.f32.bf16.bf16 {"
      "%0, %1, %2, %3, %4, %5, %6, %7, %8, %9, %10, %11, %12, %13, %14, %15, "
      "%16, %17, %18, %19, %20, %21, %22, %23, %24, %25, %26, %27, %28, %29, %30, %31, "
      "%32, %33, %34, %35, %36, %37, %38, %39"
      "}, a, b, t, 1, 1, 0, 1;\n"
    "wgmma.commit_group.sync.aligned;\nwgmma.wait_group.sync.aligned 1;\n"
    "add.u64 a, %40, 4;\nadd.u64 b, %41, 2*%48;\n"
    "wgmma.mma_async.sync.aligned.m64n80k16.f32.bf16.bf16 {"
      "%0, %1, %2, %3, %4, %5, %6, %7, %8, %9, %10, %11, %12, %13, %14, %15, "
      "%16, %17, %18, %19, %20, %21, %22, %23, %24, %25, %26, %27, %28, %29, %30, %31, "
      "%32, %33, %34, %35, %36, %37, %38, %39"
      "}, a, b, t, 1, 1, 0, 1;\n"
    "mbarrier.test_wait.parity.shared::cta.b64 p, [%46], %47;\n"
    "mbarrier.test_wait.parity.shared::cta.b64 r, [%44], %45;\nand.pred p, p, r;\n"
    "add.u64 a, %40, 6;\nadd.u64 b, %41, 3*%48;\n"
    "wgmma.mma_async.sync.aligned.m64n80k16.f32.bf16.bf16 {"
      "%0, %1, %2, %3, %4, %5, %6, %7, %8, %9, %10, %11, %12, %13, %14, %15, "
      "%16, %17, %18, %19, %20, %21, %22, %23, %24, %25, %26, %27, %28, %29, %30, %31, "
      "%32, %33, %34, %35, %36, %37, %38, %39"
      "}, a, b, t, 1, 1, 0, 1;\n"
    "wgmma.commit_group.sync.aligned;\n"
    "@p bra.uni DN;\nmov.u32 n, 0;\nWT: mbarrier.try_wait.parity.shared::cta.b64 p, [%46], %47;\nmbarrier.try_wait.parity.shared::cta.b64 r, [%44], %45;\nand.pred p, p, r;\n@p bra.uni DN;\nadd.u32 n, n, 1;\nsetp.lt.u32 p, n, 0x100000;\n@p bra.uni WT;\nDN:\n"
    "}\n"
      :
      "+f"(d[0]), "+f"(d[1]), "+f"(d[2]), "+f"(d[3]), "+f"(d[4]), "+f"(d[5]), "+f"(d[6]), "+f"(d[7]),
      "+f"(d[8]), "+f"(d[9]), "+f"(d[10]), "+f"(d[11]), "+f"(d[12]), "+f"(d[13]), "+f"(d[14]), "+f"(d[15]),
      "+f"(d[16]), "+f"(d[17]), "+f"(d[18]), "+f"(d[19]), "+f"(d[20]), "+f"(d[21]), "+f"(d[22]), "+f"(d[23]),
      "+f"(d[24]), "+f"(d[25]), "+f"(d[26]), "+f"(d[27]), "+f"(d[28]), "+f"(d[29]), "+f"(d[30]), "+f"(d[31]),
      "+f"(d[32]), "+f"(d[33]), "+f"(d[34]), "+f"(d[35]), "+f"(d[36]), "+f"(d[37]), "+f"(d[38]), "+f"(d[39])
      : "l"(da), "l"(db), "r"(rel), "r"(doR), "r"(fa), "r"(pa), "r"(fb), "r"(pb), "n"(BSTEP), "r"(acc), "r"(rela) : "memory");
    else if constexpr (W == 2 && RC == 1 && RA == 0) asm volatile(
    "{\n.reg .pred p, q, r, t;\n.reg .b64 a, b;\n.reg .u32 n;\nsetp.ne.b32 t, 1, 0;\nsetp.ne.b32 r, %49, 0;\n"
    "wgmma.mma_async.sync.aligned.m64n80k16.f32.bf16.bf16 {"
      "%0, %1, %2, %3, %4, %5, %6, %7, %8, %9, %10, %11, %12, %13, %14, %15, "
      "%16, %17, %18, %19, %20, %21, %22, %23, %24, %25, %26, %27, %28, %29, %30, %31, "
      "%32, %33, %34, %35, %36, %37, %38, %39"
      "}, %40, %41, r, 1, 1, 0, 1;\n"
    "add.u64 a, %40, 2;\nadd.u64 b, %41, %48;\n"
    "wgmma.mma_async.sync.aligned.m64n80k16.f32.bf16.bf16 {"
      "%0, %1, %2, %3, %4, %5, %6, %7, %8, %9, %10, %11, %12, %13, %14, %15, "
      "%16, %17, %18, %19, %20, %21, %22, %23, %24, %25, %26, %27, %28, %29, %30, %31, "
      "%32, %33, %34, %35, %36, %37, %38, %39"
      "}, a, b, t, 1, 1, 0, 1;\n"
    "wgmma.commit_group.sync.aligned;\nwgmma.wait_group.sync.aligned 1;\n"
    "add.u64 a, %40, 4;\nadd.u64 b, %41, 2*%48;\n"
    "wgmma.mma_async.sync.aligned.m64n80k16.f32.bf16.bf16 {"
      "%0, %1, %2, %3, %4, %5, %6, %7, %8, %9, %10, %11, %12, %13, %14, %15, "
      "%16, %17, %18, %19, %20, %21, %22, %23, %24, %25, %26, %27, %28, %29, %30, %31, "
      "%32, %33, %34, %35, %36, %37, %38, %39"
      "}, a, b, t, 1, 1, 0, 1;\n"
    "setp.ne.u32 q, %43, 0;\n@q mbarrier.arrive.shared::cta.b64 _, [%42];\n"
    "mbarrier.test_wait.parity.shared::cta.b64 p, [%46], %47;\n"
    "mbarrier.test_wait.parity.shared::cta.b64 r, [%44], %45;\nand.pred p, p, r;\n"
    "add.u64 a, %40, 6;\nadd.u64 b, %41, 3*%48;\n"
    "wgmma.mma_async.sync.aligned.m64n80k16.f32.bf16.bf16 {"
      "%0, %1, %2, %3, %4, %5, %6, %7, %8, %9, %10, %11, %12, %13, %14, %15, "
      "%16, %17, %18, %19, %20, %21, %22, %23, %24, %25, %26, %27, %28, %29, %30, %31, "
      "%32, %33, %34, %35, %36, %37, %38, %39"
      "}, a, b, t, 1, 1, 0, 1;\n"
    "wgmma.commit_group.sync.aligned;\n"
    "@p bra.uni DN;\nmov.u32 n, 0;\nWT: mbarrier.try_wait.parity.shared::cta.b64 p, [%46], %47;\nmbarrier.try_wait.parity.shared::cta.b64 r, [%44], %45;\nand.pred p, p, r;\n@p bra.uni DN;\nadd.u32 n, n, 1;\nsetp.lt.u32 p, n, 0x100000;\n@p bra.uni WT;\nDN:\n"
    "}\n"
      :
      "+f"(d[0]), "+f"(d[1]), "+f"(d[2]), "+f"(d[3]), "+f"(d[4]), "+f"(d[5]), "+f"(d[6]), "+f"(d[7]),
      "+f"(d[8]), "+f"(d[9]), "+f"(d[10]), "+f"(d[11]), "+f"(d[12]), "+f"(d[13]), "+f"(d[14]), "+f"(d[15]),
      "+f"(d[16]), "+f"(d[17]), "+f"(d[18]), "+f"(d[19]), "+f"(d[20]), "+f"(d[21]), "+f"(d[22]), "+f"(d[23]),
      "+f"(d[24]), "+f"(d[25]), "+f"(d[26]), "+f"(d[27]), "+f"(d[28]), "+f"(d[29]), "+f"(d[30]), "+f"(d[31]),
      "+f"(d[32]), "+f"(d[33]), "+f"(d[34]), "+f"(d[35]), "+f"(d[36]), "+f"(d[37]), "+f"(d[38]), "+f"(d[39])
      : "l"(da), "l"(db), "r"(rel), "r"(doR), "r"(fa), "r"(pa), "r"(fb), "r"(pb), "n"(BSTEP), "r"(acc), "r"(rela) : "memory");
    else if constexpr (W == 2 && RC == 1 && RA == 1) asm volatile(
    "{\n.reg .pred p, q, r, t;\n.reg .b64 a, b;\n.reg .u32 n;\nsetp.ne.b32 t, 1, 0;\nsetp.ne.b32 r, %49, 0;\n"
    "wgmma.mma_async.sync.aligned.m64n80k16.f32.bf16.bf16 {"
      "%0, %1, %2, %3, %4, %5, %6, %7, %8, %9, %10, %11, %12, %13, %14, %15, "
      "%16, %17, %18, %19, %20, %21, %22, %23, %24, %25, %26, %27, %28, %29, %30, %31, "
      "%32, %33, %34, %35, %36, %37, %38, %39"
      "}, %40, %41, r, 1, 1, 0, 1;\n"
    "add.u64 a, %40, 2;\nadd.u64 b, %41, %48;\n"
    "wgmma.mma_async.sync.aligned.m64n80k16.f32.bf16.bf16 {"
      "%0, %1, %2, %3, %4, %5, %6, %7, %8, %9, %10, %11, %12, %13, %14, %15, "
      "%16, %17, %18, %19, %20, %21, %22, %23, %24, %25, %26, %27, %28, %29, %30, %31, "
      "%32, %33, %34, %35, %36, %37, %38, %39"
      "}, a, b, t, 1, 1, 0, 1;\n"
    "wgmma.commit_group.sync.aligned;\nwgmma.wait_group.sync.aligned 1;\n"
    "add.u64 a, %40, 4;\nadd.u64 b, %41, 2*%48;\n"
    "wgmma.mma_async.sync.aligned.m64n80k16.f32.bf16.bf16 {"
      "%0, %1, %2, %3, %4, %5, %6, %7, %8, %9, %10, %11, %12, %13, %14, %15, "
      "%16, %17, %18, %19, %20, %21, %22, %23, %24, %25, %26, %27, %28, %29, %30, %31, "
      "%32, %33, %34, %35, %36, %37, %38, %39"
      "}, a, b, t, 1, 1, 0, 1;\n"
    "setp.ne.u32 q, %43, 0;\n@q mbarrier.arrive.shared::cta.b64 _, [%42];\n@q mbarrier.arrive.shared::cta.b64 _, [%50];\n"
    "mbarrier.test_wait.parity.shared::cta.b64 p, [%46], %47;\n"
    "mbarrier.test_wait.parity.shared::cta.b64 r, [%44], %45;\nand.pred p, p, r;\n"
    "add.u64 a, %40, 6;\nadd.u64 b, %41, 3*%48;\n"
    "wgmma.mma_async.sync.aligned.m64n80k16.f32.bf16.bf16 {"
      "%0, %1, %2, %3, %4, %5, %6, %7, %8, %9, %10, %11, %12, %13, %14, %15, "
      "%16, %17, %18, %19, %20, %21, %22, %23, %24, %25, %26, %27, %28, %29, %30, %31, "
      "%32, %33, %34, %35, %36, %37, %38, %39"
      "}, a, b, t, 1, 1, 0, 1;\n"
    "wgmma.commit_group.sync.aligned;\n"
    "@p bra.uni DN;\nmov.u32 n, 0;\nWT: mbarrier.try_wait.parity.shared::cta.b64 p, [%46], %47;\nmbarrier.try_wait.parity.shared::cta.b64 r, [%44], %45;\nand.pred p, p, r;\n@p bra.uni DN;\nadd.u32 n, n, 1;\nsetp.lt.u32 p, n, 0x100000;\n@p bra.uni WT;\nDN:\n"
    "}\n"
      :
      "+f"(d[0]), "+f"(d[1]), "+f"(d[2]), "+f"(d[3]), "+f"(d[4]), "+f"(d[5]), "+f"(d[6]), "+f"(d[7]),
      "+f"(d[8]), "+f"(d[9]), "+f"(d[10]), "+f"(d[11]), "+f"(d[12]), "+f"(d[13]), "+f"(d[14]), "+f"(d[15]),
      "+f"(d[16]), "+f"(d[17]), "+f"(d[18]), "+f"(d[19]), "+f"(d[20]), "+f"(d[21]), "+f"(d[22]), "+f"(d[23]),
      "+f"(d[24]), "+f"(d[25]), "+f"(d[26]), "+f"(d[27]), "+f"(d[28]), "+f"(d[29]), "+f"(d[30]), "+f"(d[31]),
      "+f"(d[32]), "+f"(d[33]), "+f"(d[34]), "+f"(d[35]), "+f"(d[36]), "+f"(d[37]), "+f"(d[38]), "+f"(d[39])
      : "l"(da), "l"(db), "r"(rel), "r"(doR), "r"(fa), "r"(pa), "r"(fb), "r"(pb), "n"(BSTEP), "r"(acc), "r"(rela) : "memory");
    else static_assert(W < 0, "variant not generated");
  }
};
template <> struct KB<192> {
  template <int W, int RC, int RA, int BSTEP> static __device__ __forceinline__ void run(float* d, uint64_t da, uint64_t db, uint32_t rel, uint32_t rela, uint32_t doR, uint32_t fa, uint32_t pa, uint32_t fb, uint32_t pb, uint32_t acc) {
    if constexpr (W == 0 && RC == 2 && RA == 0) asm volatile(
    "{\n.reg .pred p, q, r, t;\n.reg .b64 a, b;\n.reg .u32 n;\nsetp.ne.b32 t, 1, 0;\nsetp.ne.b32 r, %105, 0;\n"
    "wgmma.mma_async.sync.aligned.m64n192k16.f32.bf16.bf16 {"
      "%0, %1, %2, %3, %4, %5, %6, %7, %8, %9, %10, %11, %12, %13, %14, %15, "
      "%16, %17, %18, %19, %20, %21, %22, %23, %24, %25, %26, %27, %28, %29, %30, %31, "
      "%32, %33, %34, %35, %36, %37, %38, %39, %40, %41, %42, %43, %44, %45, %46, %47, "
      "%48, %49, %50, %51, %52, %53, %54, %55, %56, %57, %58, %59, %60, %61, %62, %63, "
      "%64, %65, %66, %67, %68, %69, %70, %71, %72, %73, %74, %75, %76, %77, %78, %79, "
      "%80, %81, %82, %83, %84, %85, %86, %87, %88, %89, %90, %91, %92, %93, %94, %95"
      "}, %96, %97, r, 1, 1, 0, 1;\n"
    "add.u64 a, %96, 2;\nadd.u64 b, %97, %104;\n"
    "wgmma.mma_async.sync.aligned.m64n192k16.f32.bf16.bf16 {"
      "%0, %1, %2, %3, %4, %5, %6, %7, %8, %9, %10, %11, %12, %13, %14, %15, "
      "%16, %17, %18, %19, %20, %21, %22, %23, %24, %25, %26, %27, %28, %29, %30, %31, "
      "%32, %33, %34, %35, %36, %37, %38, %39, %40, %41, %42, %43, %44, %45, %46, %47, "
      "%48, %49, %50, %51, %52, %53, %54, %55, %56, %57, %58, %59, %60, %61, %62, %63, "
      "%64, %65, %66, %67, %68, %69, %70, %71, %72, %73, %74, %75, %76, %77, %78, %79, "
      "%80, %81, %82, %83, %84, %85, %86, %87, %88, %89, %90, %91, %92, %93, %94, %95"
      "}, a, b, t, 1, 1, 0, 1;\n"
    "wgmma.commit_group.sync.aligned;\nwgmma.wait_group.sync.aligned 1;\n"
    "add.u64 a, %96, 4;\nadd.u64 b, %97, 2*%104;\n"
    "wgmma.mma_async.sync.aligned.m64n192k16.f32.bf16.bf16 {"
      "%0, %1, %2, %3, %4, %5, %6, %7, %8, %9, %10, %11, %12, %13, %14, %15, "
      "%16, %17, %18, %19, %20, %21, %22, %23, %24, %25, %26, %27, %28, %29, %30, %31, "
      "%32, %33, %34, %35, %36, %37, %38, %39, %40, %41, %42, %43, %44, %45, %46, %47, "
      "%48, %49, %50, %51, %52, %53, %54, %55, %56, %57, %58, %59, %60, %61, %62, %63, "
      "%64, %65, %66, %67, %68, %69, %70, %71, %72, %73, %74, %75, %76, %77, %78, %79, "
      "%80, %81, %82, %83, %84, %85, %86, %87, %88, %89, %90, %91, %92, %93, %94, %95"
      "}, a, b, t, 1, 1, 0, 1;\n"
    "setp.ne.u32 q, %99, 0;\n@q mbarrier.arrive.shared::cta.b64 _, [%98];\n@q mbarrier.arrive.shared::cta.b64 _, [%98];\n"
    "add.u64 a, %96, 6;\nadd.u64 b, %97, 3*%104;\n"
    "wgmma.mma_async.sync.aligned.m64n192k16.f32.bf16.bf16 {"
      "%0, %1, %2, %3, %4, %5, %6, %7, %8, %9, %10, %11, %12, %13, %14, %15, "
      "%16, %17, %18, %19, %20, %21, %22, %23, %24, %25, %26, %27, %28, %29, %30, %31, "
      "%32, %33, %34, %35, %36, %37, %38, %39, %40, %41, %42, %43, %44, %45, %46, %47, "
      "%48, %49, %50, %51, %52, %53, %54, %55, %56, %57, %58, %59, %60, %61, %62, %63, "
      "%64, %65, %66, %67, %68, %69, %70, %71, %72, %73, %74, %75, %76, %77, %78, %79, "
      "%80, %81, %82, %83, %84, %85, %86, %87, %88, %89, %90, %91, %92, %93, %94, %95"
      "}, a, b, t, 1, 1, 0, 1;\n"
    "wgmma.commit_group.sync.aligned;\n"
    "}\n"
      :
      "+f"(d[0]), "+f"(d[1]), "+f"(d[2]), "+f"(d[3]), "+f"(d[4]), "+f"(d[5]), "+f"(d[6]), "+f"(d[7]),
      "+f"(d[8]), "+f"(d[9]), "+f"(d[10]), "+f"(d[11]), "+f"(d[12]), "+f"(d[13]), "+f"(d[14]), "+f"(d[15]),
      "+f"(d[16]), "+f"(d[17]), "+f"(d[18]), "+f"(d[19]), "+f"(d[20]), "+f"(d[21]), "+f"(d[22]), "+f"(d[23]),
      "+f"(d[24]), "+f"(d[25]), "+f"(d[26]), "+f"(d[27]), "+f"(d[28]), "+f"(d[29]), "+f"(d[30]), "+f"(d[31]),
      "+f"(d[32]), "+f"(d[33]), "+f"(d[34]), "+f"(d[35]), "+f"(d[36]), "+f"(d[37]), "+f"(d[38]), "+f"(d[39]),
      "+f"(d[40]), "+f"(d[41]), "+f"(d[42]), "+f"(d[43]), "+f"(d[44]), "+f"(d[45]), "+f"(d[46]), "+f"(d[47]),
      "+f"(d[48]), "+f"(d[49]), "+f"(d[50]), "+f"(d[51]), "+f"(d[52]), "+f"(d[53]), "+f"(d[54]), "+f"(d[55]),
      "+f"(d[56]), "+f"(d[57]), "+f"(d[58]), "+f"(d[59]), "+f"(d[60]), "+f"(d[61]), "+f"(d[62]), "+f"(d[63]),
      "+f"(d[64]), "+f"(d[65]), "+f"(d[66]), "+f"(d[67]), "+f"(d[68]), "+f"(d[69]), "+f"(d[70]), "+f"(d[71]),
      "+f"(d[72]), "+f"(d[73]), "+f"(d[74]), "+f"(d[75]), "+f"(d[76]), "+f"(d[77]), "+f"(d[78]), "+f"(d[79]),
      "+f"(d[80]), "+f"(d[81]), "+f"(d[82]), "+f"(d[83]), "+f"(d[84]), "+f"(d[85]), "+f"(d[86]), "+f"(d[87]),
      "+f"(d[88]), "+f"(d[89]), "+f"(d[90]), "+f"(d[91]), "+f"(d[92]), "+f"(d[93]), "+f"(d[94]), "+f"(d[95])
      : "l"(da), "l"(db), "r"(rel), "r"(doR), "r"(fa), "r"(pa), "r"(fb), "r"(pb), "n"(BSTEP), "r"(acc), "r"(rela) : "memory");
    else if constexpr (W == 0 && RC == 2 && RA == 2) asm volatile(
    "{\n.reg .pred p, q, r, t;\n.reg .b64 a, b;\n.reg .u32 n;\nsetp.ne.b32 t, 1, 0;\nsetp.ne.b32 r, %105, 0;\n"
    "wgmma.mma_async.sync.aligned.m64n192k16.f32.bf16.bf16 {"
      "%0, %1, %2, %3, %4, %5, %6, %7, %8, %9, %10, %11, %12, %13, %14, %15, "
      "%16, %17, %18, %19, %20, %21, %22, %23, %24, %25, %26, %27, %28, %29, %30, %31, "
      "%32, %33, %34, %35, %36, %37, %38, %39, %40, %41, %42, %43, %44, %45, %46, %47, "
      "%48, %49, %50, %51, %52, %53, %54, %55, %56, %57, %58, %59, %60, %61, %62, %63, "
      "%64, %65, %66, %67, %68, %69, %70, %71, %72, %73, %74, %75, %76, %77, %78, %79, "
      "%80, %81, %82, %83, %84, %85, %86, %87, %88, %89, %90, %91, %92, %93, %94, %95"
      "}, %96, %97, r, 1, 1, 0, 1;\n"
    "add.u64 a, %96, 2;\nadd.u64 b, %97, %104;\n"
    "wgmma.mma_async.sync.aligned.m64n192k16.f32.bf16.bf16 {"
      "%0, %1, %2, %3, %4, %5, %6, %7, %8, %9, %10, %11, %12, %13, %14, %15, "
      "%16, %17, %18, %19, %20, %21, %22, %23, %24, %25, %26, %27, %28, %29, %30, %31, "
      "%32, %33, %34, %35, %36, %37, %38, %39, %40, %41, %42, %43, %44, %45, %46, %47, "
      "%48, %49, %50, %51, %52, %53, %54, %55, %56, %57, %58, %59, %60, %61, %62, %63, "
      "%64, %65, %66, %67, %68, %69, %70, %71, %72, %73, %74, %75, %76, %77, %78, %79, "
      "%80, %81, %82, %83, %84, %85, %86, %87, %88, %89, %90, %91, %92, %93, %94, %95"
      "}, a, b, t, 1, 1, 0, 1;\n"
    "wgmma.commit_group.sync.aligned;\nwgmma.wait_group.sync.aligned 1;\n"
    "add.u64 a, %96, 4;\nadd.u64 b, %97, 2*%104;\n"
    "wgmma.mma_async.sync.aligned.m64n192k16.f32.bf16.bf16 {"
      "%0, %1, %2, %3, %4, %5, %6, %7, %8, %9, %10, %11, %12, %13, %14, %15, "
      "%16, %17, %18, %19, %20, %21, %22, %23, %24, %25, %26, %27, %28, %29, %30, %31, "
      "%32, %33, %34, %35, %36, %37, %38, %39, %40, %41, %42, %43, %44, %45, %46, %47, "
      "%48, %49, %50, %51, %52, %53, %54, %55, %56, %57, %58, %59, %60, %61, %62, %63, "
      "%64, %65, %66, %67, %68, %69, %70, %71, %72, %73, %74, %75, %76, %77, %78, %79, "
      "%80, %81, %82, %83, %84, %85, %86, %87, %88, %89, %90, %91, %92, %93, %94, %95"
      "}, a, b, t, 1, 1, 0, 1;\n"
    "setp.ne.u32 q, %99, 0;\n@q mbarrier.arrive.shared::cta.b64 _, [%98];\n@q mbarrier.arrive.shared::cta.b64 _, [%98];\n@q mbarrier.arrive.shared::cta.b64 _, [%106];\n@q mbarrier.arrive.shared::cta.b64 _, [%106];\n"
    "add.u64 a, %96, 6;\nadd.u64 b, %97, 3*%104;\n"
    "wgmma.mma_async.sync.aligned.m64n192k16.f32.bf16.bf16 {"
      "%0, %1, %2, %3, %4, %5, %6, %7, %8, %9, %10, %11, %12, %13, %14, %15, "
      "%16, %17, %18, %19, %20, %21, %22, %23, %24, %25, %26, %27, %28, %29, %30, %31, "
      "%32, %33, %34, %35, %36, %37, %38, %39, %40, %41, %42, %43, %44, %45, %46, %47, "
      "%48, %49, %50, %51, %52, %53, %54, %55, %56, %57, %58, %59, %60, %61, %62, %63, "
      "%64, %65, %66, %67, %68, %69, %70, %71, %72, %73, %74, %75, %76, %77, %78, %79, "
      "%80, %81, %82, %83, %84, %85, %86, %87, %88, %89, %90, %91, %92, %93, %94, %95"
      "}, a, b, t, 1, 1, 0, 1;\n"
    "wgmma.commit_group.sync.aligned;\n"
    "}\n"
      :
      "+f"(d[0]), "+f"(d[1]), "+f"(d[2]), "+f"(d[3]), "+f"(d[4]), "+f"(d[5]), "+f"(d[6]), "+f"(d[7]),
      "+f"(d[8]), "+f"(d[9]), "+f"(d[10]), "+f"(d[11]), "+f"(d[12]), "+f"(d[13]), "+f"(d[14]), "+f"(d[15]),
      "+f"(d[16]), "+f"(d[17]), "+f"(d[18]), "+f"(d[19]), "+f"(d[20]), "+f"(d[21]), "+f"(d[22]), "+f"(d[23]),
      "+f"(d[24]), "+f"(d[25]), "+f"(d[26]), "+f"(d[27]), "+f"(d[28]), "+f"(d[29]), "+f"(d[30]), "+f"(d[31]),
      "+f"(d[32]), "+f"(d[33]), "+f"(d[34]), "+f"(d[35]), "+f"(d[36]), "+f"(d[37]), "+f"(d[38]), "+f"(d[39]),
      "+f"(d[40]), "+f"(d[41]), "+f"(d[42]), "+f"(d[43]), "+f"(d[44]), "+f"(d[45]), "+f"(d[46]), "+f"(d[47]),
      "+f"(d[48]), "+f"(d[49]), "+f"(d[50]), "+f"(d[51]), "+f"(d[52]), "+f"(d[53]), "+f"(d[54]), "+f"(d[55]),
      "+f"(d[56]), "+f"(d[57]), "+f"(d[58]), "+f"(d[59]), "+f"(d[60]), "+f"(d[61]), "+f"(d[62]), "+f"(d[63]),
      "+f"(d[64]), "+f"(d[65]), "+f"(d[66]), "+f"(d[67]), "+f"(d[68]), "+f"(d[69]), "+f"(d[70]), "+f"(d[71]),
      "+f"(d[72]), "+f"(d[73]), "+f"(d[74]), "+f"(d[75]), "+f"(d[76]), "+f"(d[77]), "+f"(d[78]), "+f"(d[79]),
      "+f"(d[80]), "+f"(d[81]), "+f"(d[82]), "+f"(d[83]), "+f"(d[84]), "+f"(d[85]), "+f"(d[86]), "+f"(d[87]),
      "+f"(d[88]), "+f"(d[89]), "+f"(d[90]), "+f"(d[91]), "+f"(d[92]), "+f"(d[93]), "+f"(d[94]), "+f"(d[95])
      : "l"(da), "l"(db), "r"(rel), "r"(doR), "r"(fa), "r"(pa), "r"(fb), "r"(pb), "n"(BSTEP), "r"(acc), "r"(rela) : "memory");
    else if constexpr (W == 1 && RC == 2 && RA == 2) asm volatile(
    "{\n.reg .pred p, q, r, t;\n.reg .b64 a, b;\n.reg .u32 n;\nsetp.ne.b32 t, 1, 0;\nsetp.ne.b32 r, %105, 0;\n"
    "wgmma.mma_async.sync.aligned.m64n192k16.f32.bf16.bf16 {"
      "%0, %1, %2, %3, %4, %5, %6, %7, %8, %9, %10, %11, %12, %13, %14, %15, "
      "%16, %17, %18, %19, %20, %21, %22, %23, %24, %25, %26, %27, %28, %29, %30, %31, "
      "%32, %33, %34, %35, %36, %37, %38, %39, %40, %41, %42, %43, %44, %45, %46, %47, "
      "%48, %49, %50, %51, %52, %53, %54, %55, %56, %57, %58, %59, %60, %61, %62, %63, "
      "%64, %65, %66, %67, %68, %69, %70, %71, %72, %73, %74, %75, %76, %77, %78, %79, "
      "%80, %81, %82, %83, %84, %85, %86, %87, %88, %89, %90, %91, %92, %93, %94, %95"
      "}, %96, %97, r, 1, 1, 0, 1;\n"
    "add.u64 a, %96, 2;\nadd.u64 b, %97, %104;\n"
    "wgmma.mma_async.sync.aligned.m64n192k16.f32.bf16.bf16 {"
      "%0, %1, %2, %3, %4, %5, %6, %7, %8, %9, %10, %11, %12, %13, %14, %15, "
      "%16, %17, %18, %19, %20, %21, %22, %23, %24, %25, %26, %27, %28, %29, %30, %31, "
      "%32, %33, %34, %35, %36, %37, %38, %39, %40, %41, %42, %43, %44, %45, %46, %47, "
      "%48, %49, %50, %51, %52, %53, %54, %55, %56, %57, %58, %59, %60, %61, %62, %63, "
      "%64, %65, %66, %67, %68, %69, %70, %71, %72, %73, %74, %75, %76, %77, %78, %79, "
      "%80, %81, %82, %83, %84, %85, %86, %87, %88, %89, %90, %91, %92, %93, %94, %95"
      "}, a, b, t, 1, 1, 0, 1;\n"
    "wgmma.commit_group.sync.aligned;\nwgmma.wait_group.sync.aligned 1;\n"
    "add.u64 a, %96, 4;\nadd.u64 b, %97, 2*%104;\n"
    "wgmma.mma_async.sync.aligned.m64n192k16.f32.bf16.bf16 {"
      "%0, %1, %2, %3, %4, %5, %6, %7, %8, %9, %10, %11, %12, %13, %14, %15, "
      "%16, %17, %18, %19, %20, %21, %22, %23, %24, %25, %26, %27, %28, %29, %30, %31, "
      "%32, %33, %34, %35, %36, %37, %38, %39, %40, %41, %42, %43, %44, %45, %46, %47, "
      "%48, %49, %50, %51, %52, %53, %54, %55, %56, %57, %58, %59, %60, %61, %62, %63, "
      "%64, %65, %66, %67, %68, %69, %70, %71, %72, %73, %74, %75, %76, %77, %78, %79, "
      "%80, %81, %82, %83, %84, %85, %86, %87, %88, %89, %90, %91, %92, %93, %94, %95"
      "}, a, b, t, 1, 1, 0, 1;\n"
    "setp.ne.u32 q, %99, 0;\n@q mbarrier.arrive.shared::cta.b64 _, [%98];\n@q mbarrier.arrive.shared::cta.b64 _, [%98];\n@q mbarrier.arrive.shared::cta.b64 _, [%106];\n@q mbarrier.arrive.shared::cta.b64 _, [%106];\n"
    "mbarrier.test_wait.parity.shared::cta.b64 p, [%102], %103;\n"
    "add.u64 a, %96, 6;\nadd.u64 b, %97, 3*%104;\n"
    "wgmma.mma_async.sync.aligned.m64n192k16.f32.bf16.bf16 {"
      "%0, %1, %2, %3, %4, %5, %6, %7, %8, %9, %10, %11, %12, %13, %14, %15, "
      "%16, %17, %18, %19, %20, %21, %22, %23, %24, %25, %26, %27, %28, %29, %30, %31, "
      "%32, %33, %34, %35, %36, %37, %38, %39, %40, %41, %42, %43, %44, %45, %46, %47, "
      "%48, %49, %50, %51, %52, %53, %54, %55, %56, %57, %58, %59, %60, %61, %62, %63, "
      "%64, %65, %66, %67, %68, %69, %70, %71, %72, %73, %74, %75, %76, %77, %78, %79, "
      "%80, %81, %82, %83, %84, %85, %86, %87, %88, %89, %90, %91, %92, %93, %94, %95"
      "}, a, b, t, 1, 1, 0, 1;\n"
    "wgmma.commit_group.sync.aligned;\n"
    "@p bra.uni DN;\nmov.u32 n, 0;\nWT: mbarrier.try_wait.parity.shared::cta.b64 p, [%102], %103;\n@p bra.uni DN;\nadd.u32 n, n, 1;\nsetp.lt.u32 p, n, 0x100000;\n@p bra.uni WT;\nDN:\n"
    "}\n"
      :
      "+f"(d[0]), "+f"(d[1]), "+f"(d[2]), "+f"(d[3]), "+f"(d[4]), "+f"(d[5]), "+f"(d[6]), "+f"(d[7]),
      "+f"(d[8]), "+f"(d[9]), "+f"(d[10]), "+f"(d[11]), "+f"(d[12]), "+f"(d[13]), "+f"(d[14]), "+f"(d[15]),
      "+f"(d[16]), "+f"(d[17]), "+f"(d[18]), "+f"(d[19]), "+f"(d[20]), "+f"(d[21]), "+f"(d[22]), "+f"(d[23]),
      "+f"(d[24]), "+f"(d[25]), "+f"(d[26]), "+f"(d[27]), "+f"(d[28]), "+f"(d[29]), "+f"(d[30]), "+f"(d[31]),
      "+f"(d[32]), "+f"(d[33]), "+f"(d[34]), "+f"(d[35]), "+f"(d[36]), "+f"(d[37]), "+f"(d[38]), "+f"(d[39]),
      "+f"(d[40]), "+f"(d[41]), "+f"(d[42]), "+f"(d[43]), "+f"(d[44]), "+f"(d[45]), "+f"(d[46]), "+f"(d[47]),
      "+f"(d[48]), "+f"(d[49]), "+f"(d[50]), "+f"(d[51]), "+f"(d[52]), "+f"(d[53]), "+f"(d[54]), "+f"(d[55]),
      "+f"(d[56]), "+f"(d[57]), "+f"(d[58]), "+f"(d[59]), "+f"(d[60]), "+f"(d[61]), "+f"(d[62]), "+f"(d[63]),
      "+f"(d[64]), "+f"(d[65]), "+f"(d[66]), "+f"(d[67]), "+f"(d[68]), "+f"(d[69]), "+f"(d[70]), "+f"(d[71]),
      "+f"(d[72]), "+f"(d[73]), "+f"(d[74]), "+f"(d[75]), "+f"(d[76]), "+f"(d[77]), "+f"(d[78]), "+f"(d[79]),
      "+f"(d[80]), "+f"(d[81]), "+f"(d[82]), "+f"(d[83]), "+f"(d[84]), "+f"(d[85]), "+f"(d[86]), "+f"(d[87]),
      "+f"(d[88]), "+f"(d[89]), "+f"(d[90]), "+f"(d[91]), "+f"(d[92]), "+f"(d[93]), "+f"(d[94]), "+f"(d[95])
      : "l"(da), "l"(db), "r"(rel), "r"(doR), "r"(fa), "r"(pa), "r"(fb), "r"(pb), "n"(BSTEP), "r"(acc), "r"(rela) : "memory");
    else if constexpr (W == 2 && RC == 2 && RA == 0) asm volatile(
    "{\n.reg .pred p, q, r, t;\n.reg .b64 a, b;\n.reg .u32 n;\nsetp.ne.b32 t, 1, 0;\nsetp.ne.b32 r, %105, 0;\n"
    "wgmma.mma_async.sync.aligned.m64n192k16.f32.bf16.bf16 {"
      "%0, %1, %2, %3, %4, %5, %6, %7, %8, %9, %10, %11, %12, %13, %14, %15, "
      "%16, %17, %18, %19, %20, %21, %22, %23, %24, %25, %26, %27, %28, %29, %30, %31, "
      "%32, %33, %34, %35, %36, %37, %38, %39, %40, %41, %42, %43, %44, %45, %46, %47, "
      "%48, %49, %50, %51, %52, %53, %54, %55, %56, %57, %58, %59, %60, %61, %62, %63, "
      "%64, %65, %66, %67, %68, %69, %70, %71, %72, %73, %74, %75, %76, %77, %78, %79, "
      "%80, %81, %82, %83, %84, %85, %86, %87, %88, %89, %90, %91, %92, %93, %94, %95"
      "}, %96, %97, r, 1, 1, 0, 1;\n"
    "add.u64 a, %96, 2;\nadd.u64 b, %97, %104;\n"
    "wgmma.mma_async.sync.aligned.m64n192k16.f32.bf16.bf16 {"
      "%0, %1, %2, %3, %4, %5, %6, %7, %8, %9, %10, %11, %12, %13, %14, %15, "
      "%16, %17, %18, %19, %20, %21, %22, %23, %24, %25, %26, %27, %28, %29, %30, %31, "
      "%32, %33, %34, %35, %36, %37, %38, %39, %40, %41, %42, %43, %44, %45, %46, %47, "
      "%48, %49, %50, %51, %52, %53, %54, %55, %56, %57, %58, %59, %60, %61, %62, %63, "
      "%64, %65, %66, %67, %68, %69, %70, %71, %72, %73, %74, %75, %76, %77, %78, %79, "
      "%80, %81, %82, %83, %84, %85, %86, %87, %88, %89, %90, %91, %92, %93, %94, %95"
      "}, a, b, t, 1, 1, 0, 1;\n"
    "wgmma.commit_group.sync.aligned;\nwgmma.wait_group.sync.aligned 1;\n"
    "add.u64 a, %96, 4;\nadd.u64 b, %97, 2*%104;\n"
    "wgmma.mma_async.sync.aligned.m64n192k16.f32.bf16.bf16 {"
      "%0, %1, %2, %3, %4, %5, %6, %7, %8, %9, %10, %11, %12, %13, %14, %15, "
      "%16, %17, %18, %19, %20, %21, %22, %23, %24, %25, %26, %27, %28, %29, %30, %31, "
      "%32, %33, %34, %35, %36, %37, %38, %39, %40, %41, %42, %43, %44, %45, %46, %47, "
      "%48, %49, %50, %51, %52, %53, %54, %55, %56, %57, %58, %59, %60, %61, %62, %63, "
      "%64, %65, %66, %67, %68, %69, %70, %71, %72, %73, %74, %75, %76, %77, %78, %79, "
      "%80, %81, %82, %83, %84, %85, %86, %87, %88, %89, %90, %91, %92, %93, %94, %95"
      "}, a, b, t, 1, 1, 0, 1;\n"
    "setp.ne.u32 q, %99, 0;\n@q mbarrier.arrive.shared::cta.b64 _, [%98];\n@q mbarrier.arrive.shared::cta.b64 _, [%98];\n"
    "mbarrier.test_wait.parity.shared::cta.b64 p, [%102], %103;\n"
    "mbarrier.test_wait.parity.shared::cta.b64 r, [%100], %101;\nand.pred p, p, r;\n"
    "add.u64 a, %96, 6;\nadd.u64 b, %97, 3*%104;\n"
    "wgmma.mma_async.sync.aligned.m64n192k16.f32.bf16.bf16 {"
      "%0, %1, %2, %3, %4, %5, %6, %7, %8, %9, %10, %11, %12, %13, %14, %15, "
      "%16, %17, %18, %19, %20, %21, %22, %23, %24, %25, %26, %27, %28, %29, %30, %31, "
      "%32, %33, %34, %35, %36, %37, %38, %39, %40, %41, %42, %43, %44, %45, %46, %47, "
      "%48, %49, %50, %51, %52, %53, %54, %55, %56, %57, %58, %59, %60, %61, %62, %63, "
      "%64, %65, %66, %67, %68, %69, %70, %71, %72, %73, %74, %75, %76, %77, %78, %79, "
      "%80, %81, %82, %83, %84, %85, %86, %87, %88, %89, %90, %91, %92, %93, %94, %95"
      "}, a, b, t, 1, 1, 0, 1;\n"
    "wgmma.commit_group.sync.aligned;\n"
    "@p bra.uni DN;\nmov.u32 n, 0;\nWT: mbarrier.try_wait.parity.shared::cta.b64 p, [%102], %103;\nmbarrier.try_wait.parity.shared::cta.b64 r, [%100], %101;\nand.pred p, p, r;\n@p bra.uni DN;\nadd.u32 n, n, 1;\nsetp.lt.u32 p, n, 0x100000;\n@p bra.uni WT;\nDN:\n"
    "}\n"
      :
      "+f"(d[0]), "+f"(d[1]), "+f"(d[2]), "+f"(d[3]), "+f"(d[4]), "+f"(d[5]), "+f"(d[6]), "+f"(d[7]),
      "+f"(d[8]), "+f"(d[9]), "+f"(d[10]), "+f"(d[11]), "+f"(d[12]), "+f"(d[13]), "+f"(d[14]), "+f"(d[15]),
      "+f"(d[16]), "+f"(d[17]), "+f"(d[18]), "+f"(d[19]), "+f"(d[20]), "+f"(d[21]), "+f"(d[22]), "+f"(d[23]),
      "+f"(d[24]), "+f"(d[25]), "+f"(d[26]), "+f"(d[27]), "+f"(d[28]), "+f"(d[29]), "+f"(d[30]), "+f"(d[31]),
      "+f"(d[32]), "+f"(d[33]), "+f"(d[34]), "+f"(d[35]), "+f"(d[36]), "+f"(d[37]), "+f"(d[38]), "+f"(d[39]),
      "+f"(d[40]), "+f"(d[41]), "+f"(d[42]), "+f"(d[43]), "+f"(d[44]), "+f"(d[45]), "+f"(d[46]), "+f"(d[47]),
      "+f"(d[48]), "+f"(d[49]), "+f"(d[50]), "+f"(d[51]), "+f"(d[52]), "+f"(d[53]), "+f"(d[54]), "+f"(d[55]),
      "+f"(d[56]), "+f"(d[57]), "+f"(d[58]), "+f"(d[59]), "+f"(d[60]), "+f"(d[61]), "+f"(d[62]), "+f"(d[63]),
      "+f"(d[64]), "+f"(d[65]), "+f"(d[66]), "+f"(d[67]), "+f"(d[68]), "+f"(d[69]), "+f"(d[70]), "+f"(d[71]),
      "+f"(d[72]), "+f"(d[73]), "+f"(d[74]), "+f"(d[75]), "+f"(d[76]), "+f"(d[77]), "+f"(d[78]), "+f"(d[79]),
      "+f"(d[80]), "+f"(d[81]), "+f"(d[82]), "+f"(d[83]), "+f"(d[84]), "+f"(d[85]), "+f"(d[86]), "+f"(d[87]),
      "+f"(d[88]), "+f"(d[89]), "+f"(d[90]), "+f"(d[91]), "+f"(d[92]), "+f"(d[93]), "+f"(d[94]), "+f"(d[95])
      : "l"(da), "l"(db), "r"(rel), "r"(doR), "r"(fa), "r"(pa), "r"(fb), "r"(pb), "n"(BSTEP), "r"(acc), "r"(rela) : "memory");
    else if constexpr (W == 2 && RC == 2 && RA == 2) asm volatile(
    "{\n.reg .pred p, q, r, t;\n.reg .b64 a, b;\n.reg .u32 n;\nsetp.ne.b32 t, 1, 0;\nsetp.ne.b32 r, %105, 0;\n"
    "wgmma.mma_async.sync.aligned.m64n192k16.f32.bf16.bf16 {"
      "%0, %1, %2, %3, %4, %5, %6, %7, %8, %9, %10, %11, %12, %13, %14, %15, "
      "%16, %17, %18, %19, %20, %21, %22, %23, %24, %25, %26, %27, %28, %29, %30, %31, "
      "%32, %33, %34, %35, %36, %37, %38, %39, %40, %41, %42, %43, %44, %45, %46, %47, "
      "%48, %49, %50, %51, %52, %53, %54, %55, %56, %57, %58, %59, %60, %61, %62, %63, "
      "%64, %65, %66, %67, %68, %69, %70, %71, %72, %73, %74, %75, %76, %77, %78, %79, "
      "%80, %81, %82, %83, %84, %85, %86, %87, %88, %89, %90, %91, %92, %93, %94, %95"
      "}, %96, %97, r, 1, 1, 0, 1;\n"
    "add.u64 a, %96, 2;\nadd.u64 b, %97, %104;\n"
    "wgmma.mma_async.sync.aligned.m64n192k16.f32.bf16.bf16 {"
      "%0, %1, %2, %3, %4, %5, %6, %7, %8, %9, %10, %11, %12, %13, %14, %15, "
      "%16, %17, %18, %19, %20, %21, %22, %23, %24, %25, %26, %27, %28, %29, %30, %31, "
      "%32, %33, %34, %35, %36, %37, %38, %39, %40, %41, %42, %43, %44, %45, %46, %47, "
      "%48, %49, %50, %51, %52, %53, %54, %55, %56, %57, %58, %59, %60, %61, %62, %63, "
      "%64, %65, %66, %67, %68, %69, %70, %71, %72, %73, %74, %75, %76, %77, %78, %79, "
      "%80, %81, %82, %83, %84, %85, %86, %87, %88, %89, %90, %91, %92, %93, %94, %95"
      "}, a, b, t, 1, 1, 0, 1;\n"
    "wgmma.commit_group.sync.aligned;\nwgmma.wait_group.sync.aligned 1;\n"
    "add.u64 a, %96, 4;\nadd.u64 b, %97, 2*%104;\n"
    "wgmma.mma_async.sync.aligned.m64n192k16.f32.bf16.bf16 {"
      "%0, %1, %2, %3, %4, %5, %6, %7, %8, %9, %10, %11, %12, %13, %14, %15, "
      "%16, %17, %18, %19, %20, %21, %22, %23, %24, %25, %26, %27, %28, %29, %30, %31, "
      "%32, %33, %34, %35, %36, %37, %38, %39, %40, %41, %42, %43, %44, %45, %46, %47, "
      "%48, %49, %50, %51, %52, %53, %54, %55, %56, %57, %58, %59, %60, %61, %62, %63, "
      "%64, %65, %66, %67, %68, %69, %70, %71, %72, %73, %74, %75, %76, %77, %78, %79, "
      "%80, %81, %82, %83, %84, %85, %86, %87, %88, %89, %90, %91, %92, %93, %94, %95"
      "}, a, b, t, 1, 1, 0, 1;\n"
    "setp.ne.u32 q, %99, 0;\n@q mbarrier.arrive.shared::cta.b64 _, [%98];\n@q mbarrier.arrive.shared::cta.b64 _, [%98];\n@q mbarrier.arrive.shared::cta.b64 _, [%106];\n@q mbarrier.arrive.shared::cta.b64 _, [%106];\n"
    "mbarrier.test_wait.parity.shared::cta.b64 p, [%102], %103;\n"
    "mbarrier.test_wait.parity.shared::cta.b64 r, [%100], %101;\nand.pred p, p, r;\n"
    "add.u64 a, %96, 6;\nadd.u64 b, %97, 3*%104;\n"
    "wgmma.mma_async.sync.aligned.m64n192k16.f32.bf16.bf16 {"
      "%0, %1, %2, %3, %4, %5, %6, %7, %8, %9, %10, %11, %12, %13, %14, %15, "
      "%16, %17, %18, %19, %20, %21, %22, %23, %24, %25, %26, %27, %28, %29, %30, %31, "
      "%32, %33, %34, %35, %36, %37, %38, %39, %40, %41, %42, %43, %44, %45, %46, %47, "
      "%48, %49, %50, %51, %52, %53, %54, %55, %56, %57, %58, %59, %60, %61, %62, %63, "
      "%64, %65, %66, %67, %68, %69, %70, %71, %72, %73, %74, %75, %76, %77, %78, %79, "
      "%80, %81, %82, %83, %84, %85, %86, %87, %88, %89, %90, %91, %92, %93, %94, %95"
      "}, a, b, t, 1, 1, 0, 1;\n"
    "wgmma.commit_group.sync.aligned;\n"
    "@p bra.uni DN;\nmov.u32 n, 0;\nWT: mbarrier.try_wait.parity.shared::cta.b64 p, [%102], %103;\nmbarrier.try_wait.parity.shared::cta.b64 r, [%100], %101;\nand.pred p, p, r;\n@p bra.uni DN;\nadd.u32 n, n, 1;\nsetp.lt.u32 p, n, 0x100000;\n@p bra.uni WT;\nDN:\n"
    "}\n"
      :
      "+f"(d[0]), "+f"(d[1]), "+f"(d[2]), "+f"(d[3]), "+f"(d[4]), "+f"(d[5]), "+f"(d[6]), "+f"(d[7]),
      "+f"(d[8]), "+f"(d[9]), "+f"(d[10]), "+f"(d[11]), "+f"(d[12]), "+f"(d[13]), "+f"(d[14]), "+f"(d[15]),
      "+f"(d[16]), "+f"(d[17]), "+f"(d[18]), "+f"(d[19]), "+f"(d[20]), "+f"(d[21]), "+f"(d[22]), "+f"(d[23]),
      "+f"(d[24]), "+f"(d[25]), "+f"(d[26]), "+f"(d[27]), "+f"(d[28]), "+f"(d[29]), "+f"(d[30]), "+f"(d[31]),
      "+f"(d[32]), "+f"(d[33]), "+f"(d[34]), "+f"(d[35]), "+f"(d[36]), "+f"(d[37]), "+f"(d[38]), "+f"(d[39]),
      "+f"(d[40]), "+f"(d[41]), "+f"(d[42]), "+f"(d[43]), "+f"(d[44]), "+f"(d[45]), "+f"(d[46]), "+f"(d[47]),
      "+f"(d[48]), "+f"(d[49]), "+f"(d[50]), "+f"(d[51]), "+f"(d[52]), "+f"(d[53]), "+f"(d[54]), "+f"(d[55]),
      "+f"(d[56]), "+f"(d[57]), "+f"(d[58]), "+f"(d[59]), "+f"(d[60]), "+f"(d[61]), "+f"(d[62]), "+f"(d[63]),
      "+f"(d[64]), "+f"(d[65]), "+f"(d[66]), "+f"(d[67]), "+f"(d[68]), "+f"(d[69]), "+f"(d[70]), "+f"(d[71]),
      "+f"(d[72]), "+f"(d[73]), "+f"(d[74]), "+f"(d[75]), "+f"(d[76]), "+f"(d[77]), "+f"(d[78]), "+f"(d[79]),
      "+f"(d[80]), "+f"(d[81]), "+f"(d[82]), "+f"(d[83]), "+f"(d[84]), "+f"(d[85]), "+f"(d[86]), "+f"(d[87]),
      "+f"(d[88]), "+f"(d[89]), "+f"(d[90]), "+f"(d[91]), "+f"(d[92]), "+f"(d[93]), "+f"(d[94]), "+f"(d[95])
      : "l"(da), "l"(db), "r"(rel), "r"(doR), "r"(fa), "r"(pa), "r"(fb), "r"(pb), "n"(BSTEP), "r"(acc), "r"(rela) : "memory");
    else static_assert(W < 0, "variant not generated");
  }
};

#define NPRE 2
#define KV_T0 4000
#define KV2T 2000
#define XSD 400
#define CSD 600
#define ZW 300
#define TP_T 5000
#define PF2_D 200
#define PF_D 600
#define LKI 14
#define LEAD 4
#define HOLDA 30
#define HOLDB 28
#define HD 100
#define YD 600
#define HP0 3500
#define HPD 450
#define NSLEEP 100
#define MAP 4
#define EARLY 0

namespace {

constexpr int kS = 2048, kD = 640, kF = 1536;
constexpr int A_SLOT = 8192, B_SLOT = 24576, W_SLOT = 20480;
constexpr int OFF_A = 0;
constexpr int OFF_B = OFF_A + 10 * A_SLOT;
constexpr int XB_PL = 2112;
constexpr int CV_KE = 4224, CV_KO = CV_KE + 4160;
constexpr int CV_SZ = CV_KO + 4160;
constexpr int OFF_CV = OFF_B + 5 * B_SLOT;
constexpr int OFF_CS = OFF_CV + 2 * CV_SZ;
constexpr int OFF_XS = OFF_CS + 1536;
constexpr int OFF_BAR = OFF_XS + 512;
constexpr int SMEM_BYTES = OFF_BAR + 512;
static_assert(SMEM_BYTES <= 232448, "smem");
constexpr int OFF_RT = OFF_CS + 768;
constexpr int BAR_AF = OFF_BAR, BAR_BF = OFF_BAR + 8 * 10, BAR_WF = OFF_BAR + 8 * 15, BAR_ST = OFF_BAR + 8 * 21, BAR_XF = OFF_BAR + 8 * 23;
constexpr int BAR_ZP = OFF_BAR + 8 * 25, BAR_DUMMY = OFF_BAR + 8 * 27, BAR_PART = OFF_BAR + 8 * 28, BAR_WO = OFF_BAR + 8 * 29;
constexpr int BAR_YT = OFF_BAR + 8 * 30, BAR_KV2 = OFF_BAR + 8 * 31, BAR_XS = OFF_BAR + 8 * 32, BAR_HOLD = OFF_BAR + 8 * 33, BAR_ZG = OFF_BAR + 8 * 34;
constexpr int OFF_TAG = OFF_BAR + 8 * 35;
constexpr int BAR_HV = OFF_BAR + 8 * 36;
constexpr int BAR_HR = BAR_HV + 64, BAR_B2 = OFF_BAR + 8 * 26;
constexpr int BAR_XL = OFF_CS - 16;
constexpr int BAR_AE = OFF_BAR + 8 * 45, BAR_BE = OFF_BAR + 8 * 53, BAR_WE = OFF_BAR + 8 * 58;
constexpr int NB_WG = 1, NB_G1 = 3, NB_WO = 4, NB_CD = 5, NB_Z = 6, NB_C = 7, NB_KU = 8, NB_SV = 9, NB_KF = 12, NB_G1D = 13, NB_KU2 = 14, NB_KL = 15;

#define NB_SV2(h) ((h) ? NB_KU2 : NB_KU)

constexpr int CNT_KV = 0, CNT_WO = 4, CNT_Z = 8;
struct Scratch {
  uint8_t kvx[kD * 4096];
  uint8_t z2[4 * 32 * 24576];
  uint8_t h[32 * 12 * 8192];
  uint8_t wo[4 * 12 * 20480];
  uint8_t y[kD * 4096];
  uint4 zstat[32 * 128];
  uint2 xstat[kS];
  uint32_t colsum[kF];
  uint32_t cnt[32];
  uint32_t hflag[32 * 32];
  uint32_t epoch[136];

};
__device__ __align__(1024) Scratch g_scr;
#define TSP
#define TSA
#define TR(i)
#define STAMP(i)
#define STAMPE(i)
#define STAMP2(i)
#define STAMPW(i)

struct Params {
  Scratch* scr;
  int by_smid;
  const __nv_bfloat16 *x, *k, *v, *shift, *ssmk, *ssmD, *wsp, *bsp, *wout;
  __nv_bfloat16* out;
  CUtensorMap tmX, tmW, tmWsp, tmY, tmKV;
  uint16_t job[132];
};

__device__ __forceinline__ uint64_t mkdesc(uint32_t addr, uint32_t lbo, uint32_t sbo, uint32_t swz) {
  return (uint64_t)((addr & 0x3FFFF) >> 4) | ((uint64_t)(lbo >> 4) << 16) | ((uint64_t)(sbo >> 4) << 32) | ((uint64_t)swz << 62);
}
#define WG_FENCE() asm volatile("wgmma.fence.sync.aligned;" ::: "memory")
#define WG_COMMIT() asm volatile("wgmma.commit_group.sync.aligned;" ::: "memory")
#define WG_WAIT(n) asm volatile("wgmma.wait_group.sync.aligned %0;" ::"n"(n) : "memory")
template <int N> __device__ __forceinline__ void acc_fence(float* d) {
#pragma unroll
  for (int i = 0; i < N; i++) asm volatile("" : "+f"(d[i])::"memory");
}
__device__ __forceinline__ void mbar_init(uint32_t bar, int cnt) { asm volatile("mbarrier.init.shared::cta.b64 [%0], %1;" ::"r"(bar), "r"(cnt) : "memory"); }
__device__ __forceinline__ void mbar_expect(uint32_t bar, uint32_t bytes) { asm volatile("mbarrier.arrive.expect_tx.shared::cta.b64 _, [%0], %1;" ::"r"(bar), "r"(bytes) : "memory"); }
__device__ __forceinline__ void mbar_arrive(uint32_t bar) { asm volatile("mbarrier.arrive.shared::cta.b64 _, [%0];" ::"r"(bar) : "memory"); }
__device__ __forceinline__ void mbar_arrive_if(uint32_t bar, bool c) {
  asm volatile("{\n.reg .pred p;\nsetp.ne.u32 p, %1, 0;\n@p mbarrier.arrive.shared::cta.b64 _, [%0];\n}\n" ::"r"(bar), "r"((uint32_t)c) : "memory");
}
__device__ __forceinline__ bool mbar_try(uint32_t bar, uint32_t parity) {
  uint32_t ok;
  asm volatile("{\n.reg .pred p;\nmbarrier.try_wait.parity.shared::cta.b64 p, [%1], %2;\nselp.u32 %0, 1, 0, p;\n}\n" : "=r"(ok) : "r"(bar), "r"(parity) : "memory");
  return ok;
}
__device__ __forceinline__ void die() { asm volatile("st.volatile.global.u32 [%0], %1;" ::"l"(0ull), "r"(0) : "memory"); }
template <bool G = false> __device__ __forceinline__ void spin_guard(uint32_t& n, uint32_t = 0) { if (G && ++n == (1u << 20)) die(); }
template <bool G = false> __device__ __forceinline__ void mbar_wait(uint32_t bar, uint32_t parity) {
  uint32_t t0 = 0;
#pragma unroll 1
  while (!mbar_try(bar, parity)) spin_guard<G>(t0, bar);
}
__device__ __forceinline__ void mbar_wait2(uint32_t b0, uint32_t p0, uint32_t b1, uint32_t p1) { mbar_wait(b0, p0); mbar_wait(b1, p1); }
__device__ __forceinline__ int tid_now() { int v; asm volatile("mov.u32 %0, %%tid.x;" : "=r"(v)); return v & 127; }
__device__ __forceinline__ bool elect_one() {
  uint32_t p;
  asm volatile("{\n.reg .pred P;\nelect.sync _|P, 0xffffffff;\nselp.u32 %0, 1, 0, P;\n}\n" : "=r"(p));
  return p;
}
__device__ __forceinline__ void bar_sync(int id, int n) { asm volatile("bar.sync %0, %1;" ::"r"(id), "r"(n) : "memory"); }
__device__ __forceinline__ void bar_arrive(int id, int n) { asm volatile("bar.arrive %0, %1;" ::"r"(id), "r"(n) : "memory"); }
__device__ __forceinline__ void fence_async_smem() { asm volatile("fence.proxy.async.shared::cta;" ::: "memory"); }
__device__ __forceinline__ void bulk_g2s(uint32_t dst, const void* src, uint32_t bytes, uint32_t bar) {
  asm volatile("cp.async.bulk.shared::cluster.global.mbarrier::complete_tx::bytes [%0], [%1], %2, [%3];" ::"r"(dst), "l"(src), "r"(bytes), "r"(bar) : "memory");
}
__device__ __forceinline__ void bulk_s2g(void* dst, uint32_t src, uint32_t bytes) {
  asm volatile("cp.async.bulk.global.shared::cta.bulk_group [%0], [%1], %2;" ::"l"(dst), "r"(src), "r"(bytes) : "memory");
}
__device__ __forceinline__ void tma2d(uint32_t dst, const CUtensorMap* m, int c0, int c1, uint32_t bar) {
  asm volatile("cp.async.bulk.tensor.2d.shared::cluster.global.mbarrier::complete_tx::bytes [%0], [%1, {%3, %4}], [%2];" ::"r"(dst), "l"(m), "r"(bar), "r"(c0), "r"(c1) : "memory");
}
__device__ __forceinline__ void tma3d(uint32_t dst, const CUtensorMap* m, int c0, int c1, int c2, uint32_t bar) {
  asm volatile("cp.async.bulk.tensor.3d.shared::cluster.global.mbarrier::complete_tx::bytes [%0], [%1, {%3, %4, %5}], [%2];" ::"r"(dst), "l"(m), "r"(bar), "r"(c0), "r"(c1), "r"(c2) : "memory");
}
__device__ __forceinline__ uint4 ld_ll4(const void* p) {
  uint64_t a, b;
  asm volatile("ld.relaxed.gpu.global.v2.u64 {%0,%1}, [%2];" : "=l"(a), "=l"(b) : "l"(p) : "memory");
  return make_uint4((uint32_t)a, (uint32_t)(a >> 32), (uint32_t)b, (uint32_t)(b >> 32));
}
__device__ __forceinline__ void st_ll4(void* p, uint32_t a, uint32_t b, uint32_t c, uint32_t d) {
  asm volatile("st.relaxed.gpu.global.v2.u64 [%0], {%1,%2};" ::"l"(p), "l"(a | ((uint64_t)b << 32)), "l"(c | ((uint64_t)d << 32)) : "memory");
}
__device__ __forceinline__ void st_ll2(void* p, uint32_t a, uint32_t b) { asm volatile("st.relaxed.gpu.global.u64 [%0], %1;" ::"l"(p), "l"(a | ((uint64_t)b << 32)) : "memory"); }
__device__ __forceinline__ void wgmma_colsum(float* d, uint64_t da, uint64_t db) {
  asm volatile("{\n.reg .pred p;\nsetp.ne.b32 p, 1, 0;\nwgmma.mma_async.sync.aligned.m64n8k16.f32.bf16.bf16 {%0, %1, %2, %3}, %4, %5, p, 1, 1, 1, 0;\n}\n"
               : "+f"(d[0]), "+f"(d[1]), "+f"(d[2]), "+f"(d[3]) : "l"(da), "l"(db));
}
__device__ __forceinline__ void prefetch_l2(const void* p) { asm volatile("prefetch.global.L2 [%0];" ::"l"(p)); }
template <bool SLEEP = true> __device__ __forceinline__ void pace(uint32_t& t, uint32_t dt) {
  t += dt;
  while ((int32_t)((uint32_t)clock() - t) < 0) { if (SLEEP) __nanosleep(NSLEEP); }
}
__device__ __forceinline__ void red_release(uint32_t* p) { asm volatile("red.release.gpu.global.add.u32 [%0], 1;" ::"l"(p) : "memory"); }
__device__ __forceinline__ uint4 ldg4(const void* p) { uint4 v; asm volatile("ld.global.v4.u32 {%0,%1,%2,%3}, [%4];" : "=r"(v.x), "=r"(v.y), "=r"(v.z), "=r"(v.w) : "l"(p) : "memory"); return v; }
__device__ __forceinline__ uint32_t ldg1(const void* p) { uint32_t v; asm volatile("ld.global.u32 %0, [%1];" : "=r"(v) : "l"(p) : "memory"); return v; }
__device__ __forceinline__ void stg4_if(void* p, uint32_t a, uint32_t b, uint32_t c, uint32_t d, bool on) {
  asm volatile("{\n.reg .pred p;\nsetp.ne.u32 p, %5, 0;\n@p st.global.v4.u32 [%0], {%1,%2,%3,%4};\n}\n" ::"l"(p), "r"(a), "r"(b), "r"(c), "r"(d), "r"((uint32_t)on) : "memory");
}
template <int OFF> __device__ __forceinline__ uint32_t lds32(uint32_t a) { uint32_t v; asm volatile("ld.shared.u32 %0, [%1+%2];" : "=r"(v) : "r"(a), "n"(OFF)); return v; }
__device__ __forceinline__ uint4 lds128(uint32_t a) { uint4 v; asm volatile("ld.shared.v4.u32 {%0,%1,%2,%3}, [%4];" : "=r"(v.x), "=r"(v.y), "=r"(v.z), "=r"(v.w) : "r"(a) : "memory"); return v; }
__device__ __forceinline__ float2 lds64f(uint32_t a) { float2 v; asm volatile("ld.shared.v2.f32 {%0,%1}, [%2];" : "=f"(v.x), "=f"(v.y) : "r"(a) : "memory"); return v; }
__device__ __forceinline__ void sts64f(uint32_t a, float x, float y) { asm volatile("st.shared.v2.f32 [%0], {%1,%2};" ::"r"(a), "f"(x), "f"(y) : "memory"); }
__device__ __forceinline__ void sts32(uint32_t a, uint32_t x) { asm volatile("st.shared.u32 [%0], %1;" ::"r"(a), "r"(x) : "memory"); }
__device__ __forceinline__ void sts128(uint32_t a, uint32_t x, uint32_t y, uint32_t z, uint32_t w) { asm volatile("st.shared.v4.u32 [%0], {%1,%2,%3,%4};" ::"r"(a), "r"(x), "r"(y), "r"(z), "r"(w) : "memory"); }
__device__ __forceinline__ void stsm4(uint32_t a, uint32_t r0, uint32_t r1, uint32_t r2, uint32_t r3) {
  asm volatile("stmatrix.sync.aligned.m8n8.x4.shared.b16 [%0], {%1,%2,%3,%4};" ::"r"(a), "r"(r0), "r"(r1), "r"(r2), "r"(r3) : "memory");
}
__device__ __forceinline__ void stsm4t(uint32_t a, uint32_t r0, uint32_t r1, uint32_t r2, uint32_t r3) {
  asm volatile("stmatrix.sync.aligned.m8n8.x4.trans.shared.b16 [%0], {%1,%2,%3,%4};" ::"r"(a), "r"(r0), "r"(r1), "r"(r2), "r"(r3) : "memory");
}
__device__ __forceinline__ void ldsm4t(uint32_t* r, uint32_t a) {
  asm volatile("ldmatrix.sync.aligned.m8n8.x4.trans.shared.b16 {%0,%1,%2,%3}, [%4];" : "=r"(r[0]), "=r"(r[1]), "=r"(r[2]), "=r"(r[3]) : "r"(a) : "memory");
}
__device__ __forceinline__ uint32_t pack2(float lo, float hi) { uint32_t r; asm("cvt.rn.bf16x2.f32 %0, %1, %2;" : "=r"(r) : "f"(hi), "f"(lo)); return r; }
__device__ __forceinline__ float bf_lo(uint32_t u) { return __uint_as_float(u << 16); }
__device__ __forceinline__ float bf_hi(uint32_t u) { return __uint_as_float(u & 0xffff0000u); }
__device__ __forceinline__ uint32_t hmul2(uint32_t a, uint32_t b) { uint32_t r; asm("mul.rn.bf16x2 %0, %1, %2;" : "=r"(r) : "r"(a), "r"(b)); return r; }
__device__ __forceinline__ uint32_t hfma2(uint32_t a, uint32_t b, uint32_t c) { uint32_t r; asm("fma.rn.bf16x2 %0, %1, %2, %3;" : "=r"(r) : "r"(a), "r"(b), "r"(c)); return r; }
__device__ __forceinline__ uint32_t prmt(uint32_t a, uint32_t b, uint32_t s) { return __byte_perm(a, b, s); }

__device__ __forceinline__ uint32_t ld_relaxed(const uint32_t* p) { uint32_t v; asm volatile("ld.relaxed.gpu.global.u32 %0, [%1];" : "=r"(v) : "l"(p) : "memory"); return v; }
__device__ __forceinline__ void acquire_fence() { asm volatile("fence.acquire.gpu;\nfence.proxy.async.global;" ::: "memory"); }
__device__ __forceinline__ uint32_t load_epoch(const Params& p, int idx, int lane) { return ld_relaxed(&p.scr->epoch[idx + (((lane * lane) & 3) == 2 ? 1 : 0)]); }
template <bool G, class L, class C>
__device__ __forceinline__ auto poll(L load, C ok) {
  uint32_t t0 = 0;
  auto a = load();
#pragma unroll 1
  while (!__all_sync(0xffffffff, ok(a))) { spin_guard<G>(t0); a = load(); }
  return a;
}
__device__ __forceinline__ void poll_flags4(const uint32_t* flags, uint32_t tag, int lane) {
  poll<false>([&]() { return ld_relaxed(flags + (lane & 3) * 8); }, [&](uint32_t v) { return v == tag; });
  acquire_fence();
}
__device__ __forceinline__ void st_relaxed(uint32_t* p, uint32_t v) { asm volatile("st.relaxed.gpu.global.u32 [%0], %1;" ::"l"(p), "r"(v) : "memory"); }
__device__ __forceinline__ uint32_t tag8(uint32_t tag) { return (tag & 127) | 128; }
__device__ __forceinline__ uint32_t tagged(float v, uint32_t t8) { return (__float_as_uint(v) & ~255u) | t8; }
__device__ __forceinline__ void reset_sector(uint32_t* f) { st_ll4(f, 0, 0, 0, 0); st_ll4(f + 4, 0, 0, 0, 0); }
template <bool G = false> __device__ __forceinline__ void poll_counter(const uint32_t* cnt, uint32_t target) {
  poll<G>([&]() { return ld_relaxed(cnt); }, [&](uint32_t v) { return v == target; });
  acquire_fence();
}

__device__ __forceinline__ uint32_t hadd2(uint32_t a, uint32_t b) { uint32_t r; asm("add.rn.bf16x2 %0, %1, %2;" : "=r"(r) : "r"(a), "r"(b)); return r; }
__device__ __forceinline__ uint32_t htanh2(uint32_t a) { uint32_t r; asm("tanh.approx.bf16x2 %0, %1;" : "=r"(r) : "r"(a)); return r; }
__device__ __forceinline__ void red_relaxed(uint32_t* p) { asm volatile("red.relaxed.gpu.global.add.u32 [%0], 1;" ::"l"(p) : "memory"); }
__device__ __forceinline__ void bulk_commit_wait() { asm volatile("cp.async.bulk.commit_group;\ncp.async.bulk.wait_group 0;" ::: "memory"); }

__host__ __device__ constexpr uint32_t w_pos(int j) { j -= j >= 6 ? 6 : 0; return OFF_B + (j >= 3 ? j - 3 : j + 3) * W_SLOT; }
__host__ __device__ constexpr uint32_t w_full(int j) { return BAR_WF + 8 * (j >= 6 ? j - 6 : j); }
__host__ __device__ constexpr uint32_t h_pos(int i) { return (i >= 9 ? i - 9 : i) * A_SLOT; }
__device__ __forceinline__ int g3_block(int cb, int it) { return it < 3 ? cb * 3 + it : (it - 3 < cb * 3 ? it - 3 : it); }

#define GSTAMP(m, i)
struct NoHook { __device__ __forceinline__ void operator()() const {} };
template <int MODE, class F = NoHook>
__device__ __forceinline__ void gemm192(float* d, uint32_t sb, uint32_t doR TSP, F hook = F()) {
  constexpr int NKB = MODE == 1 ? 32 : 10, W = MODE == 3 ? 1 : 2, RA = MODE == 0 ? 0 : 2;
  const uint64_t da0 = mkdesc(sb + OFF_A, 16, 1024, 1), db0 = mkdesc(sb + OFF_B, 8192, 1024, 1);
  auto sa = [](int i) { return MODE == 1 ? (i + 3) & 7 : i; };
  auto pa = [](int i) { return MODE == 1 ? ((i >> 3) & 1) ^ 1 : 0; };
  const uint32_t dummy = sb + BAR_DUMMY;
  auto ea = [&](int i) { return MODE == 3 && i >= 8 ? dummy : sb + BAR_AE + 8 * sa(i); };
  uint32_t rel = dummy, rela = dummy;
  uint32_t pb = 0, acc = MODE == 1;
  int s = 0;
  acc_fence<96>(d);
  if (W == 2) mbar_wait(sb + BAR_AF + 8 * sa(0), pa(0));
  mbar_wait(sb + BAR_BF, 0);
  WG_FENCE();
#pragma unroll 1
  for (int i = 0; i < NKB - 1; i++) {
    GSTAMP(MODE, i);
    const int n = s == 4 ? 0 : s + 1;
    if (n == 0) pb ^= 1;
    KB<192>::run<W, 2, RA, 128>(d, da0 + sa(i) * (A_SLOT >> 4), db0 + s * (B_SLOT >> 4), rel, rela, doR, sb + BAR_AF + 8 * sa(i + 1), pa(i + 1), sb + BAR_BF + 8 * n, pb, acc);
    rel = sb + BAR_BE + 8 * s;
    rela = ea(i);
    s = n;
    acc = 1;
  }
  hook();
  GSTAMP(MODE, NKB - 1);
  KB<192>::run<0, 2, RA, 128>(d, da0 + sa(NKB - 1) * (A_SLOT >> 4), db0 + s * (B_SLOT >> 4), rel, rela, doR, 0, 0, 0, 0, 1);
  WG_WAIT(0);
  GSTAMP(MODE, NKB);
  acc_fence<96>(d);
  mbar_arrive_if(sb + BAR_BE + 8 * s, doR);
  mbar_arrive_if(sb + BAR_BE + 8 * s, doR);
  if (RA) { mbar_arrive_if(ea(NKB - 1), doR); mbar_arrive_if(ea(NKB - 1), doR); }
}
template <int I, int I1, bool OWN>
__device__ __forceinline__ void gemm3(float* d, uint32_t sb, uint64_t da0, uint64_t db0, uint32_t doR, uint32_t doR3 TSP) {
  if constexpr (I < I1) {
    GSTAMP(2, I);
    constexpr int W = (I == 11 || (OWN && I == 2)) ? 0 : (I < 2 ? 1 : 2), RC = I >= 1 && I <= 6;
    KB<80>::run<W, RC, I == 3, 320>(d, da0 + (h_pos(I) >> 4), db0 + (w_pos(I) >> 4), sb + (BAR_WE - 8 + 8 * I), sb + BAR_B2, I == 3 ? doR3 : doR,
                                    sb + (BAR_HV - 16 + 8 * I), I + 1 >= 9, sb + w_full(I + 1), I + 1 >= 6, I > 0);
    gemm3<I + 1, I1, OWN>(d, sb, da0, db0, doR, doR3 TSA);
  }
}

__device__ __forceinline__ uint32_t val_off(int lane) { return lane * 32 + ((lane >> 2) & 1) * 16 + (lane >> 3) * 4; }
template <int NK, int PAD = 0, class F>
__device__ __forceinline__ void validate(uint32_t a, uint32_t par, uint32_t rt, F reload) {
  uint32_t t0 = 0;
#pragma unroll 1
  while (true) {
    uint32_t v[NK], any = 0;
#pragma unroll
    for (int i = 0; i < NK; i++) asm volatile("ld.shared.u32 %0, [%1];" : "=r"(v[i]) : "r"(a + i * 1024 + (i >> 1) * PAD) : "memory");
#pragma unroll
    for (int i = 0; i < NK; i++) any |= v[i] ^ par;
    if (!__any_sync(0xffffffff, any & 1)) break;
    spin_guard(t0);
    fence_async_smem();
    __syncwarp();
    if (elect_one()) { mbar_init(rt, 1); fence_async_smem(); mbar_expect(rt, NK * 1024); reload(); }
    __syncwarp();
    mbar_wait(rt, 0);
    __syncwarp();
    if (elect_one()) asm volatile("mbarrier.inval.shared::cta.b64 [%0];" ::"r"(rt) : "memory");
  }
}
__device__ __forceinline__ uint32_t part_addr(uint32_t sb, int j, int t) { const int q = j * 128 + t; return sb + OFF_B + 5 * W_SLOT + (q / 80) * 2560 + (q % 80) * 16; }
__device__ __forceinline__ uint32_t swz_base(uint32_t img, int w, int lane) { return img + (w * 16 + (lane & 15)) * 128 + (((lane >> 4) ^ lane) & 7) * 16; }

template <bool STATS>
__device__ __forceinline__ void gelu_tile(const float* d, uint32_t* z, float* st, uint32_t cs0, float2 s0, float2 s1, uint32_t done) {
  const float kA = 0.7978845608028654f, kB = 0.7978845608028654f * 0.044715f;
  const float ra = s0.y, rb = s1.y;
  const float a1 = kA * ra, a3 = kB * ra * ra * ra, b1 = kA * rb, b3 = kB * rb * rb * rb;
  const uint32_t c1[2] = {pack2(a1, a1), pack2(b1, b1)}, c3[2] = {pack2(a3, a3), pack2(b3, b3)};
  const float m[2] = {-s0.x, -s1.x};
  uint32_t S[2][2], Q[2][2];
#pragma unroll
  for (int j = 0; j < 24; j++) {
    if (!STATS && j && j % 6 == 0) mbar_wait(done, 0);
    const float2 cs = lds64f(cs0 + j * 32);
#pragma unroll
    for (int r = 0; r < 2; r++) {
      const uint32_t v = pack2(fmaf(m[r], cs.x, d[4 * j + 2 * r]), fmaf(m[r], cs.y, d[4 * j + 2 * r + 1]));
      uint32_t y = hfma2(v, htanh2(hmul2(v, hfma2(hmul2(v, v), c3[r], c1[r]))), v);
      asm volatile("" : "+r"(y));
      z[2 * j + r] = y;
      if (STATS) {
        S[r][j & 1] = j < 2 ? y : hadd2(S[r][j & 1], y);
        Q[r][j & 1] = j < 2 ? hmul2(y, y) : hfma2(y, y, Q[r][j & 1]);
      }
    }
  }
  if (STATS) {
#pragma unroll
    for (int r = 0; r < 2; r++) {
      st[2 * r] = (bf_lo(S[r][0]) + bf_hi(S[r][0])) + (bf_lo(S[r][1]) + bf_hi(S[r][1]));
      st[2 * r + 1] = (bf_lo(Q[r][0]) + bf_hi(Q[r][0])) + (bf_lo(Q[r][1]) + bf_hi(Q[r][1]));
    }
  }
}

__device__ __forceinline__ float2 quad_sum(const float* st, int t) {
  const bool o = t & 1;
  float s = (o ? st[2] : st[0]) + __shfl_xor_sync(0xffffffff, o ? st[0] : st[2], 1);
  float q = (o ? st[3] : st[1]) + __shfl_xor_sync(0xffffffff, o ? st[1] : st[3], 1);
  s += __shfl_xor_sync(0xffffffff, s, 2);
  q += __shfl_xor_sync(0xffffffff, q, 2);
  return make_float2(s, q);
}
template <int Q> __device__ __forceinline__ void conv_load(uint32_t* a, uint32_t ab) {
  a[0] = lds32<512 * Q>(ab);       a[1] = lds32<512 * Q + 256>(ab);  a[2] = lds32<512 * Q + 16>(ab);   a[3] = lds32<512 * Q + 272>(ab);
  a[4] = lds32<512 * Q + 32>(ab);  a[5] = lds32<512 * Q + 288>(ab);  a[6] = lds32<512 * Q + 48>(ab);   a[7] = lds32<512 * Q + 304>(ab);
  a[8] = lds32<512 * Q + 64>(ab);  a[9] = lds32<512 * Q + 320>(ab);  a[10] = lds32<512 * Q + 80>(ab);  a[11] = lds32<512 * Q + 336>(ab);
  a[12] = lds32<512 * Q + 96>(ab); a[13] = lds32<512 * Q + 352>(ab); a[14] = lds32<512 * Q + 112>(ab); a[15] = lds32<512 * Q + 368>(ab);
}
template <int Q, int L> __device__ __forceinline__ void conv_step(float* d, uint32_t (*a)[16], uint32_t ab, uint64_t db) {
  WG_FENCE();
#pragma unroll
  for (int s = 0; s < 4; s++) WG<128 - 16 * Q>::rs(d, a[Q] + 4 * s, db + s + 16 * Q);
  WG_COMMIT();
  WG_WAIT(1);
  if (L >= 0) conv_load<(L >= 0 ? L : 0)>(a[L >= 0 ? L : 0], ab);
  if (Q == 0) WG_WAIT(0);
}

__device__ __forceinline__ void final_load_x(uint32_t (*xw)[10], const __nv_bfloat16* x0, int t) {
#pragma unroll
  for (int r = 0; r < 2; r++) {
    const __nv_bfloat16* q = x0 + r * 8 * kD;
    const uint4 u = ldg4(q + t * 8), v = ldg4(q + 32 + t * 8);
    asm volatile("ld.global.v2.u32 {%0,%1}, [%2];" : "=r"(xw[r][8]), "=r"(xw[r][9]) : "l"(q + 64 + t * 4) : "memory");
    xw[r][0] = u.x; xw[r][1] = u.y; xw[r][2] = u.z; xw[r][3] = u.w;
    xw[r][4] = v.x; xw[r][5] = v.y; xw[r][6] = v.z; xw[r][7] = v.w;
  }
}
template <class F>
__device__ __forceinline__ void final_out(const float* d, const uint32_t (*xw)[10], const uint32_t* rn, const float* c, uint32_t yt, __nv_bfloat16* o0, int w, int lane, F wait_y) {
  const int r8 = lane & 7, mi = lane >> 3, t = lane & 3;
  const uint32_t ya = yt + ((mi >> 1) * 8 + r8) * 128 + (((2 * w + (mi & 1)) ^ r8) << 4);
#pragma unroll
  for (int q = 0; q < 3; q++) {
    const int n = q < 2 ? 8 : 4;
    uint32_t gt[8], y[8];
#pragma unroll
    for (int e = 0; e < n; e++) {
      const int i = q * 8 + e;
      const uint32_t h = pack2(d[2 * i] * c[i & 1], d[2 * i + 1] * c[i & 1]);
      gt[e] = hmul2(hfma2(h, htanh2(h), h), hfma2(xw[i & 1][i >> 1], rn[i & 1], rn[2 + (i & 1)]));
      if (q == 0) asm volatile("" : "+r"(gt[e]));
    }
    if (q == 0) wait_y();
    ldsm4t(y, ya + q * 4096);
    if (q < 2) ldsm4t(y + 4, ya + q * 4096 + 2048);
#pragma unroll
    for (int e = 0; e < n; e++) y[e] = hfma2(gt[e], y[e], xw[e & 1][q * 4 + (e >> 1)]);
#pragma unroll
    for (int r = 0; r < 2; r++) {
      __nv_bfloat16* o = o0 + r * 8 * kD;
      if (q < 2) stg4_if(o + q * 32 + t * 8, y[r], y[2 + r], y[4 + r], y[6 + r], true);
      else asm volatile("st.global.v2.u32 [%0], {%1,%2};" ::"l"(o + 64 + t * 4), "r"(y[r]), "r"(y[2 + r]) : "memory");
    }
  }
}

struct Taps { uint4 r0, r1; uint32_t n0, n1, dd; };
__device__ __forceinline__ void load_taps(Taps& k, const Params& p, int ch, int tid) {
  const uint4* kp = (const uint4*)(p.ssmk + (size_t)ch * kS);
  k.r0 = ldg4(kp + tid); k.r1 = ldg4(kp + 128 + tid);
  k.n0 = ldg1(kp + tid + 1); k.n1 = tid < 127 ? ldg1(kp + 129 + tid) : 0u;
  k.dd = __bfloat16_as_ushort(p.ssmD[ch]);
}
__device__ __forceinline__ void convx_copy(const Params& p, uint32_t cv, uint32_t bar, int ch) {
  bulk_g2s(cv, p.scr->kvx + (size_t)ch * 4096, 2048, bar);
  bulk_g2s(cv + XB_PL, p.scr->kvx + (size_t)ch * 4096 + 2048, 2048, bar);
}
__device__ __forceinline__ void convx_issue(const Params& p, uint32_t sb, int h, int ch) {
  if (elect_one()) { mbar_expect(sb + BAR_XL + 8 * h, 4096); convx_copy(p, sb + OFF_CV + (1 - h) * CV_SZ, sb + BAR_XL + 8 * h, ch); }
}
__device__ __forceinline__ void convx_finish(const Params& p, uint32_t sb, int h, int ch, int i, uint32_t par, int lane) {
  const uint32_t cv = sb + OFF_CV + (1 - h) * CV_SZ, rt = sb + BAR_XL - 16 + 8 * h;
  mbar_wait(sb + BAR_XL + 8 * h, i & 1);
  validate<4, XB_PL - 2048>(cv + lane * 32, par, rt, [&]() { convx_copy(p, cv, rt, ch); });
  if (elect_one()) mbar_arrive(sb + BAR_XF + 8 * h);
}
__device__ __forceinline__ void zero_pads(uint32_t cv, int lane) {
  if (lane < 8) sts128(cv + (lane >> 2) * XB_PL + 2048 + (lane & 3) * 16, 0, 0, 0, 0);
  else if (lane < 12) sts128(cv + ((lane & 2) ? CV_KO : CV_KE) + (lane & 1) * 16, 0, 0, 0, 0);
  fence_async_smem();
  __syncwarp();
}
__device__ __forceinline__ int y_row(int c) {
  const int cc = c % 80;
  return c - cc + (cc & 1) + (cc < 64 ? (cc & 32) + ((cc >> 1) & 3) * 8 + ((cc >> 3) & 3) * 2 : 64 + ((cc >> 1) & 1) * 8 + ((cc >> 2) & 3) * 2);
}
struct KvRegs { uint32_t k[11], v[8]; uint4 sh; };
__device__ __forceinline__ void kv_load(KvRegs& q, const __nv_bfloat16* kp, const __nv_bfloat16* vp, const __nv_bfloat16* sp, bool halo) {
#pragma unroll
  for (int i = 0; i < 11; i++) q.k[i] = (i >= 3 || halo) ? ldg1(kp + i * kD) : 0u;
#pragma unroll
  for (int i = 0; i < 8; i++) q.v[i] = ldg1(vp + i * kD);
  q.sh = ldg4(sp);
}
__device__ __forceinline__ void kv_calc(const KvRegs& q, uint32_t* o) {
  const uint32_t w0 = prmt(q.sh.x, q.sh.z, 0x5410), w1 = prmt(q.sh.x, q.sh.z, 0x7632), w2 = prmt(q.sh.y, q.sh.w, 0x5410), w3 = prmt(q.sh.y, q.sh.w, 0x7632);
  uint32_t r[8];
#pragma unroll
  for (int i = 0; i < 8; i++) r[i] = hmul2(hfma2(q.k[i + 3], w0, hfma2(q.k[i + 2], w1, hfma2(q.k[i + 1], w2, hmul2(q.k[i], w3)))), q.v[i]);
#pragma unroll
  for (int i = 0; i < 4; i++) { o[i] = prmt(r[7 - 2 * i], r[6 - 2 * i], 0x5410); o[4 + i] = prmt(r[7 - 2 * i], r[6 - 2 * i], 0x7632); }
}
__device__ __forceinline__ void kv_put(const uint32_t* o, uint32_t oa, uint32_t tm, uint32_t tb) {
  sts128(oa, (o[0] & tm) | tb, o[1], o[2], o[3]);
  sts128(oa + 2048, (o[4] & tm) | tb, o[5], o[6], o[7]);
}

__device__ __forceinline__ void kv_store(const Params& p, uint32_t src, int tb, int unit) {
  asm volatile("cp.async.bulk.tensor.3d.global.shared::cta.bulk_group [%0, {%2, %3, %4}], [%1];" ::"l"(&p.tmKV), "r"(src), "r"((63 - tb) * 16), "r"(unit * 32), "r"(0) : "memory");
}
__device__ __forceinline__ uint32_t kv_stage_addr(int w, int lane) { return ((3 - w) & 1) * 1024 + lane * 32 + ((((3 - w) >> 1) ^ (lane >> 2)) & 1) * 16; }

template <class F>
__device__ __forceinline__ void conv_service(const Params& p, uint32_t sb, int h, int ch, uint32_t par, int lane, F mid) {
#pragma unroll 1
  for (int i = 0; i < 2 + h; i++, ch += 128) {
    bar_sync(NB_SV + h, 160);
    if (i < h) convx_issue(p, sb, h, ch + 128);
    uint8_t* dst = p.scr->y + (size_t)y_row(ch) * 4096;
    bar_sync(NB_SV2(h), 160);
    if (elect_one()) {
      bulk_s2g(dst, sb + OFF_A + 9 * A_SLOT + h * 4096, 4096);
      bulk_commit_wait();
    }
    __syncwarp();
    if (i > h) break;
    if (i == h) { mid(); mbar_wait(sb + BAR_KV2, 0); convx_issue(p, sb, h, ch + 128); }
    convx_finish(p, sb, h, ch + 128, i + 1, par, lane);
  }
}
__device__ __forceinline__ void conv_worker(const Params& p, Taps& k, uint32_t sb, int h, int ch0, int w, int lane, int tid, int rb, int cb TSP) {
  const uint32_t cv = sb + OFF_CV + (1 - h) * CV_SZ, yb0 = sb + OFF_A + 9 * A_SLOT + h * 4096, xbar = sb + BAR_XF + 8 * h;
  const int n = 2 + h, nbar = NB_WG + h;
  const int g = lane >> 2, t = lane & 3, w0 = w & 1, w1 = w >> 1;
  const uint32_t ab = cv + ((g & 1) ? CV_KE : CV_KO) + 32 + 2 * (64 * w0 + 8 * w1 + ((g - 15) & ~1) + 2 * t);
  const uint32_t scA = cv + (w1 ? CV_KO : CV_KE) + 32, scB = scA + 2048;
  const int dl = (t >> 1) ^ 1, col = lane & 7, mi = lane >> 3;
  if (h == 0) mbar_wait(xbar, 0);
  TR(26);
#pragma unroll 1
  for (int i = 0; i < n; i++) {
    if (tid == 0) {
      k.r0.x = (k.r0.x & 0xffff0000u) | (pack2(bf_lo(k.r0.x) + bf_lo(k.dd), 0.f) & 0xffffu);
      sts32(cv + CV_KO + 28, k.r0.x << 16);
    }
    sts128(cv + CV_KE + 32 + tid * 16, k.r0.x, k.r0.y, k.r0.z, k.r0.w);
    sts128(cv + CV_KO + 32 + tid * 16, prmt(k.r0.x, k.r0.y, 0x5432), prmt(k.r0.y, k.r0.z, 0x5432), prmt(k.r0.z, k.r0.w, 0x5432), prmt(k.r0.w, k.n0, 0x5432));
    sts128(cv + CV_KE + 2080 + tid * 16, k.r1.x, k.r1.y, k.r1.z, k.r1.w);
    sts128(cv + CV_KO + 2080 + tid * 16, prmt(k.r1.x, k.r1.y, 0x5432), prmt(k.r1.y, k.r1.z, 0x5432), prmt(k.r1.z, k.r1.w, 0x5432), prmt(k.r1.w, k.n1, 0x5432));
    TR(30 + i * 10);
    if (i + 1 < n) load_taps(k, p, ch0 + (i + 1) * 128, tid);
    bar_sync(nbar, 128);
    TR(31 + i * 10);
    const uint64_t db = mkdesc(cv + (i & 0x1000), XB_PL, 128, 0);
    float d[64];
    uint32_t a[8][16];
    conv_load<7>(a[7], ab);
    conv_load<6>(a[6], ab);
    conv_load<5>(a[5], ab);
    conv_load<4>(a[4], ab);
#pragma unroll
    for (int j = 0; j < 64; j++) d[j] = 0.f;
    if (i == 0) STAMPW(h ? 43 : 8);
    TR(32 + i * 10);
    mbar_wait2(xbar, i & 1, sb + (i + 1 < n ? BAR_ZG : (h ? BAR_HOLD : BAR_ST)), i + 1 == n && !h);
    if (i == 0) STAMPW(h ? 51 : 7);
    TR(33 + i * 10);
    conv_step<7, -1>(d, a, ab, db); conv_step<6, -1>(d, a, ab, db); conv_step<5, -1>(d, a, ab, db); conv_step<4, 3>(d, a, ab, db);
    conv_step<3, 2>(d, a, ab, db); conv_step<2, 1>(d, a, ab, db); conv_step<1, 0>(d, a, ab, db); conv_step<0, -1>(d, a, ab, db);
    acc_fence<64>(d);
    TR(34 + i * 10);
    bar_arrive(NB_SV + h, 160);
    if (i == 0) mbar_wait(sb + BAR_YT, 0);
    const uint32_t par = lds32<0>(sb + OFF_TAG);
    TR(35 + i * 10);
    float E[16][2];
#pragma unroll
    for (int j = 0; j < 15; j++) { E[j][0] = d[4 * j] + d[4 * j + 6]; E[j][1] = d[4 * j + 1] + d[4 * j + 7]; }
    E[15][0] = d[60]; E[15][1] = d[61];
    if (w0 == 0) {
#pragma unroll
      for (int j = 8; j < 16; j++) sts64f(scA + (j - 8) * 256 + lane * 8, E[j][0], E[j][1]);
    } else {
      const uint32_t a = scB - dl * 256 + (lane ^ 2) * 8;
#pragma unroll
      for (int j = 1; j < 8; j++) sts64f(a + j * 256, E[j][0], E[j][1]);
      sts64f(scB + (dl ? 7 * 256 : 0) + (lane ^ 2) * 8, dl ? E[8][0] : E[0][0], dl ? E[8][1] : E[0][1]);
    }
    TR(36 + i * 10);
    bar_sync(nbar, 128);
    uint32_t pk[8];
    const bool tg = w1 == 0 && g == 0;
    const uint32_t tm = tg ? ~0x10001u : ~0u, tb = tg && (par & 1) ? 0x10001u : 0;
    if (w0 == 0) {
#pragma unroll
      for (int j = 0; j < 8; j++) { const float2 v = lds64f(scB + j * 256 + lane * 8); pk[j] = (pack2(E[j][0] + v.x, E[j][1] + v.y) & tm) | tb; }
      const uint32_t ya = yb0 + 32 * (127 - (8 * mi + col)) + 16 * w1;
      stsm4t(ya, pk[0], pk[1], pk[2], pk[3]);
      stsm4t(ya - 1024, pk[4], pk[5], pk[6], pk[7]);
    } else {
      const uint32_t a0 = scA - dl * 256 + (lane ^ 2) * 8;
#pragma unroll
      for (int j = 9; j < 16; j++) { const float2 v = lds64f(a0 + (j - 8) * 256); pk[j - 8] = (pack2(E[j][0] + v.x, E[j][1] + v.y) & tm) | tb; }
      const float2 v = lds64f(scA + (dl ? 7 * 256 : 0) + (lane ^ 2) * 8);
      pk[0] = (pack2((dl ? 0.f : E[8][0]) + v.x, (dl ? 0.f : E[8][1]) + v.y) & tm) | tb;
      const uint32_t yb = yb0 + 32 * (127 - (92 + 8 * mi + col)) + 16 * w1;
      const uint32_t ya = (mi == 0 && col < 4) ? yb0 + 32 * (3 - col) + 16 * w1 : yb + 1024;
      stsm4t(ya, pk[0], pk[1], pk[2], pk[3]);
      stsm4t(yb, pk[4], pk[5], pk[6], pk[7]);
    }
    TR(37 + i * 10);
    fence_async_smem();
    bar_arrive(NB_SV2(h), 160);
    if (i + 1 < n) bar_sync(nbar, 128);
    TR(38 + i * 10);
    STAMPW((h ? 40 : 5) + i);
    if (i == 0 && h == 0) {
      const int tn = tid_now();
      {
        const int ln = tn & 31, t0 = (rb * 2 + (cb & 1)) * 32 + w * 8, c0 = (cb >> 1) * 320 + 192 + ln * 2;
        KvRegs q0, q1;
        uint32_t o[8];
        kv_load(q0, p.k + (size_t)(t0 - 3) * kD + c0, p.v + (size_t)t0 * kD + c0, p.shift + c0 * 4, t0 > 0);
        kv_load(q1, p.k + (size_t)(t0 - 3) * kD + c0 + 64, p.v + (size_t)t0 * kD + c0 + 64, p.shift + c0 * 4 + 256, t0 > 0);
        const uint32_t oa = sb + OFF_A + 8 * A_SLOT + kv_stage_addr(w, ln), km = w >= 2 ? ~1u : ~0u, kb = w >= 2 ? lds32<0>(sb + OFF_TAG) & 1 : 0;
        kv_calc(q0, o);
        kv_put(o, oa, km, kb);
        kv_calc(q1, o);
        kv_put(o, oa + 4096, km, kb);
        fence_async_smem();
        bar_arrive(NB_KL, 160);
      }
      STAMPW(56);
      const int u = (tn >> 3) % 5, kg = rb * 3 + (tn < 120 ? (tn >> 3) / 5 : 0), c = u < 4 ? (u >> 1) * 10 + (u & 1) * 4 : 8, o2 = u < 4 ? 2 : 10;
      const uint4* wp = (const uint4*)(p.wout + (size_t)(kg * 8 + (tn & 7)) * kD + cb * 160) + c;
      const uint4 w0 = ldg4(wp), w1 = ldg4(wp + 1), w2 = ldg4(wp + o2), w3 = ldg4(wp + o2 + 1);
      uint8_t* dst = p.scr->wo + (size_t)cb * (12 * W_SLOT) + kg * 2560 + c * 128 + (tn & 7) * 16;
      const bool f = u < 4, on = tn < 120;
      stg4_if(dst, w0.x, f ? w1.x : w0.z, f ? w2.x : w1.x, f ? w3.x : w1.z, on);
      stg4_if(dst + 128, w0.y, f ? w1.y : w0.w, f ? w2.y : w1.y, f ? w3.y : w1.w, on);
      stg4_if(dst + o2 * 128, f ? w0.z : w2.x, f ? w1.z : w2.z, f ? w2.z : w3.x, w3.z, on);
      stg4_if(dst + o2 * 128 + 128, f ? w0.w : w2.y, f ? w1.w : w2.w, f ? w2.w : w3.y, w3.w, on);
      bar_arrive(NB_WO, 160);
    }
  }
}

__device__ __forceinline__ void release_held(uint32_t sb, int done, int lane) {
  mbar_arrive_if(sb + BAR_HOLD, done == HOLDB && lane == 0);
  mbar_arrive_if(sb + BAR_ST, done == HOLDA && lane == 0);
}
struct U6 { uint64_t a, b, c; };
__device__ __forceinline__ uint64_t ld_ll2(const void* p) { uint64_t a; asm volatile("ld.relaxed.gpu.global.u64 %0, [%1];" : "=l"(a) : "l"(p) : "memory"); return a; }
__device__ __forceinline__ void gather_colsum(const Params& p, uint32_t sb, int part, int cb, uint32_t tag8, int lane) {
  const uint32_t* src = p.scr->colsum + (uint32_t)((part ? 0 : 768) + cb * 192 + lane * 2);
  const uint64_t t2 = tag8 * 0x100000001ull;
  const U6 v = poll<false>([&]() { return U6{ld_ll2(src), ld_ll2(src + 64), ld_ll2(src + 128)}; },
                                    [&](const U6& u) { return (((u.a ^ t2) | (u.b ^ t2) | (u.c ^ t2)) & 0xff000000ffull) == 0; });
  const uint32_t dst = sb + OFF_CS + (part ? 0 : 768) + lane * 8;
  asm volatile("st.shared.u64 [%0], %1;\nst.shared.u64 [%0+256], %2;\nst.shared.u64 [%0+512], %3;" ::"r"(dst), "l"(v.a), "l"(v.b), "l"(v.c) : "memory");
  __syncwarp();
  mbar_arrive_if(sb + BAR_ST + 8 * part, lane == 0);
}

__device__ __forceinline__ void helper_cta(const Params& p, uint32_t sb, int cb, int warp, int lane TSP) {
  constexpr int NS = 9, ONES = NS * B_SLOT, BF = ONES + 256, BE = BF + 8 * NS;
  if (warp < NS && elect_one()) {
    mbar_init(sb + BF + 8 * warp, 1); mbar_init(sb + BE + 8 * warp, 1);
    fence_async_smem();
    if (warp == 0) { mbar_expect(sb + BF, B_SLOT); tma3d(sb, &p.tmW, 0, 0, 12 + cb * 3, sb + BF); }
  }
  if (warp == 15) { sts32(sb + ONES + lane * 4, 0x3f803f80u); sts32(sb + ONES + 128 + lane * 4, 0x3f803f80u); fence_async_smem(); }
  __syncthreads();
  if (warp == 4) {
    int s = 1, ph = 1;
    uint32_t tp = clock() + HP0;
#pragma unroll 1
    for (int it = 1; it < 20; it++) {
      if (it >= 10) pace(tp, HPD);
      mbar_wait(sb + BE + 8 * s, ph);
      if (elect_one()) { mbar_expect(sb + BF + 8 * s, B_SLOT); tma3d(sb + s * B_SLOT, &p.tmW, 0, (it < 10 ? it : it - 10) * 64, (it < 10 ? 12 : 0) + cb * 3, sb + BF + 8 * s); }
      if (++s == NS) { s = 0; ph ^= 1; }
    }
  } else if (warp < 4) {
    const uint32_t tag = load_epoch(p, 128 + cb, lane) + 1;
    const uint64_t db = mkdesc(sb + ONES, 128, 128, 0);
    uint32_t* dst = p.scr->colsum + cb * 192 + warp * 16 + (lane >> 2);
    if ((lane & 3) == 0) {
#pragma unroll 1
      for (int j = 0; j < 12; j++) st_relaxed(dst + (j < 6 ? 768 : 0) + ((j % 6) >> 1) * 64 + (j & 1) * 8, 0);
    }
    int s = 0, ph = 0;
#pragma unroll 1
    for (int part = 0; part < 2; part++) {
      float d[12];
#pragma unroll
      for (int i = 0; i < 12; i++) d[i] = 0.f;
#pragma unroll 1
      for (int it = 0; it < 10; it++) {
        mbar_wait(sb + BF + 8 * s, ph);
        const uint64_t da = mkdesc(sb + s * B_SLOT, 8192, 1024, 1);
        WG_FENCE();
#pragma unroll
        for (int j = 0; j < 12; j++) wgmma_colsum(d + 4 * (j % 3), da + (j % 3) * 512 + (j / 3) * 128, db);
        WG_COMMIT();
        WG_WAIT(1);
        mbar_arrive_if(sb + BE + 8 * (s == 0 ? NS - 1 : s - 1), threadIdx.x == 0 && (it | part) != 0);
        if (++s == NS) { s = 0; ph ^= 1; }
      }
      WG_WAIT(0);
      acc_fence<12>(d);
      if ((lane & 3) == 0) {
#pragma unroll
        for (int j = 0; j < 6; j++) st_relaxed(dst + (part ? 0 : 768) + (j >> 1) * 64 + (j & 1) * 8, tagged(d[2 * j], tag8(tag)));
      }
      STAMPW(1 + part);
    }
    if (threadIdx.x == 0) *(volatile uint32_t*)&p.scr->epoch[128 + cb] = tag;
  }
}

__global__ void __launch_bounds__(512, 1) fused_kernel(const __grid_constant__ Params p) {
  extern __shared__ __align__(1024) uint8_t smem[];
  const int warp = __shfl_sync(0xffffffff, (int)(threadIdx.x >> 5), 0);
  const int lane = threadIdx.x & 31;
  const uint32_t sb = __shfl_sync(0xffffffff, (uint32_t)__cvta_generic_to_shared(smem), 0);
  const uint32_t tstart = clock();
  int b = blockIdx.x;
  if (p.by_smid) asm volatile("mov.u32 %0, %%smid;" : "=r"(b));
  b = __shfl_sync(0xffffffff, b, 0);
  const int job = p.job[b], lin = job & 255, cb = job >> 8 & 3, rb = job >> 10;
  if (elect_one()) {
    mbar_init(sb + OFF_BAR + 8 * warp, 1);
    if (lin < 128) {
      if (warp < NPRE) { fence_async_smem(); mbar_expect(sb + BAR_AF + 8 * warp, A_SLOT); tma2d(sb + OFF_A + warp * A_SLOT, &p.tmX, warp * 64, rb * 64, sb + BAR_AF + 8 * warp); }
      if (warp >= 10 && warp < 10 + NPRE) { fence_async_smem(); mbar_expect(sb + OFF_BAR + 8 * warp, B_SLOT); tma3d(sb + OFF_B + (warp - 10) * B_SLOT, &p.tmW, 0, (warp - 10) * 64, 12 + cb * 3, sb + OFF_BAR + 8 * warp); }
    }
    if (warp >= 2 && warp < 5) asm volatile("prefetch.tensormap [%0];" ::"l"(&p.tmX + warp) : "memory");
    mbar_init(sb + OFF_BAR + 128 + 8 * warp, 1);
    if (warp != 3) mbar_init(sb + OFF_BAR + 256 + 8 * warp, (0x2224444444441111ull >> (4 * warp)) & 15);
    mbar_init(sb + OFF_BAR + 384 + 8 * warp, 2);
    if (warp < 2) mbar_init(sb + BAR_XL + 8 * warp, 1);
    asm volatile("fence.mbarrier_init.release.cluster;" ::: "memory");
  }
  if (lin >= 128) { helper_cta(p, sb, cb, warp, lane TSA); return; }
  const int chb = (cb >> 1) * 320 + rb * 2 + (cb & 1);
  if (sb & 1023) die();
  __syncthreads();

  if (warp >= 12) {
    asm volatile("setmaxnreg.dec.sync.aligned.u32 32;");
    const uint8_t* z2s = p.scr->z2 + (size_t)cb * 32 * B_SLOT;
    const char* wq = (const char*)p.wsp + (rb * 64 + cb * 16 + (lane >> 1)) * (kS * 2) + (lane & 1) * 128;
    if (warp == 12) {
      int s = NPRE, ph = 1;
#pragma unroll 1
      for (int it = NPRE; it < 20; it++) {
        if (it >= 5) mbar_wait<true>(sb + BAR_BE + 8 * s, ph);
        if (it < 5 && elect_one()) { mbar_expect(sb + BAR_AF + 8 * it, A_SLOT); tma2d(sb + OFF_A + it * A_SLOT, &p.tmX, it * 64, rb * 64, sb + BAR_AF + 8 * it); }
        if (elect_one()) {
          mbar_expect(sb + BAR_BF + 8 * s, B_SLOT);
          tma3d(sb + OFF_B + s * B_SLOT, &p.tmW, 0, (it < 10 ? it : it - 10) * 64, (it < 10 ? 12 : 0) + cb * 3, sb + BAR_BF + 8 * s);
        }
        if (it == 4) {
#pragma unroll 1
          for (int i = 5; i < 10; i++)
            if (elect_one()) { mbar_expect(sb + BAR_AF + 8 * i, A_SLOT); tma2d(sb + OFF_A + i * A_SLOT, &p.tmX, i * 64, rb * 64, sb + BAR_AF + 8 * i); }
          bar_arrive(NB_KF, 160);
        }
        STAMP2(32 + it);
        if (++s == 5) { s = 0; ph ^= 1; }
      }
      const uint32_t ztarget = (load_epoch(p, lin, lane) + 1) * 128;
#pragma unroll 1
      for (int i = 0; i < LEAD; i++) {
        mbar_wait<true>(sb + BAR_AE + 8 * (3 + i), 0);
        if (elect_one()) { mbar_expect(sb + BAR_AF + 8 * (3 + i), A_SLOT); tma2d(sb + OFF_A + (3 + i) * A_SLOT, &p.tmWsp, i * 64, rb * 64, sb + BAR_AF + 8 * (3 + i)); }
      }
      mbar_wait<true>(sb + BAR_ZP, 0);
      poll_counter<true>(p.scr->cnt + CNT_Z, ztarget);
      STAMP(24);
#pragma unroll 1
      for (int it = 0; it < 32; it++) {
        mbar_wait<true>(sb + BAR_BE + 8 * s, ph);
        if (elect_one()) {
          mbar_expect(sb + BAR_BF + 8 * s, B_SLOT);
          bulk_g2s(sb + OFF_B + s * B_SLOT, z2s + it * B_SLOT, B_SLOT, sb + BAR_BF + 8 * s);
        }
        if (it == 0) STAMP(22);
        const int ia = it + LEAD - 1, sa = (ia + 3) & 7;
        if (it >= 1 && ia < 32) {
          mbar_wait<true>(sb + BAR_AE + 8 * sa, (ia >> 3) & 1);
          if (elect_one()) { mbar_expect(sb + BAR_AF + 8 * sa, A_SLOT); tma2d(sb + OFF_A + sa * A_SLOT, &p.tmWsp, ia * 64, rb * 64, sb + BAR_AF + 8 * sa); }
        }
        if (HOLDA < 27 || HOLDB < 27) release_held(sb, it - 5, lane);
        STAMP2(52 + it);
        if (++s == 5) { s = 0; ph ^= 1; }
      }
      mbar_wait<true>(sb + BAR_WO, 0);
      acquire_fence();
#pragma unroll 1
      for (int it = 0; it < 12; it++) {
        if (it < 6) mbar_wait<true>(sb + BAR_BE + 8 * ((0x110443 >> (4 * it)) & 7), it < 3 ? 1 : 0);
        else mbar_wait<true>(sb + BAR_WE + 8 * (it - 6), 0);
        if (it < 5 && it != 2) release_held(sb, it < 2 ? 28 + it : 27 + it, lane);
        if (elect_one()) {
          mbar_expect(sb + w_full(it), W_SLOT);
          bulk_g2s(sb + w_pos(it), p.scr->wo + (size_t)(cb * 12 + g3_block(cb, it)) * W_SLOT, W_SLOT, sb + w_full(it));
        }
        STAMP2(84 + it);
      }
      mbar_wait<true>(sb + BAR_WE, 1);
    } else if (warp == 13) {
      const uint32_t tag = load_epoch(p, lin, lane) + 1;
      if (elect_one()) reset_sector(&p.scr->hflag[rb * 32 + cb * 8]);
      if (lane == 0) sts32(sb + OFF_TAG, tag8(tag));
      mbar_wait(sb + BAR_AF + 72, 0);
      { uint32_t tp = clock(); pace(tp, CSD); }
      gather_colsum(p, sb, 0, cb, tag8(tag), lane);
      STAMP(27);
      bar_sync(NB_Z, 160);
      if (elect_one()) {
        mbar_arrive(sb + BAR_ZG);
        bulk_s2g((void*)(z2s + rb * B_SLOT), sb + OFF_A, B_SLOT);
        bulk_commit_wait();
        mbar_arrive(sb + BAR_ZP);
        STAMPE(58);
        red_release(p.scr->cnt + CNT_Z);
      }
      __syncwarp();
      STAMP(28);
      {
        uint32_t tp = clock();
#pragma unroll 1
        for (int i = 1; i < 16; i++) {
          pace(tp, PF_D);
          prefetch_l2(wq + i * 256);
          if (i == LKI) bar_sync(NB_KL, 160);
          if ((i == LKI || i == LKI + 1) && elect_one()) {
            kv_store(p, sb + OFF_A + 8 * A_SLOT + (i - LKI) * 4096, rb * 2 + (cb & 1), (cb >> 1) * 5 + 3 + i - LKI);
            bulk_commit_wait();
            if (i > LKI) red_relaxed(p.scr->cnt + CNT_KV + 2 + (cb >> 1));
          }
          __syncwarp();
          if (i == LKI + 1) STAMP(59);
        }
      }
      if (!EARLY) poll_counter(p.scr->cnt + CNT_KV + 2 + (cb >> 1), tag * 64);
      if (elect_one()) mbar_arrive(sb + BAR_KV2);
      STAMP(34);
      const uint8_t* hs = p.scr->h + (size_t)rb * 12 * A_SLOT;
#pragma unroll 1
      for (int i = 0; i < 3; i++) {
        mbar_wait(sb + BAR_HR - 16 + 8 * i, 0);
        if (elect_one()) bulk_s2g((void*)(hs + (cb * 3 + i) * A_SLOT), sb + OFF_A + i * A_SLOT, A_SLOT);
      }
      if (elect_one()) {
        st_relaxed(&p.scr->hflag[rb * 32 + cb * 8], tag);
        bulk_commit_wait();
      }
      __syncwarp();
      STAMP(20);
      if (!EARLY) poll_flags4(p.scr->hflag + rb * 32, tag, lane);
      { uint32_t tp = clock(); pace<false>(tp, HD); }
      STAMP(37);
#pragma unroll 1
      for (int it = 3; it < 12; it++) {
        const uint32_t land = sb + BAR_AF + 8 * (it < 9 ? it : it - 9);
        if (it == 9) mbar_wait2(sb + BAR_PART, 0, sb + BAR_B2, 0);
        if (elect_one()) { mbar_expect(land, A_SLOT); bulk_g2s(sb + h_pos(it), hs + g3_block(cb, it) * A_SLOT, A_SLOT, land); }
      }
      STAMP(21);
    } else if (warp == 14) {
      const uint32_t tag = load_epoch(p, lin, lane) + 1;
      const int tb = rb * 2 + (cb & 1), u0 = (cb >> 1) * 5;
      const uint32_t ks = sb + OFF_CV + CV_SZ, par = __shfl_sync(0xffffffff, tag, 0);
      {
        uint32_t tp = tstart;
        pace(tp, TP_T);
        const char* q = (const char*)p.ssmk + chb * 4096 + lane * 128;
        prefetch_l2(q); prefetch_l2(q + 64 * 4096);
      }
      mbar_wait2(sb + BAR_XS, 0, sb + BAR_ST, 0);
      bar_sync(NB_KU, 160);
      if (elect_one()) { kv_store(p, ks, tb, u0); kv_store(p, ks + 4096, tb, u0 + 1); bulk_commit_wait(); red_relaxed(p.scr->cnt + CNT_KV + (cb >> 1)); }
      __syncwarp();
      STAMP(35);
      bar_sync(NB_KU2, 160);
      if (elect_one()) { kv_store(p, ks + 8192, tb, u0 + 2); bulk_commit_wait(); }
      __syncwarp();
      zero_pads(ks, lane);
      bar_arrive(NB_G1D, 64);
      STAMP(30);
      {
        uint32_t tp = clock();
        const size_t o = (size_t)(tb * 32 + lane) * (kD * 2) + (u0 + 3) * 128;
        const char* r = (const char*)p.wout + (rb * 24 + min(lane, 23)) * (kD * 2) + cb * 320;
        const char* q = (const char*)p.ssmk + (chb + 128) * 4096 + lane * 128;
#pragma unroll 1
        for (int i = 0; i < 10; i++) {
          pace(tp, PF2_D);
          prefetch_l2(i < 3 ? q + i * 64 * 4096 : (i < 7 ? (const char*)((i & 1) ? p.k : p.v) + o + ((i - 3) >> 1) * 128 : r + (i - 7) * 128));
        }
      }
      conv_service(p, sb, 0, chb + 64, par, lane, NoHook());
      bar_sync(NB_CD, 64);
      STAMP(47);
      if (!EARLY) mbar_wait(sb + BAR_WE + 40, 0);
      { uint32_t tp = clock(); pace<false>(tp, YD); }
      if (elect_one()) {
        mbar_expect(sb + BAR_YT, 20480);
#pragma unroll 1
        for (int i = 0; i < 4; i++) tma2d(sb + OFF_CV + i * 5120, &p.tmY, rb * 64, cb * 160 + i * 40, sb + BAR_YT);
      }
      if (lane == 0) *(volatile uint32_t*)&p.scr->epoch[lin] = tag;
      STAMP(23);
    } else {
      const uint32_t tag = load_epoch(p, lin, lane) + 1;
      mbar_wait(sb + BAR_AF + 72, 0);
      { uint32_t tp = clock(); pace(tp, XSD); }
      {
        const uint32_t t8 = tag8(tag);
        const uint4 u = poll<false>([&]() { return ld_ll4(&p.scr->xstat[rb * 64 + lane * 2]); },
                                                [&](const uint4& v) { return (((v.x ^ t8) | (v.y ^ t8) | (v.z ^ t8) | (v.w ^ t8)) & 255u) == 0; });
        sts128(sb + OFF_XS + lane * 16, u.x, u.y, u.z, u.w);
      }
      __syncwarp();
      if (lane == 0) mbar_arrive(sb + BAR_XS);
      STAMP(25);
      const uint32_t par = __shfl_sync(0xffffffff, tag, 0);
      bar_sync(NB_G1D, 64);
      if (!EARLY) poll_counter(p.scr->cnt + CNT_KV + (cb >> 1), tag * 64);
      convx_issue(p, sb, 1, chb);
      convx_issue(p, sb, 0, chb + 64);
#pragma unroll 1
      for (int h = 1; h >= 0; h--) convx_finish(p, sb, h, chb + 64 - 64 * h, 0, par, lane);
      STAMP(48);
      gather_colsum(p, sb, 1, cb, tag8(tag), lane);
      STAMP(38);
      conv_service(p, sb, 1, chb, par, lane, [&]() {
        bar_sync(NB_WO, 160);
        if (elect_one()) red_release(p.scr->cnt + CNT_WO + cb);
        STAMP(49);
        poll_counter(p.scr->cnt + CNT_WO + cb, tag * 32);
        if (elect_one()) mbar_arrive(sb + BAR_WO);
        STAMP(46);
      });
      bar_arrive(NB_CD, 64);
    }
  } else if (warp >= 8) {
    const int w = warp & 3;
    {
      const int tid = tid_now();
      uint2* xs = &p.scr->xstat[rb * 64 + cb * 16 + (tid >> 3)];
      if ((tid & 7) == 0) st_ll2(xs, 0, 0);
      const uint32_t epoch = load_epoch(p, lin, lane);
      float sa[4] = {0.f, 0.f, 0.f, 0.f}, qa[4] = {0.f, 0.f, 0.f, 0.f};
#pragma unroll 1
      for (int i = 0; i < 10; i++) {
        mbar_wait(sb + BAR_AF + 8 * i, 0);
        const uint4 x4 = lds128(sb + OFF_A + i * A_SLOT + cb * 2048 + tid * 16);
        const uint32_t u[4] = {x4.x, x4.y, x4.z, x4.w};
#pragma unroll
        for (int e = 0; e < 4; e++) { const float a = bf_lo(u[e]), c = bf_hi(u[e]); sa[e] += a + c; qa[e] = fmaf(a, a, fmaf(c, c, qa[e])); }
      }
      float s = (sa[0] + sa[1]) + (sa[2] + sa[3]), q = (qa[0] + qa[1]) + (qa[2] + qa[3]);
#pragma unroll
      for (int o = 1; o <= 4; o <<= 1) { s += __shfl_xor_sync(0xffffffff, s, o); q += __shfl_xor_sync(0xffffffff, q, o); }
      const float m = s * (1.f / kD);
      const float r = rsqrtf(fmaxf(fmaf(-m, m, q * (1.f / kD)), 0.f) + 1e-5f);
      if ((tid & 7) == 0) st_ll2(xs, tagged(m, tag8(epoch + 1)), tagged(r, tag8(epoch + 1)));
      STAMPW(12); TR(70);
      fence_async_smem();
    }
    asm volatile("setmaxnreg.inc.sync.aligned.u32 160;");
    const unsigned short* bp = (const unsigned short*)p.bsp + rb * 64 + w * 16 + (lane >> 2);
    const uint32_t bias = bp[0] | ((uint32_t)bp[8] << 16);
    float d[96];
    uint32_t z[48];
    {
#pragma unroll
      for (int i = 0; i < 96; i++) d[i] = 0.f;
      bar_sync(NB_G1, 256);
      TR(71);
      gemm192<3>(d, sb, tid_now() == 0 TSA);
      mbar_arrive_if(sb + BAR_YT, tid_now() == 0);
      STAMPW(14); TR(74);
      mbar_wait2(sb + BAR_XS, 0, sb + BAR_ST + 8, 0);
      const uint32_t xa1 = sb + OFF_XS + (w * 16 + (lane >> 2)) * 8;
      gelu_tile<false>(d, z, nullptr, sb + OFF_CS + (lane & 3) * 8, lds64f(xa1), lds64f(xa1 + 64), sb + BAR_XS);
    }
#pragma unroll
    for (int j = 0; j < 96; j++) d[j] = (j & 2) ? bf_hi(bias) : bf_lo(bias);
    STAMPW(15); TR(76);
    gemm192<1>(d, sb, tid_now() == 0 TSA);
    STAMPW(16); TR(77);
    {
      const int l2 = tid_now() & 31;
      const uint32_t ha = swz_base(sb + OFF_A, w, l2);
      const bool tg = (l2 & 3) == (l2 >> 3);
      const uint32_t tm = tg ? ~1u : ~0u, tb = tg ? lds32<0>(sb + OFF_TAG) & 1 : 0;
#pragma unroll
      for (int j = 0; j < 24; j += 2) {
#pragma unroll
        for (int e = 0; e < 4; e++) z[2 * j + e] = hmul2(z[2 * j + e], pack2(d[4 * j + 2 * e], d[4 * j + 2 * e + 1]));
        stsm4((ha ^ ((j & 7) * 16)) + (j >> 3) * A_SLOT, (z[2 * j] & tm) | tb, (z[2 * j + 1] & tm) | tb, z[2 * j + 2], z[2 * j + 3]);
        if ((j & 7) == 6) {
          fence_async_smem();
          __syncwarp();
          mbar_arrive_if(sb + BAR_HR - 16 + (j >> 3) * 8, l2 == 0);
        }
      }
    }
    STAMPW(17); TR(78);
    const int t3 = tid_now();
    {
      acc_fence<40>(d);
      mbar_wait2(sb + BAR_HR, 0, sb + BAR_WF, 0);
      WG_FENCE();
      gemm3<0, 3, true>(d, sb, mkdesc(sb, 16, 1024, 1), mkdesc(sb, 2560, 128, 0), t3 == 0, 0 TSA);
      WG_WAIT(0);
      acc_fence<40>(d);
      TR(79);
#pragma unroll
      for (int j = 0; j < 5; j++)
        sts128(part_addr(sb, j, t3), pack2(d[8 * j], d[8 * j + 1]), pack2(d[8 * j + 2], d[8 * j + 3]), pack2(d[8 * j + 4], d[8 * j + 5]), pack2(d[8 * j + 6], d[8 * j + 7]));
      bar_sync(NB_C, 128);
      mbar_arrive_if(sb + BAR_PART, t3 == 0);
      STAMPW(45); TR(80);
    }
    {
      const uint32_t par = __shfl_sync(0xffffffff, lds32<0>(sb + OFF_TAG), 0), a = sb + w * 2048 + val_off(t3 & 31);
      const uint8_t* hs = p.scr->h + (size_t)rb * 12 * A_SLOT + w * 2048;
      const uint32_t rt = sb + OFF_RT + 8 * w;
#pragma unroll 1
      for (int it = 3; it < 12; it++) {
        mbar_wait(sb + BAR_AF + 8 * (it < 9 ? it : it - 9), 1);
        validate<2>(a + h_pos(it), par, rt, [&]() { bulk_g2s(sb + h_pos(it) + w * 2048, hs + g3_block(cb, it) * A_SLOT, 2048, rt); });
        if (elect_one()) mbar_arrive(sb + BAR_HV + 8 * (it - 3));
        if (it == 3) STAMPW(26);
      }
      {
        const int l = t3 & 31;
        mbar_wait(sb + BAR_YT, 1);
        validate<5>(sb + OFF_CV + w * 5120 + (l >> 2) * 128 + ((2 * (l & 3)) ^ (l >> 2)) * 16, par, rt, [&]() { tma2d(sb + OFF_CV + w * 5120, &p.tmY, rb * 64, cb * 160 + w * 40, rt); });
        bar_sync(NB_C, 128);
        mbar_arrive_if(sb + BAR_PART, t3 == 0);
        STAMPW(57);
      }
    }
  } else {
    const int h = warp >> 2, w = warp & 3;
    Taps k;
    asm volatile("setmaxnreg.inc.sync.aligned.u32 160;");
    if (h == 0) {
      uint4* zs = &p.scr->zstat[rb * 128 + w * 8 + (lane >> 2)];
      if ((lane & 3) == 0) st_ll4(zs + cb * 32, 0, 0, 0, 0);
      float d[96];
      uint32_t z[48];
#pragma unroll
      for (int i = 0; i < 96; i++) d[i] = 0.f;
      gemm192<0>(d, sb, tid_now() == 0 TSA, [&]() { bar_arrive(NB_G1, 256); });
      STAMPW(1); TR(0);
      const int tid = tid_now(), lane = tid & 31, g = lane >> 2, t = lane & 3;
      mbar_wait2(sb + BAR_XS, 0, sb + BAR_ST, 0);
      STAMPW(52); TR(1);
      const uint32_t xa1 = sb + OFF_XS + (w * 16 + g) * 8;
      const uint32_t tag = lds32<0>(sb + OFF_TAG);
      const float2 s0 = lds64f(xa1), s1 = lds64f(xa1 + 64);
      float st[4];
      gelu_tile<true>(d, z, st, sb + OFF_CS + 768 + t * 8, s0, s1, 0);
      TR(2);
      float2 sq = quad_sum(st, t);
      if (t < 2) st_ll2((uint2*)(zs + cb * 32) + t, tagged(sq.x, tag), __float_as_uint(sq.y));
      STAMPW(2); TR(3);
      { uint32_t tp = clock(); pace<false>(tp, ZW); }
      const uint4 u = poll<false>([&]() { return ld_ll4(zs + t * 32); }, [&](const uint4& v) { return (((v.x ^ tag) | (v.z ^ tag)) & 255u) == 0; });
      STAMPW(3); TR(10);
      st[0] = __uint_as_float(u.x); st[1] = __uint_as_float(u.y); st[2] = __uint_as_float(u.z); st[3] = __uint_as_float(u.w);
      sq = quad_sum(st, t);
      const float ca = 0.5f * ((t & 1) ? s1.y : s0.y), ma = sq.x * (1.f / 768.f);
      const float ra = ca * rsqrtf(fmaf(fmaxf(fmaf(-ma, ma, sq.y * (1.f / 768.f)), 0.f), ca * ca, 1e-5f));
      const uint32_t r2 = pack2(ra, ra);
      const float na = -ma * bf_lo(r2);
      const uint32_t n2 = pack2(na, na), r2o = __shfl_xor_sync(0xffffffff, r2, 1), n2o = __shfl_xor_sync(0xffffffff, n2, 1);
      const uint32_t fr[2] = {(t & 1) ? r2o : r2, (t & 1) ? r2 : r2o}, fn[2] = {(t & 1) ? n2o : n2, (t & 1) ? n2 : n2o};
      const uint32_t za = swz_base(sb + OFF_A, w, lane);
      TR(11);
      mbar_wait(sb + BAR_AE + 16, 0);
      TR(12);
#pragma unroll
      for (int j = 0; j < 24; j += 2)
        stsm4((za ^ ((j & 7) * 16)) + (j >> 3) * A_SLOT, hfma2(z[2 * j], fr[0], fn[0]), hfma2(z[2 * j + 1], fr[1], fn[1]), hfma2(z[2 * j + 2], fr[0], fn[0]), hfma2(z[2 * j + 3], fr[1], fn[1]));
      TR(14);
      fence_async_smem();
      bar_arrive(NB_Z, 160);
      STAMPW(4); TR(15);
      load_taps(k, p, chb + 64, tid);
    } else {
      if (w == 0) zero_pads(sb + OFF_CV, lane);
      const uint32_t epoch = load_epoch(p, lin, lane);
      const int t0 = (rb * 2 + (cb & 1)) * 32 + w * 8, c0 = (cb >> 1) * 320 + lane * 2;
      const __nv_bfloat16* kp = p.k + (size_t)(t0 - 3) * kD + c0;
      const __nv_bfloat16* vp = p.v + (size_t)t0 * kD + c0;
      const __nv_bfloat16* sp = p.shift + c0 * 4;
      const uint32_t oa = sb + OFF_CV + CV_SZ + kv_stage_addr(w, lane);
      bar_sync(NB_KF, 160);
      uint32_t tp = tstart;
      pace(tp, KV_T0);
      KvRegs n0, n1;
      uint32_t o[8];
      kv_load(n0, kp, vp, sp, t0 > 0);
      kv_load(n1, kp + 64, vp + 64, sp + 256, t0 > 0);
      const uint32_t tm = w >= 2 ? ~1u : ~0u, tb = w >= 2 ? (epoch + 1) & 1 : 0;
      kv_calc(n0, o);
      kv_put(o, oa, tm, tb);
      kv_calc(n1, o);
      kv_put(o, oa + 4096, tm, tb);
      fence_async_smem();
      bar_arrive(NB_KU, 160);
      TR(0);
      pace(tp, KV2T);
      kv_load(n0, kp + 128, vp + 128, sp + 512, t0 > 0);
      load_taps(k, p, chb, tid_now());
      kv_calc(n0, o);
      kv_put(o, oa + 8192, tm, tb);
      fence_async_smem();
      bar_arrive(NB_KU2, 160);
      STAMPW(13); TR(1);
    }
    uint32_t xw[2][10];
    {
      const int tid = tid_now();
      final_load_x(xw, p.x + (rb * 64 + w * 16 + ((tid & 31) >> 2)) * kD + cb * 160 + h * 80, tid & 3);
      conv_worker(p, k, sb, h, chb + 64 - 64 * h, w, tid & 31, tid, rb, cb TSA);
    }
    float d[40];
    const int t3 = tid_now();
    const uint32_t o0 = (rb * 64 + w * 16 + ((t3 & 31) >> 2)) * kD + cb * 160 + h * 80;
    float cf[2];
    uint32_t rn[4];
    const uint32_t xs_addr = sb + OFF_XS + (w * 16 + ((t3 & 31) >> 2)) * 8;
    TR(60);
    {
      const float2 s0 = lds64f(xs_addr), s1 = lds64f(xs_addr + 64);
      cf[0] = 0.25f * s0.y; cf[1] = 0.25f * s1.y;
      rn[0] = pack2(s0.y, s0.y); rn[1] = pack2(s1.y, s1.y);
      rn[2] = pack2(-s0.x * bf_lo(rn[0]), -s0.x * bf_lo(rn[0])); rn[3] = pack2(-s1.x * bf_lo(rn[1]), -s1.x * bf_lo(rn[1]));
    }
    const uint64_t da3 = mkdesc(sb, 16, 1024, 1), db3 = mkdesc(sb + h * 1280, 2560, 128, 0);
    if (h == 0) {
      mbar_wait(sb + BAR_PART, 0);
      TR(61);
#pragma unroll
      for (int j = 0; j < 5; j++) {
        const uint4 v = lds128(part_addr(sb, j, t3));
        d[8 * j] = bf_lo(v.x); d[8 * j + 1] = bf_hi(v.x); d[8 * j + 2] = bf_lo(v.y); d[8 * j + 3] = bf_hi(v.y);
        d[8 * j + 4] = bf_lo(v.z); d[8 * j + 5] = bf_hi(v.z); d[8 * j + 6] = bf_lo(v.w); d[8 * j + 7] = bf_hi(v.w);
      }
      fence_async_smem();
      bar_sync(NB_WG, 128);
      mbar_arrive_if(sb + BAR_WE + 16, t3 == 0);
      acc_fence<40>(d);
      mbar_wait2(sb + BAR_HV, 0, sb + w_full(3), 0);
    } else {
#pragma unroll
      for (int j = 0; j < 40; j++) d[j] = 0.f;
      acc_fence<40>(d);
      mbar_wait2(sb + BAR_HR, 0, sb + BAR_WF, 0);
      WG_FENCE();
      gemm3<0, 3, false>(d, sb, da3, db3, t3 == 0, 0 TSA);
    }
    TR(62);
    if (h == 0) STAMPW(36);
    WG_FENCE();
    gemm3<3, 12, false>(d, sb, da3, db3, t3 == 0, h && t3 == 0 TSA);
    WG_WAIT(0);
    GSTAMP(2, 12);
    acc_fence<40>(d);
    STAMPW(h ? 18 : 10);
    TR(63);
    const int l3 = tid_now() & 31;
    final_out(d, xw, rn, cf, sb + OFF_CV + h * 10240, p.out + o0, w, l3, [&]() {
      STAMPW(h ? 44 : 9);
      TR(64);
      mbar_wait(sb + BAR_PART, 1);
      TR(65);
    });
    TR(66);
    mbar_arrive_if(sb + BAR_WE, t3 == 0);
  }
}

typedef CUresult (*EncodeFn)(CUtensorMap*, CUtensorMapDataType, cuuint32_t, void*, const cuuint64_t*, const cuuint64_t*, const cuuint32_t*,
                             const cuuint32_t*, CUtensorMapInterleave, CUtensorMapSwizzle, CUtensorMapL2promotion, CUtensorMapFloatOOBfill);

void encode(EncodeFn fn, CUtensorMap* m, const void* ptr, int rank, const cuuint64_t* dims, const cuuint64_t* strides, const cuuint32_t* box,
            CUtensorMapSwizzle swz = CU_TENSOR_MAP_SWIZZLE_128B) {
  const cuuint32_t es[3] = {1, 1, 1};
  fn(m, CU_TENSOR_MAP_DATA_TYPE_BFLOAT16, rank, const_cast<void*>(ptr), dims, strides, box, es, CU_TENSOR_MAP_INTERLEAVE_NONE,
     swz, CU_TENSOR_MAP_L2_PROMOTION_L2_128B, CU_TENSOR_MAP_FLOAT_OOB_FILL_NONE);
}

}

extern "C" void kernel_launch(void* const* d_in, const int* in_sizes, int n_in, void* d_out, int out_size) {
  (void)in_sizes; (void)n_in; (void)out_size;
  static EncodeFn enc = nullptr;
  static Scratch* scr = nullptr;
  static int sms = 0;
  if (!enc) {
    void* fn = nullptr;
    cudaDriverEntryPointQueryResult qr;
    cudaGetDriverEntryPoint("cuTensorMapEncodeTiled", &fn, cudaEnableDefault, &qr);
    enc = (EncodeFn)fn;
    cudaFuncSetAttribute(fused_kernel, cudaFuncAttributeMaxDynamicSharedMemorySize, SMEM_BYTES);
    cudaGetSymbolAddress((void**)&scr, g_scr);
    int dev = 0;
    cudaGetDevice(&dev);
    cudaDeviceGetAttribute(&sms, cudaDevAttrMultiProcessorCount, dev);
  }
  Params p;
  p.scr = scr;
  p.by_smid = sms == 132;
  for (int b = 0; b < 132; b++) {
    const int tp = b >> 1, t7 = (tp - 32) / 7;
    const int lin = tp < 32 ? ((tp & 7) ? (tp & 7) * 16 : 8) + (tp >> 3) * 2 + (b & 1)
                            : (tp < 60 ? (tp - 31 - t7 * 7) * 16 + 8 + t7 * 2 + (b & 1) : (tp < 62 ? 128 + (b & 3) : b - 124));
    const int cb = ((lin >> 4) & 1) * 2 + (lin & 1), rb = (lin >> 5) * 8 + ((lin >> 1) & 7);
    p.job[b] = lin < 128 ? lin | cb << 8 | rb << 10 : lin | (lin & 3) << 8;
  }
  p.x = (const __nv_bfloat16*)d_in[0];
  p.k = (const __nv_bfloat16*)d_in[1];
  p.v = (const __nv_bfloat16*)d_in[2];
  p.shift = (const __nv_bfloat16*)d_in[3];
  p.ssmk = (const __nv_bfloat16*)d_in[4];
  p.ssmD = (const __nv_bfloat16*)d_in[5];
  p.wsp = (const __nv_bfloat16*)d_in[8];
  p.bsp = (const __nv_bfloat16*)d_in[9];
  p.wout = (const __nv_bfloat16*)d_in[10];
  p.out = (__nv_bfloat16*)d_out;
  {
    const cuuint64_t dims[2] = {kD, kS}, st[1] = {kD * 2};
    const cuuint32_t box[2] = {64, 64};
    encode(enc, &p.tmX, d_in[0], 2, dims, st, box);
  }
  {
    const cuuint64_t dims[3] = {64, kD, kF / 64}, st[2] = {kF * 2, 128};
    const cuuint32_t box[3] = {64, 64, 3};
    encode(enc, &p.tmW, d_in[7], 3, dims, st, box);
  }
  {
    const cuuint64_t dims[2] = {kS, kS}, st[1] = {kS * 2};
    const cuuint32_t box[2] = {64, 64};
    encode(enc, &p.tmWsp, d_in[8], 2, dims, st, box);
  }
  {
    const cuuint64_t dims[2] = {kS, kD}, st[1] = {kS * 2};
    const cuuint32_t box[2] = {64, 40};
    encode(enc, &p.tmY, scr->y, 2, dims, st, box);
  }
  {
    const cuuint64_t dims[3] = {1024, kD / 2, 4}, st[2] = {8192, 2048};
    const cuuint32_t box[3] = {16, 32, 4};
    encode(enc, &p.tmKV, scr->kvx, 3, dims, st, box, CU_TENSOR_MAP_SWIZZLE_32B);
  }
  fused_kernel<<<132, 512, SMEM_BYTES, cudaStreamPerThread>>>(p);
}
```

```cpp
#include <cuda_runtime.h>
#include <cuda.h>
#include <cuda_bf16.h>
#include <stdint.h>

template <int N> struct WG;
template <> struct WG<16> {
  static __device__ __forceinline__ void rs(float* d, const uint32_t* a, uint64_t db) {
    asm volatile("{\n.reg .pred p;\nsetp.ne.b32 p, 1, 0;\nwgmma.mma_async.sync.aligned.m64n16k16.f32.bf16.bf16 {"
      "%0, %1, %2, %3, %4, %5, %6, %7"
      "}, {%8, %9, %10, %11}, %12, p, 1, 1, 0;\n}\n"
      :
      "+f"(d[0]), "+f"(d[1]), "+f"(d[2]), "+f"(d[3]), "+f"(d[4]), "+f"(d[5]), "+f"(d[6]), "+f"(d[7])
      : "r"(a[0]), "r"(a[1]), "r"(a[2]), "r"(a[3]), "l"(db));
  }
};
template <> struct WG<32> {
  static __device__ __forceinline__ void rs(float* d, const uint32_t* a, uint64_t db) {
    asm volatile("{\n.reg .pred p;\nsetp.ne.b32 p, 1, 0;\nwgmma.mma_async.sync.aligned.m64n32k16.f32.bf16.bf16 {"
      "%0, %1, %2, %3, %4, %5, %6, %7, %8, %9, %10, %11, %12, %13, %14, %15"
      "}, {%16, %17, %18, %19}, %20, p, 1, 1, 0;\n}\n"
      :
      "+f"(d[0]), "+f"(d[1]), "+f"(d[2]), "+f"(d[3]), "+f"(d[4]), "+f"(d[5]), "+f"(d[6]), "+f"(d[7]),
      "+f"(d[8]), "+f"(d[9]), "+f"(d[10]), "+f"(d[11]), "+f"(d[12]), "+f"(d[13]), "+f"(d[14]), "+f"(d[15])
      : "r"(a[0]), "r"(a[1]), "r"(a[2]), "r"(a[3]), "l"(db));
  }
};
template <> struct WG<48> {
  static __device__ __forceinline__ void rs(float* d, const uint32_t* a, uint64_t db) {
    asm volatile("{\n.reg .pred p;\nsetp.ne.b32 p, 1, 0;\nwgmma.mma_async.sync.aligned.m64n48k16.f32.bf16.bf16 {"
      "%0, %1, %2, %3, %4, %5, %6, %7, %8, %9, %10, %11, %12, %13, %14, %15, "
      "%16, %17, %18, %19, %20, %21, %22, %23"
      "}, {%24, %25, %26, %27}, %28, p, 1, 1, 0;\n}\n"
      :
      "+f"(d[0]), "+f"(d[1]), "+f"(d[2]), "+f"(d[3]), "+f"(d[4]), "+f"(d[5]), "+f"(d[6]), "+f"(d[7]),
      "+f"(d[8]), "+f"(d[9]), "+f"(d[10]), "+f"(d[11]), "+f"(d[12]), "+f"(d[13]), "+f"(d[14]), "+f"(d[15]),
      "+f"(d[16]), "+f"(d[17]), "+f"(d[18]), "+f"(d[19]), "+f"(d[20]), "+f"(d[21]), "+f"(d[22]), "+f"(d[23])
      : "r"(a[0]), "r"(a[1]), "r"(a[2]), "r"(a[3]), "l"(db));
  }
};
template <> struct WG<64> {
  static __device__ __forceinline__ void rs(float* d, const uint32_t* a, uint64_t db) {
    asm volatile("{\n.reg .pred p;\nsetp.ne.b32 p, 1, 0;\nwgmma.mma_async.sync.aligned.m64n64k16.f32.bf16.bf16 {"
      "%0, %1, %2, %3, %4, %5, %6, %7, %8, %9, %10, %11, %12, %13, %14, %15, "
      "%16, %17, %18, %19, %20, %21, %22, %23, %24, %25, %26, %27, %28, %29, %30, %31"
      "}, {%32, %33, %34, %35}, %36, p, 1, 1, 0;\n}\n"
      :
      "+f"(d[0]), "+f"(d[1]), "+f"(d[2]), "+f"(d[3]), "+f"(d[4]), "+f"(d[5]), "+f"(d[6]), "+f"(d[7]),
      "+f"(d[8]), "+f"(d[9]), "+f"(d[10]), "+f"(d[11]), "+f"(d[12]), "+f"(d[13]), "+f"(d[14]), "+f"(d[15]),
      "+f"(d[16]), "+f"(d[17]), "+f"(d[18]), "+f"(d[19]), "+f"(d[20]), "+f"(d[21]), "+f"(d[22]), "+f"(d[23]),
      "+f"(d[24]), "+f"(d[25]), "+f"(d[26]), "+f"(d[27]), "+f"(d[28]), "+f"(d[29]), "+f"(d[30]), "+f"(d[31])
      : "r"(a[0]), "r"(a[1]), "r"(a[2]), "r"(a[3]), "l"(db));
  }
};
template <> struct WG<80> {
  static __device__ __forceinline__ void rs(float* d, const uint32_t* a, uint64_t db) {
    asm volatile("{\n.reg .pred p;\nsetp.ne.b32 p, 1, 0;\nwgmma.mma_async.sync.aligned.m64n80k16.f32.bf16.bf16 {"
      "%0, %1, %2, %3, %4, %5, %6, %7, %8, %9, %10, %11, %12, %13, %14, %15, "
      "%16, %17, %18, %19, %20, %21, %22, %23, %24, %25, %26, %27, %28, %29, %30, %31, "
      "%32, %33, %34, %35, %36, %37, %38, %39"
      "}, {%40, %41, %42, %43}, %44, p, 1, 1, 0;\n}\n"
      :
      "+f"(d[0]), "+f"(d[1]), "+f"(d[2]), "+f"(d[3]), "+f"(d[4]), "+f"(d[5]), "+f"(d[6]), "+f"(d[7]),
      "+f"(d[8]), "+f"(d[9]), "+f"(d[10]), "+f"(d[11]), "+f"(d[12]), "+f"(d[13]), "+f"(d[14]), "+f"(d[15]),
      "+f"(d[16]), "+f"(d[17]), "+f"(d[18]), "+f"(d[19]), "+f"(d[20]), "+f"(d[21]), "+f"(d[22]), "+f"(d[23]),
      "+f"(d[24]), "+f"(d[25]), "+f"(d[26]), "+f"(d[27]), "+f"(d[28]), "+f"(d[29]), "+f"(d[30]), "+f"(d[31]),
      "+f"(d[32]), "+f"(d[33]), "+f"(d[34]), "+f"(d[35]), "+f"(d[36]), "+f"(d[37]), "+f"(d[38]), "+f"(d[39])
      : "r"(a[0]), "r"(a[1]), "r"(a[2]), "r"(a[3]), "l"(db));
  }
};
template <> struct WG<96> {
  static __device__ __forceinline__ void rs(float* d, const uint32_t* a, uint64_t db) {
    asm volatile("{\n.reg .pred p;\nsetp.ne.b32 p, 1, 0;\nwgmma.mma_async.sync.aligned.m64n96k16.f32.bf16.bf16 {"
      "%0, %1, %2, %3, %4, %5, %6, %7, %8, %9, %10, %11, %12, %13, %14, %15, "
      "%16, %17, %18, %19, %20, %21, %22, %23, %24, %25, %26, %27, %28, %29, %30, %31, "
      "%32, %33, %34, %35, %36, %37, %38, %39, %40, %41, %42, %43, %44, %45, %46, %47"
      "}, {%48, %49, %50, %51}, %52, p, 1, 1, 0;\n}\n"
      :
      "+f"(d[0]), "+f"(d[1]), "+f"(d[2]), "+f"(d[3]), "+f"(d[4]), "+f"(d[5]), "+f"(d[6]), "+f"(d[7]),
      "+f"(d[8]), "+f"(d[9]), "+f"(d[10]), "+f"(d[11]), "+f"(d[12]), "+f"(d[13]), "+f"(d[14]), "+f"(d[15]),
      "+f"(d[16]), "+f"(d[17]), "+f"(d[18]), "+f"(d[19]), "+f"(d[20]), "+f"(d[21]), "+f"(d[22]), "+f"(d[23]),
      "+f"(d[24]), "+f"(d[25]), "+f"(d[26]), "+f"(d[27]), "+f"(d[28]), "+f"(d[29]), "+f"(d[30]), "+f"(d[31]),
      "+f"(d[32]), "+f"(d[33]), "+f"(d[34]), "+f"(d[35]), "+f"(d[36]), "+f"(d[37]), "+f"(d[38]), "+f"(d[39]),
      "+f"(d[40]), "+f"(d[41]), "+f"(d[42]), "+f"(d[43]), "+f"(d[44]), "+f"(d[45]), "+f"(d[46]), "+f"(d[47])
      : "r"(a[0]), "r"(a[1]), "r"(a[2]), "r"(a[3]), "l"(db));
  }
};
template <> struct WG<112> {
  static __device__ __forceinline__ void rs(float* d, const uint32_t* a, uint64_t db) {
    asm volatile("{\n.reg .pred p;\nsetp.ne.b32 p, 1, 0;\nwgmma.mma_async.sync.aligned.m64n112k16.f32.bf16.bf16 {"
      "%0, %1, %2, %3, %4, %5, %6, %7, %8, %9, %10, %11, %12, %13, %14, %15, "
      "%16, %17, %18, %19, %20, %21, %22, %23, %24, %25, %26, %27, %28, %29, %30, %31, "
      "%32, %33, %34, %35, %36, %37, %38, %39, %40, %41, %42, %43, %44, %45, %46, %47, "
      "%48, %49, %50, %51, %52, %53, %54, %55"
      "}, {%56, %57, %58, %59}, %60, p, 1, 1, 0;\n}\n"
      :
      "+f"(d[0]), "+f"(d[1]), "+f"(d[2]), "+f"(d[3]), "+f"(d[4]), "+f"(d[5]), "+f"(d[6]), "+f"(d[7]),
      "+f"(d[8]), "+f"(d[9]), "+f"(d[10]), "+f"(d[11]), "+f"(d[12]), "+f"(d[13]), "+f"(d[14]), "+f"(d[15]),
      "+f"(d[16]), "+f"(d[17]), "+f"(d[18]), "+f"(d[19]), "+f"(d[20]), "+f"(d[21]), "+f"(d[22]), "+f"(d[23]),
      "+f"(d[24]), "+f"(d[25]), "+f"(d[26]), "+f"(d[27]), "+f"(d[28]), "+f"(d[29]), "+f"(d[30]), "+f"(d[31]),
      "+f"(d[32]), "+f"(d[33]), "+f"(d[34]), "+f"(d[35]), "+f"(d[36]), "+f"(d[37]), "+f"(d[38]), "+f"(d[39]),
      "+f"(d[40]), "+f"(d[41]), "+f"(d[42]), "+f"(d[43]), "+f"(d[44]), "+f"(d[45]), "+f"(d[46]), "+f"(d[47]),
      "+f"(d[48]), "+f"(d[49]), "+f"(d[50]), "+f"(d[51]), "+f"(d[52]), "+f"(d[53]), "+f"(d[54]), "+f"(d[55])
      : "r"(a[0]), "r"(a[1]), "r"(a[2]), "r"(a[3]), "l"(db));
  }
};
template <> struct WG<128> {
  static __device__ __forceinline__ void rs(float* d, const uint32_t* a, uint64_t db) {
    asm volatile("{\n.reg .pred p;\nsetp.ne.b32 p, 1, 0;\nwgmma.mma_async.sync.aligned.m64n128k16.f32.bf16.bf16 {"
      "%0, %1, %2, %3, %4, %5, %6, %7, %8, %9, %10, %11, %12, %13, %14, %15, "
      "%16, %17, %18, %19, %20, %21, %22, %23, %24, %25, %26, %27, %28, %29, %30, %31, "
      "%32, %33, %34, %35, %36, %37, %38, %39, %40, %41, %42, %43, %44, %45, %46, %47, "
      "%48, %49, %50, %51, %52, %53, %54, %55, %56, %57, %58, %59, %60, %61, %62, %63"
      "}, {%64, %65, %66, %67}, %68, p, 1, 1, 0;\n}\n"
      :
      "+f"(d[0]), "+f"(d[1]), "+f"(d[2]), "+f"(d[3]), "+f"(d[4]), "+f"(d[5]), "+f"(d[6]), "+f"(d[7]),
      "+f"(d[8]), "+f"(d[9]), "+f"(d[10]), "+f"(d[11]), "+f"(d[12]), "+f"(d[13]), "+f"(d[14]), "+f"(d[15]),
      "+f"(d[16]), "+f"(d[17]), "+f"(d[18]), "+f"(d[19]), "+f"(d[20]), "+f"(d[21]), "+f"(d[22]), "+f"(d[23]),
      "+f"(d[24]), "+f"(d[25]), "+f"(d[26]), "+f"(d[27]), "+f"(d[28]), "+f"(d[29]), "+f"(d[30]), "+f"(d[31]),
      "+f"(d[32]), "+f"(d[33]), "+f"(d[34]), "+f"(d[35]), "+f"(d[36]), "+f"(d[37]), "+f"(d[38]), "+f"(d[39]),
      "+f"(d[40]), "+f"(d[41]), "+f"(d[42]), "+f"(d[43]), "+f"(d[44]), "+f"(d[45]), "+f"(d[46]), "+f"(d[47]),
      "+f"(d[48]), "+f"(d[49]), "+f"(d[50]), "+f"(d[51]), "+f"(d[52]), "+f"(d[53]), "+f"(d[54]), "+f"(d[55]),
      "+f"(d[56]), "+f"(d[57]), "+f"(d[58]), "+f"(d[59]), "+f"(d[60]), "+f"(d[61]), "+f"(d[62]), "+f"(d[63])
      : "r"(a[0]), "r"(a[1]), "r"(a[2]), "r"(a[3]), "l"(db));
  }
};
template <int N> struct KB;
template <> struct KB<80> {
  template <int W, int RC, int RA, int BSTEP> static __device__ __forceinline__ void run(float* d, uint64_t da, uint64_t db, uint32_t rel, uint32_t rela, uint32_t doR, uint32_t fa, uint32_t pa, uint32_t fb, uint32_t pb, uint32_t acc) {
    if constexpr (W == 0 && RC == 0 && RA == 0) asm volatile(
    "{\n.reg .pred p, q, r, t;\n.reg .b64 a, b;\n.reg .u32 n;\nsetp.ne.b32 t, 1, 0;\nsetp.ne.b32 r, %49, 0;\n"
    "wgmma.mma_async.sync.aligned.m64n80k16.f32.bf16.bf16 {"
      "%0, %1, %2, %3, %4, %5, %6, %7, %8, %9, %10, %11, %12, %13, %14, %15, "
      "%16, %17, %18, %19, %20, %21, %22, %23, %24, %25, %26, %27, %28, %29, %30, %31, "
      "%32, %33, %34, %35, %36, %37, %38, %39"
      "}, %40, %41, r, 1, 1, 0, 1;\n"
    "add.u64 a, %40, 2;\nadd.u64 b, %41, %48;\n"
    "wgmma.mma_async.sync.aligned.m64n80k16.f32.bf16.bf16 {"
      "%0, %1, %2, %3, %4, %5, %6, %7, %8, %9, %10, %11, %12, %13, %14, %15, "
      "%16, %17, %18, %19, %20, %21, %22, %23, %24, %25, %26, %27, %28, %29, %30, %31, "
      "%32, %33, %34, %35, %36, %37, %38, %39"
      "}, a, b, t, 1, 1, 0, 1;\n"
    "wgmma.commit_group.sync.aligned;\nwgmma.wait_group.sync.aligned 1;\n"
    "add.u64 a, %40, 4;\nadd.u64 b, %41, 2*%48;\n"
    "wgmma.mma_async.sync.aligned.m64n80k16.f32.bf16.bf16 {"
      "%0, %1, %2, %3, %4, %5, %6, %7, %8, %9, %10, %11, %12, %13, %14, %15, "
      "%16, %17, %18, %19, %20, %21, %22, %23, %24, %25, %26, %27, %28, %29, %30, %31, "
      "%32, %33, %34, %35, %36, %37, %38, %39"
      "}, a, b, t, 1, 1, 0, 1;\n"
    "add.u64 a, %40, 6;\nadd.u64 b, %41, 3*%48;\n"
    "wgmma.mma_async.sync.aligned.m64n80k16.f32.bf16.bf16 {"
      "%0, %1, %2, %3, %4, %5, %6, %7, %8, %9, %10, %11, %12, %13, %14, %15, "
      "%16, %17, %18, %19, %20, %21, %22, %23, %24, %25, %26, %27, %28, %29, %30, %31, "
      "%32, %33, %34, %35, %36, %37, %38, %39"
      "}, a, b, t, 1, 1, 0, 1;\n"
    "wgmma.commit_group.sync.aligned;\n"
    "}\n"
      :
      "+f"(d[0]), "+f"(d[1]), "+f"(d[2]), "+f"(d[3]), "+f"(d[4]), "+f"(d[5]), "+f"(d[6]), "+f"(d[7]),
      "+f"(d[8]), "+f"(d[9]), "+f"(d[10]), "+f"(d[11]), "+f"(d[12]), "+f"(d[13]), "+f"(d[14]), "+f"(d[15]),
      "+f"(d[16]), "+f"(d[17]), "+f"(d[18]), "+f"(d[19]), "+f"(d[20]), "+f"(d[21]), "+f"(d[22]), "+f"(d[23]),
      "+f"(d[24]), "+f"(d[25]), "+f"(d[26]), "+f"(d[27]), "+f"(d[28]), "+f"(d[29]), "+f"(d[30]), "+f"(d[31]),
      "+f"(d[32]), "+f"(d[33]), "+f"(d[34]), "+f"(d[35]), "+f"(d[36]), "+f"(d[37]), "+f"(d[38]), "+f"(d[39])
      : "l"(da), "l"(db), "r"(rel), "r"(doR), "r"(fa), "r"(pa), "r"(fb), "r"(pb), "n"(BSTEP), "r"(acc), "r"(rela) : "memory");
    else if constexpr (W == 0 && RC == 1 && RA == 0) asm volatile(
    "{\n.reg .pred p, q, r, t;\n.reg .b64 a, b;\n.reg .u32 n;\nsetp.ne.b32 t, 1, 0;\nsetp.ne.b32 r, %49, 0;\n"
    "wgmma.mma_async.sync.aligned.m64n80k16.f32.bf16.bf16 {"
      "%0, %1, %2, %3, %4, %5, %6, %7, %8, %9, %10, %11, %12, %13, %14, %15, "
      "%16, %17, %18, %19, %20, %21, %22, %23, %24, %25, %26, %27, %28, %29, %30, %31, "
      "%32, %33, %34, %35, %36, %37, %38, %39"
      "}, %40, %41, r, 1, 1, 0, 1;\n"
    "add.u64 a, %40, 2;\nadd.u64 b, %41, %48;\n"
    "wgmma.mma_async.sync.aligned.m64n80k16.f32.bf16.bf16 {"
      "%0, %1, %2, %3, %4, %5, %6, %7, %8, %9, %10, %11, %12, %13, %14, %15, "
      "%16, %17, %18, %19, %20, %21, %22, %23, %24, %25, %26, %27, %28, %29, %30, %31, "
      "%32, %33, %34, %35, %36, %37, %38, %39"
      "}, a, b, t, 1, 1, 0, 1;\n"
    "wgmma.commit_group.sync.aligned;\nwgmma.wait_group.sync.aligned 1;\n"
    "add.u64 a, %40, 4;\nadd.u64 b, %41, 2*%48;\n"
    "wgmma.mma_async.sync.aligned.m64n80k16.f32.bf16.bf16 {"
      "%0, %1, %2, %3, %4, %5, %6, %7, %8, %9, %10, %11, %12, %13, %14, %15, "
      "%16, %17, %18, %19, %20, %21, %22, %23, %24, %25, %26, %27, %28, %29, %30, %31, "
      "%32, %33, %34, %35, %36, %37, %38, %39"
      "}, a, b, t, 1, 1, 0, 1;\n"
    "setp.ne.u32 q, %43, 0;\n@q mbarrier.arrive.shared::cta.b64 _, [%42];\n"
    "add.u64 a, %40, 6;\nadd.u64 b, %41, 3*%48;\n"
    "wgmma.mma_async.sync.aligned.m64n80k16.f32.bf16.bf16 {"
      "%0, %1, %2, %3, %4, %5, %6, %7, %8, %9, %10, %11, %12, %13, %14, %15, "
      "%16, %17, %18, %19, %20, %21, %22, %23, %24, %25, %26, %27, %28, %29, %30, %31, "
      "%32, %33, %34, %35, %36, %37, %38, %39"
      "}, a, b, t, 1, 1, 0, 1;\n"
    "wgmma.commit_group.sync.aligned;\n"
    "}\n"
      :
      "+f"(d[0]), "+f"(d[1]), "+f"(d[2]), "+f"(d[3]), "+f"(d[4]), "+f"(d[5]), "+f"(d[6]), "+f"(d[7]),
      "+f"(d[8]), "+f"(d[9]), "+f"(d[10]), "+f"(d[11]), "+f"(d[12]), "+f"(d[13]), "+f"(d[14]), "+f"(d[15]),
      "+f"(d[16]), "+f"(d[17]), "+f"(d[18]), "+f"(d[19]), "+f"(d[20]), "+f"(d[21]), "+f"(d[22]), "+f"(d[23]),
      "+f"(d[24]), "+f"(d[25]), "+f"(d[26]), "+f"(d[27]), "+f"(d[28]), "+f"(d[29]), "+f"(d[30]), "+f"(d[31]),
      "+f"(d[32]), "+f"(d[33]), "+f"(d[34]), "+f"(d[35]), "+f"(d[36]), "+f"(d[37]), "+f"(d[38]), "+f"(d[39])
      : "l"(da), "l"(db), "r"(rel), "r"(doR), "r"(fa), "r"(pa), "r"(fb), "r"(pb), "n"(BSTEP), "r"(acc), "r"(rela) : "memory");
    else if constexpr (W == 1 && RC == 0 && RA == 0) asm volatile(
    "{\n.reg .pred p, q, r, t;\n.reg .b64 a, b;\n.reg .u32 n;\nsetp.ne.b32 t, 1, 0;\nsetp.ne.b32 r, %49, 0;\n"
    "wgmma.mma_async.sync.aligned.m64n80k16.f32.bf16.bf16 {"
      "%0, %1, %2, %3, %4, %5, %6, %7, %8, %9, %10, %11, %12, %13, %14, %15, "
      "%16, %17, %18, %19, %20, %21, %22, %23, %24, %25, %26, %27, %28, %29, %30, %31, "
      "%32, %33, %34, %35, %36, %37, %38, %39"
      "}, %40, %41, r, 1, 1, 0, 1;\n"
    "add.u64 a, %40, 2;\nadd.u64 b, %41, %48;\n"
    "wgmma.mma_async.sync.aligned.m64n80k16.f32.bf16.bf16 {"
      "%0, %1, %2, %3, %4, %5, %6, %7, %8, %9, %10, %11, %12, %13, %14, %15, "
      "%16, %17, %18, %19, %20, %21, %22, %23, %24, %25, %26, %27, %28, %29, %30, %31, "
      "%32, %33, %34, %35, %36, %37, %38, %39"
      "}, a, b, t, 1, 1, 0, 1;\n"
    "wgmma.commit_group.sync.aligned;\nwgmma.wait_group.sync.aligned 1;\n"
    "add.u64 a, %40, 4;\nadd.u64 b, %41, 2*%48;\n"
    "wgmma.mma_async.sync.aligned.m64n80k16.f32.bf16.bf16 {"
      "%0, %1, %2, %3, %4, %5, %6, %7, %8, %9, %10, %11, %12, %13, %14, %15, "
      "%16, %17, %18, %19, %20, %21, %22, %23, %24, %25, %26, %27, %28, %29, %30, %31, "
      "%32, %33, %34, %35, %36, %37, %38, %39"
      "}, a, b, t, 1, 1, 0, 1;\n"
    "mbarrier.test_wait.parity.shared::cta.b64 p, [%46], %47;\n"
    "add.u64 a, %40, 6;\nadd.u64 b, %41, 3*%48;\n"
    "wgmma.mma_async.sync.aligned.m64n80k16.f32.bf16.bf16 {"
      "%0, %1, %2, %3, %4, %5, %6, %7, %8, %9, %10, %11, %12, %13, %14, %15, "
      "%16, %17, %18, %19, %20, %21, %22, %23, %24, %25, %26, %27, %28, %29, %30, %31, "
      "%32, %33, %34, %35, %36, %37, %38, %39"
      "}, a, b, t, 1, 1, 0, 1;\n"
    "wgmma.commit_group.sync.aligned;\n"
    "@p bra.uni DN;\nmov.u32 n, 0;\nWT: mbarrier.try_wait.parity.shared::cta.b64 p, [%46], %47;\n@p bra.uni DN;\nadd.u32 n, n, 1;\nsetp.lt.u32 p, n, 0x100000;\n@p bra.uni WT;\nDN:\n"
    "}\n"
      :
      "+f"(d[0]), "+f"(d[1]), "+f"(d[2]), "+f"(d[3]), "+f"(d[4]), "+f"(d[5]), "+f"(d[6]), "+f"(d[7]),
      "+f"(d[8]), "+f"(d[9]), "+f"(d[10]), "+f"(d[11]), "+f"(d[12]), "+f"(d[13]), "+f"(d[14]), "+f"(d[15]),
      "+f"(d[16]), "+f"(d[17]), "+f"(d[18]), "+f"(d[19]), "+f"(d[20]), "+f"(d[21]), "+f"(d[22]), "+f"(d[23]),
      "+f"(d[24]), "+f"(d[25]), "+f"(d[26]), "+f"(d[27]), "+f"(d[28]), "+f"(d[29]), "+f"(d[30]), "+f"(d[31]),
      "+f"(d[32]), "+f"(d[33]), "+f"(d[34]), "+f"(d[35]), "+f"(d[36]), "+f"(d[37]), "+f"(d[38]), "+f"(d[39])
      : "l"(da), "l"(db), "r"(rel), "r"(doR), "r"(fa), "r"(pa), "r"(fb), "r"(pb), "n"(BSTEP), "r"(acc), "r"(rela) : "memory");
    else if constexpr (W == 1 && RC == 1 && RA == 0) asm volatile(
    "{\n.reg .pred p, q, r, t;\n.reg .b64 a, b;\n.reg .u32 n;\nsetp.ne.b32 t, 1, 0;\nsetp.ne.b32 r, %49, 0;\n"
    "wgmma.mma_async.sync.aligned.m64n80k16.f32.bf16.bf16 {"
      "%0, %1, %2, %3, %4, %5, %6, %7, %8, %9, %10, %11, %12, %13, %14, %15, "
      "%16, %17, %18, %19, %20, %21, %22, %23, %24, %25, %26, %27, %28, %29, %30, %31, "
      "%32, %33, %34, %35, %36, %37, %38, %39"
      "}, %40, %41, r, 1, 1, 0, 1;\n"
    "add.u64 a, %40, 2;\nadd.u64 b, %41, %48;\n"
    "wgmma.mma_async.sync.aligned.m64n80k16.f32.bf16.bf16 {"
      "%0, %1, %2, %3, %4, %5, %6, %7, %8, %9, %10, %11, %12, %13, %14, %15, "
      "%16, %17, %18, %19, %20, %21, %22, %23, %24, %25, %26, %27, %28, %29, %30, %31, "
      "%32, %33, %34, %35, %36, %37, %38, %39"
      "}, a, b, t, 1, 1, 0, 1;\n"
    "wgmma.commit_group.sync.aligned;\nwgmma.wait_group.sync.aligned 1;\n"
    "add.u64 a, %40, 4;\nadd.u64 b, %41, 2*%48;\n"
    "wgmma.mma_async.sync.aligned.m64n80k16.f32.bf16.bf16 {"
      "%0, %1, %2, %3, %4, %5, %6, %7, %8, %9, %10, %11, %12, %13, %14, %15, "
      "%16, %17, %18, %19, %20, %21, %22, %23, %24, %25, %26, %27, %28, %29, %30, %31, "
      "%32, %33, %34, %35, %36, %37, %38, %39"
      "}, a, b, t, 1, 1, 0, 1;\n"
    "setp.ne.u32 q, %43, 0;\n@q mbarrier.arrive.shared::cta.b64 _, [%42];\n"
    "mbarrier.test_wait.parity.shared::cta.b64 p, [%46], %47;\n"
    "add.u64 a, %40, 6;\nadd.u64 b, %41, 3*%48;\n"
    "wgmma.mma_async.sync.aligned.m64n80k16.f32.bf16.bf16 {"
      "%0, %1, %2, %3, %4, %5, %6, %7, %8, %9, %10, %11, %12, %13, %14, %15, "
      "%16, %17, %18, %19, %20, %21, %22, %23, %24, %25, %26, %27, %28, %29, %30, %31, "
      "%32, %33, %34, %35, %36, %37, %38, %39"
      "}, a, b, t, 1, 1, 0, 1;\n"
    "wgmma.commit_group.sync.aligned;\n"
    "@p bra.uni DN;\nmov.u32 n, 0;\nWT: mbarrier.try_wait.parity.shared::cta.b64 p, [%46], %47;\n@p bra.uni DN;\nadd.u32 n, n, 1;\nsetp.lt.u32 p, n, 0x100000;\n@p bra.uni WT;\nDN:\n"
    "}\n"
      :
      "+f"(d[0]), "+f"(d[1]), "+f"(d[2]), "+f"(d[3]), "+f"(d[4]), "+f"(d[5]), "+f"(d[6]), "+f"(d[7]),
      "+f"(d[8]), "+f"(d[9]), "+f"(d[10]), "+f"(d[11]), "+f"(d[12]), "+f"(d[13]), "+f"(d[14]), "+f"(d[15]),
      "+f"(d[16]), "+f"(d[17]), "+f"(d[18]), "+f"(d[19]), "+f"(d[20]), "+f"(d[21]), "+f"(d[22]), "+f"(d[23]),
      "+f"(d[24]), "+f"(d[25]), "+f"(d[26]), "+f"(d[27]), "+f"(d[28]), "+f"(d[29]), "+f"(d[30]), "+f"(d[31]),
      "+f"(d[32]), "+f"(d[33]), "+f"(d[34]), "+f"(d[35]), "+f"(d[36]), "+f"(d[37]), "+f"(d[38]), "+f"(d[39])
      : "l"(da), "l"(db), "r"(rel), "r"(doR), "r"(fa), "r"(pa), "r"(fb), "r"(pb), "n"(BSTEP), "r"(acc), "r"(rela) : "memory");
    else if constexpr (W == 2 && RC == 0 && RA == 0) asm volatile(
    "{\n.reg .pred p, q, r, t;\n.reg .b64 a, b;\n.reg .u32 n;\nsetp.ne.b32 t, 1, 0;\nsetp.ne.b32 r, %49, 0;\n"
    "wgmma.mma_async.sync.aligned.m64n80k16.f32.bf16.bf16 {"
      "%0, %1, %2, %3, %4, %5, %6, %7, %8, %9, %10, %11, %12, %13, %14, %15, "
      "%16, %17, %18, %19, %20, %21, %22, %23, %24, %25, %26, %27, %28, %29, %30, %31, "
      "%32, %33, %34, %35, %36, %37, %38, %39"
      "}, %40, %41, r, 1, 1, 0, 1;\n"
    "add.u64 a, %40, 2;\nadd.u64 b, %41, %48;\n"
    "wgmma.mma_async.sync.aligned.m64n80k16.f32.bf16.bf16 {"
      "%0, %1, %2, %3, %4, %5, %6, %7, %8, %9, %10, %11, %12, %13, %14, %15, "
      "%16, %17, %18, %19, %20, %21, %22, %23, %24, %25, %26, %27, %28, %29, %30, %31, "
      "%32, %33, %34, %35, %36, %37, %38, %39"
      "}, a, b, t, 1, 1, 0, 1;\n"
    "wgmma.commit_group.sync.aligned;\nwgmma.wait_group.sync.aligned 1;\n"
    "add.u64 a, %40, 4;\nadd.u64 b, %41, 2*%48;\n"
    "wgmma.mma_async.sync.aligned.m64n80k16.f32.bf16.bf16 {"
      "%0, %1, %2, %3, %4, %5, %6, %7, %8, %9, %10, %11, %12, %13, %14, %15, "
      "%16, %17, %18, %19, %20, %21, %22, %23, %24, %25, %26, %27, %28, %29, %30, %31, "
      "%32, %33, %34, %35, %36, %37, %38, %39"
      "}, a, b, t, 1, 1, 0, 1;\n"
    "mbarrier.test_wait.parity.shared::cta.b64 p, [%46], %47;\n"
    "mbarrier.test_wait.parity.shared::cta.b64 r, [%44], %45;\nand.pred p, p, r;\n"
    "add.u64 a, %40, 6;\nadd.u64 b, %41, 3*%48;\n"
    "wgmma.mma_async.sync.aligned.m64n80k16.f32.bf16.bf16 {"
      "%0, %1, %2, %3, %4, %5, %6, %7, %8, %9, %10, %11, %12, %13, %14, %15, "
      "%16, %17, %18, %19, %20, %21, %22, %23, %24, %25, %26, %27, %28, %29, %30, %31, "
      "%32, %33, %34, %35, %36, %37, %38, %39"
      "}, a, b, t, 1, 1, 0, 1;\n"
    "wgmma.commit_group.sync.aligned;\n"
    "@p bra.uni DN;\nmov.u32 n, 0;\nWT: mbarrier.try_wait.parity.shared::cta.b64 p, [%46], %47;\nmbarrier.try_wait.parity.shared::cta.b64 r, [%44], %45;\nand.pred p, p, r;\n@p bra.uni DN;\nadd.u32 n, n, 1;\nsetp.lt.u32 p, n, 0x100000;\n@p bra.uni WT;\nDN:\n"
    "}\n"
      :
      "+f"(d[0]), "+f"(d[1]), "+f"(d[2]), "+f"(d[3]), "+f"(d[4]), "+f"(d[5]), "+f"(d[6]), "+f"(d[7]),
      "+f"(d[8]), "+f"(d[9]), "+f"(d[10]), "+f"(d[11]), "+f"(d[12]), "+f"(d[13]), "+f"(d[14]), "+f"(d[15]),
      "+f"(d[16]), "+f"(d[17]), "+f"(d[18]), "+f"(d[19]), "+f"(d[20]), "+f"(d[21]), "+f"(d[22]), "+f"(d[23]),
      "+f"(d[24]), "+f"(d[25]), "+f"(d[26]), "+f"(d[27]), "+f"(d[28]), "+f"(d[29]), "+f"(d[30]), "+f"(d[31]),
      "+f"(d[32]), "+f"(d[33]), "+f"(d[34]), "+f"(d[35]), "+f"(d[36]), "+f"(d[37]), "+f"(d[38]), "+f"(d[39])
      : "l"(da), "l"(db), "r"(rel), "r"(doR), "r"(fa), "r"(pa), "r"(fb), "r"(pb), "n"(BSTEP), "r"(acc), "r"(rela) : "memory");
    else if constexpr (W == 2 && RC == 1 && RA == 0) asm volatile(
    "{\n.reg .pred p, q, r, t;\n.reg .b64 a, b;\n.reg .u32 n;\nsetp.ne.b32 t, 1, 0;\nsetp.ne.b32 r, %49, 0;\n"
    "wgmma.mma_async.sync.aligned.m64n80k16.f32.bf16.bf16 {"
      "%0, %1, %2, %3, %4, %5, %6, %7, %8, %9, %10, %11, %12, %13, %14, %15, "
      "%16, %17, %18, %19, %20, %21, %22, %23, %24, %25, %26, %27, %28, %29, %30, %31, "
      "%32, %33, %34, %35, %36, %37, %38, %39"
      "}, %40, %41, r, 1, 1, 0, 1;\n"
    "add.u64 a, %40, 2;\nadd.u64 b, %41, %48;\n"
    "wgmma.mma_async.sync.aligned.m64n80k16.f32.bf16.bf16 {"
      "%0, %1, %2, %3, %4, %5, %6, %7, %8, %9, %10, %11, %12, %13, %14, %15, "
      "%16, %17, %18, %19, %20, %21, %22, %23, %24, %25, %26, %27, %28, %29, %30, %31, "
      "%32, %33, %34, %35, %36, %37, %38, %39"
      "}, a, b, t, 1, 1, 0, 1;\n"
    "wgmma.commit_group.sync.aligned;\nwgmma.wait_group.sync.aligned 1;\n"
    "add.u64 a, %40, 4;\nadd.u64 b, %41, 2*%48;\n"
    "wgmma.mma_async.sync.aligned.m64n80k16.f32.bf16.bf16 {"
      "%0, %1, %2, %3, %4, %5, %6, %7, %8, %9, %10, %11, %12, %13, %14, %15, "
      "%16, %17, %18, %19, %20, %21, %22, %23, %24, %25, %26, %27, %28, %29, %30, %31, "
      "%32, %33, %34, %35, %36, %37, %38, %39"
      "}, a, b, t, 1, 1, 0, 1;\n"
    "setp.ne.u32 q, %43, 0;\n@q mbarrier.arrive.shared::cta.b64 _, [%42];\n"
    "mbarrier.test_wait.parity.shared::cta.b64 p, [%46], %47;\n"
    "mbarrier.test_wait.parity.shared::cta.b64 r, [%44], %45;\nand.pred p, p, r;\n"
    "add.u64 a, %40, 6;\nadd.u64 b, %41, 3*%48;\n"
    "wgmma.mma_async.sync.aligned.m64n80k16.f32.bf16.bf16 {"
      "%0, %1, %2, %3, %4, %5, %6, %7, %8, %9, %10, %11, %12, %13, %14, %15, "
      "%16, %17, %18, %19, %20, %21, %22, %23, %24, %25, %26, %27, %28, %29, %30, %31, "
      "%32, %33, %34, %35, %36, %37, %38, %39"
      "}, a, b, t, 1, 1, 0, 1;\n"
    "wgmma.commit_group.sync.aligned;\n"
    "@p bra.uni DN;\nmov.u32 n, 0;\nWT: mbarrier.try_wait.parity.shared::cta.b64 p, [%46], %47;\nmbarrier.try_wait.parity.shared::cta.b64 r, [%44], %45;\nand.pred p, p, r;\n@p bra.uni DN;\nadd.u32 n, n, 1;\nsetp.lt.u32 p, n, 0x100000;\n@p bra.uni WT;\nDN:\n"
    "}\n"
      :
      "+f"(d[0]), "+f"(d[1]), "+f"(d[2]), "+f"(d[3]), "+f"(d[4]), "+f"(d[5]), "+f"(d[6]), "+f"(d[7]),
      "+f"(d[8]), "+f"(d[9]), "+f"(d[10]), "+f"(d[11]), "+f"(d[12]), "+f"(d[13]), "+f"(d[14]), "+f"(d[15]),
      "+f"(d[16]), "+f"(d[17]), "+f"(d[18]), "+f"(d[19]), "+f"(d[20]), "+f"(d[21]), "+f"(d[22]), "+f"(d[23]),
      "+f"(d[24]), "+f"(d[25]), "+f"(d[26]), "+f"(d[27]), "+f"(d[28]), "+f"(d[29]), "+f"(d[30]), "+f"(d[31]),
      "+f"(d[32]), "+f"(d[33]), "+f"(d[34]), "+f"(d[35]), "+f"(d[36]), "+f"(d[37]), "+f"(d[38]), "+f"(d[39])
      : "l"(da), "l"(db), "r"(rel), "r"(doR), "r"(fa), "r"(pa), "r"(fb), "r"(pb), "n"(BSTEP), "r"(acc), "r"(rela) : "memory");
    else if constexpr (W == 2 && RC == 1 && RA == 1) asm volatile(
    "{\n.reg .pred p, q, r, t;\n.reg .b64 a, b;\n.reg .u32 n;\nsetp.ne.b32 t, 1, 0;\nsetp.ne.b32 r, %49, 0;\n"
    "wgmma.mma_async.sync.aligned.m64n80k16.f32.bf16.bf16 {"
      "%0, %1, %2, %3, %4, %5, %6, %7, %8, %9, %10, %11, %12, %13, %14, %15, "
      "%16, %17, %18, %19, %20, %21, %22, %23, %24, %25, %26, %27, %28, %29, %30, %31, "
      "%32, %33, %34, %35, %36, %37, %38, %39"
      "}, %40, %41, r, 1, 1, 0, 1;\n"
    "add.u64 a, %40, 2;\nadd.u64 b, %41, %48;\n"
    "wgmma.mma_async.sync.aligned.m64n80k16.f32.bf16.bf16 {"
      "%0, %1, %2, %3, %4, %5, %6, %7, %8, %9, %10, %11, %12, %13, %14, %15, "
      "%16, %17, %18, %19, %20, %21, %22, %23, %24, %25, %26, %27, %28, %29, %30, %31, "
      "%32, %33, %34, %35, %36, %37, %38, %39"
      "}, a, b, t, 1, 1, 0, 1;\n"
    "wgmma.commit_group.sync.aligned;\nwgmma.wait_group.sync.aligned 1;\n"
    "add.u64 a, %40, 4;\nadd.u64 b, %41, 2*%48;\n"
    "wgmma.mma_async.sync.aligned.m64n80k16.f32.bf16.bf16 {"
      "%0, %1, %2, %3, %4, %5, %6, %7, %8, %9, %10, %11, %12, %13, %14, %15, "
      "%16, %17, %18, %19, %20, %21, %22, %23, %24, %25, %26, %27, %28, %29, %30, %31, "
      "%32, %33, %34, %35, %36, %37, %38, %39"
      "}, a, b, t, 1, 1, 0, 1;\n"
    "setp.ne.u32 q, %43, 0;\n@q mbarrier.arrive.shared::cta.b64 _, [%42];\n@q mbarrier.arrive.shared::cta.b64 _, [%50];\n"
    "mbarrier.test_wait.parity.shared::cta.b64 p, [%46], %47;\n"
    "mbarrier.test_wait.parity.shared::cta.b64 r, [%44], %45;\nand.pred p, p, r;\n"
    "add.u64 a, %40, 6;\nadd.u64 b, %41, 3*%48;\n"
    "wgmma.mma_async.sync.aligned.m64n80k16.f32.bf16.bf16 {"
      "%0, %1, %2, %3, %4, %5, %6, %7, %8, %9, %10, %11, %12, %13, %14, %15, "
      "%16, %17, %18, %19, %20, %21, %22, %23, %24, %25, %26, %27, %28, %29, %30, %31, "
      "%32, %33, %34, %35, %36, %37, %38, %39"
      "}, a, b, t, 1, 1, 0, 1;\n"
    "wgmma.commit_group.sync.aligned;\n"
    "@p bra.uni DN;\nmov.u32 n, 0;\nWT: mbarrier.try_wait.parity.shared::cta.b64 p, [%46], %47;\nmbarrier.try_wait.parity.shared::cta.b64 r, [%44], %45;\nand.pred p, p, r;\n@p bra.uni DN;\nadd.u32 n, n, 1;\nsetp.lt.u32 p, n, 0x100000;\n@p bra.uni WT;\nDN:\n"
    "}\n"
      :
      "+f"(d[0]), "+f"(d[1]), "+f"(d[2]), "+f"(d[3]), "+f"(d[4]), "+f"(d[5]), "+f"(d[6]), "+f"(d[7]),
      "+f"(d[8]), "+f"(d[9]), "+f"(d[10]), "+f"(d[11]), "+f"(d[12]), "+f"(d[13]), "+f"(d[14]), "+f"(d[15]),
      "+f"(d[16]), "+f"(d[17]), "+f"(d[18]), "+f"(d[19]), "+f"(d[20]), "+f"(d[21]), "+f"(d[22]), "+f"(d[23]),
      "+f"(d[24]), "+f"(d[25]), "+f"(d[26]), "+f"(d[27]), "+f"(d[28]), "+f"(d[29]), "+f"(d[30]), "+f"(d[31]),
      "+f"(d[32]), "+f"(d[33]), "+f"(d[34]), "+f"(d[35]), "+f"(d[36]), "+f"(d[37]), "+f"(d[38]), "+f"(d[39])
      : "l"(da), "l"(db), "r"(rel), "r"(doR), "r"(fa), "r"(pa), "r"(fb), "r"(pb), "n"(BSTEP), "r"(acc), "r"(rela) : "memory");
    else static_assert(W < 0, "variant not generated");
  }
};
template <> struct KB<192> {
  template <int W, int RC, int RA, int BSTEP> static __device__ __forceinline__ void run(float* d, uint64_t da, uint64_t db, uint32_t rel, uint32_t rela, uint32_t doR, uint32_t fa, uint32_t pa, uint32_t fb, uint32_t pb, uint32_t acc) {
    if constexpr (W == 0 && RC == 2 && RA == 0) asm volatile(
    "{\n.reg .pred p, q, r, t;\n.reg .b64 a, b;\n.reg .u32 n;\nsetp.ne.b32 t, 1, 0;\nsetp.ne.b32 r, %105, 0;\n"
    "wgmma.mma_async.sync.aligned.m64n192k16.f32.bf16.bf16 {"
      "%0, %1, %2, %3, %4, %5, %6, %7, %8, %9, %10, %11, %12, %13, %14, %15, "
      "%16, %17, %18, %19, %20, %21, %22, %23, %24, %25, %26, %27, %28, %29, %30, %31, "
      "%32, %33, %34, %35, %36, %37, %38, %39, %40, %41, %42, %43, %44, %45, %46, %47, "
      "%48, %49, %50, %51, %52, %53, %54, %55, %56, %57, %58, %59, %60, %61, %62, %63, "
      "%64, %65, %66, %67, %68, %69, %70, %71, %72, %73, %74, %75, %76, %77, %78, %79, "
      "%80, %81, %82, %83, %84, %85, %86, %87, %88, %89, %90, %91, %92, %93, %94, %95"
      "}, %96, %97, r, 1, 1, 0, 1;\n"
    "add.u64 a, %96, 2;\nadd.u64 b, %97, %104;\n"
    "wgmma.mma_async.sync.aligned.m64n192k16.f32.bf16.bf16 {"
      "%0, %1, %2, %3, %4, %5, %6, %7, %8, %9, %10, %11, %12, %13, %14, %15, "
      "%16, %17, %18, %19, %20, %21, %22, %23, %24, %25, %26, %27, %28, %29, %30, %31, "
      "%32, %33, %34, %35, %36, %37, %38, %39, %40, %41, %42, %43, %44, %45, %46, %47, "
      "%48, %49, %50, %51, %52, %53, %54, %55, %56, %57, %58, %59, %60, %61, %62, %63, "
      "%64, %65, %66, %67, %68, %69, %70, %71, %72, %73, %74, %75, %76, %77, %78, %79, "
      "%80, %81, %82, %83, %84, %85, %86, %87, %88, %89, %90, %91, %92, %93, %94, %95"
      "}, a, b, t, 1, 1, 0, 1;\n"
    "wgmma.commit_group.sync.aligned;\nwgmma.wait_group.sync.aligned 1;\n"
    "add.u64 a, %96, 4;\nadd.u64 b, %97, 2*%104;\n"
    "wgmma.mma_async.sync.aligned.m64n192k16.f32.bf16.bf16 {"
      "%0, %1, %2, %3, %4, %5, %6, %7, %8, %9, %10, %11, %12, %13, %14, %15, "
      "%16, %17, %18, %19, %20, %21, %22, %23, %24, %25, %26, %27, %28, %29, %30, %31, "
      "%32, %33, %34, %35, %36, %37, %38, %39, %40, %41, %42, %43, %44, %45, %46, %47, "
      "%48, %49, %50, %51, %52, %53, %54, %55, %56, %57, %58, %59, %60, %61, %62, %63, "
      "%64, %65, %66, %67, %68, %69, %70, %71, %72, %73, %74, %75, %76, %77, %78, %79, "
      "%80, %81, %82, %83, %84, %85, %86, %87, %88, %89, %90, %91, %92, %93, %94, %95"
      "}, a, b, t, 1, 1, 0, 1;\n"
    "setp.ne.u32 q, %99, 0;\n@q mbarrier.arrive.shared::cta.b64 _, [%98];\n@q mbarrier.arrive.shared::cta.b64 _, [%98];\n"
    "add.u64 a, %96, 6;\nadd.u64 b, %97, 3*%104;\n"
    "wgmma.mma_async.sync.aligned.m64n192k16.f32.bf16.bf16 {"
      "%0, %1, %2, %3, %4, %5, %6, %7, %8, %9, %10, %11, %12, %13, %14, %15, "
      "%16, %17, %18, %19, %20, %21, %22, %23, %24, %25, %26, %27, %28, %29, %30, %31, "
      "%32, %33, %34, %35, %36, %37, %38, %39, %40, %41, %42, %43, %44, %45, %46, %47, "
      "%48, %49, %50, %51, %52, %53, %54, %55, %56, %57, %58, %59, %60, %61, %62, %63, "
      "%64, %65, %66, %67, %68, %69, %70, %71, %72, %73, %74, %75, %76, %77, %78, %79, "
      "%80, %81, %82, %83, %84, %85, %86, %87, %88, %89, %90, %91, %92, %93, %94, %95"
      "}, a, b, t, 1, 1, 0, 1;\n"
    "wgmma.commit_group.sync.aligned;\n"
    "}\n"
      :
      "+f"(d[0]), "+f"(d[1]), "+f"(d[2]), "+f"(d[3]), "+f"(d[4]), "+f"(d[5]), "+f"(d[6]), "+f"(d[7]),
      "+f"(d[8]), "+f"(d[9]), "+f"(d[10]), "+f"(d[11]), "+f"(d[12]), "+f"(d[13]), "+f"(d[14]), "+f"(d[15]),
      "+f"(d[16]), "+f"(d[17]), "+f"(d[18]), "+f"(d[19]), "+f"(d[20]), "+f"(d[21]), "+f"(d[22]), "+f"(d[23]),
      "+f"(d[24]), "+f"(d[25]), "+f"(d[26]), "+f"(d[27]), "+f"(d[28]), "+f"(d[29]), "+f"(d[30]), "+f"(d[31]),
      "+f"(d[32]), "+f"(d[33]), "+f"(d[34]), "+f"(d[35]), "+f"(d[36]), "+f"(d[37]), "+f"(d[38]), "+f"(d[39]),
      "+f"(d[40]), "+f"(d[41]), "+f"(d[42]), "+f"(d[43]), "+f"(d[44]), "+f"(d[45]), "+f"(d[46]), "+f"(d[47]),
      "+f"(d[48]), "+f"(d[49]), "+f"(d[50]), "+f"(d[51]), "+f"(d[52]), "+f"(d[53]), "+f"(d[54]), "+f"(d[55]),
      "+f"(d[56]), "+f"(d[57]), "+f"(d[58]), "+f"(d[59]), "+f"(d[60]), "+f"(d[61]), "+f"(d[62]), "+f"(d[63]),
      "+f"(d[64]), "+f"(d[65]), "+f"(d[66]), "+f"(d[67]), "+f"(d[68]), "+f"(d[69]), "+f"(d[70]), "+f"(d[71]),
      "+f"(d[72]), "+f"(d[73]), "+f"(d[74]), "+f"(d[75]), "+f"(d[76]), "+f"(d[77]), "+f"(d[78]), "+f"(d[79]),
      "+f"(d[80]), "+f"(d[81]), "+f"(d[82]), "+f"(d[83]), "+f"(d[84]), "+f"(d[85]), "+f"(d[86]), "+f"(d[87]),
      "+f"(d[88]), "+f"(d[89]), "+f"(d[90]), "+f"(d[91]), "+f"(d[92]), "+f"(d[93]), "+f"(d[94]), "+f"(d[95])
      : "l"(da), "l"(db), "r"(rel), "r"(doR), "r"(fa), "r"(pa), "r"(fb), "r"(pb), "n"(BSTEP), "r"(acc), "r"(rela) : "memory");
    else if constexpr (W == 0 && RC == 2 && RA == 2) asm volatile(
    "{\n.reg .pred p, q, r, t;\n.reg .b64 a, b;\n.reg .u32 n;\nsetp.ne.b32 t, 1, 0;\nsetp.ne.b32 r, %105, 0;\n"
    "wgmma.mma_async.sync.aligned.m64n192k16.f32.bf16.bf16 {"
      "%0, %1, %2, %3, %4, %5, %6, %7, %8, %9, %10, %11, %12, %13, %14, %15, "
      "%16, %17, %18, %19, %20, %21, %22, %23, %24, %25, %26, %27, %28, %29, %30, %31, "
      "%32, %33, %34, %35, %36, %37, %38, %39, %40, %41, %42, %43, %44, %45, %46, %47, "
      "%48, %49, %50, %51, %52, %53, %54, %55, %56, %57, %58, %59, %60, %61, %62, %63, "
      "%64, %65, %66, %67, %68, %69, %70, %71, %72, %73, %74, %75, %76, %77, %78, %79, "
      "%80, %81, %82, %83, %84, %85, %86, %87, %88, %89, %90, %91, %92, %93, %94, %95"
      "}, %96, %97, r, 1, 1, 0, 1;\n"
    "add.u64 a, %96, 2;\nadd.u64 b, %97, %104;\n"
    "wgmma.mma_async.sync.aligned.m64n192k16.f32.bf16.bf16 {"
      "%0, %1, %2, %3, %4, %5, %6, %7, %8, %9, %10, %11, %12, %13, %14, %15, "
      "%16, %17, %18, %19, %20, %21, %22, %23, %24, %25, %26, %27, %28, %29, %30, %31, "
      "%32, %33, %34, %35, %36, %37, %38, %39, %40, %41, %42, %43, %44, %45, %46, %47, "
      "%48, %49, %50, %51, %52, %53, %54, %55, %56, %57, %58, %59, %60, %61, %62, %63, "
      "%64, %65, %66, %67, %68, %69, %70, %71, %72, %73, %74, %75, %76, %77, %78, %79, "
      "%80, %81, %82, %83, %84, %85, %86, %87, %88, %89, %90, %91, %92, %93, %94, %95"
      "}, a, b, t, 1, 1, 0, 1;\n"
    "wgmma.commit_group.sync.aligned;\nwgmma.wait_group.sync.aligned 1;\n"
    "add.u64 a, %96, 4;\nadd.u64 b, %97, 2*%104;\n"
    "wgmma.mma_async.sync.aligned.m64n192k16.f32.bf16.bf16 {"
      "%0, %1, %2, %3, %4, %5, %6, %7, %8, %9, %10, %11, %12, %13, %14, %15, "
      "%16, %17, %18, %19, %20, %21, %22, %23, %24, %25, %26, %27, %28, %29, %30, %31, "
      "%32, %33, %34, %35, %36, %37, %38, %39, %40, %41, %42, %43, %44, %45, %46, %47, "
      "%48, %49, %50, %51, %52, %53, %54, %55, %56, %57, %58, %59, %60, %61, %62, %63, "
      "%64, %65, %66, %67, %68, %69, %70, %71, %72, %73, %74, %75, %76, %77, %78, %79, "
      "%80, %81, %82, %83, %84, %85, %86, %87, %88, %89, %90, %91, %92, %93, %94, %95"
      "}, a, b, t, 1, 1, 0, 1;\n"
    "setp.ne.u32 q, %99, 0;\n@q mbarrier.arrive.shared::cta.b64 _, [%98];\n@q mbarrier.arrive.shared::cta.b64 _, [%98];\n@q mbarrier.arrive.shared::cta.b64 _, [%106];\n@q mbarrier.arrive.shared::cta.b64 _, [%106];\n"
    "add.u64 a, %96, 6;\nadd.u64 b, %97, 3*%104;\n"
    "wgmma.mma_async.sync.aligned.m64n192k16.f32.bf16.bf16 {"
      "%0, %1, %2, %3, %4, %5, %6, %7, %8, %9, %10, %11, %12, %13, %14, %15, "
      "%16, %17, %18, %19, %20, %21, %22, %23, %24, %25, %26, %27, %28, %29, %30, %31, "
      "%32, %33, %34, %35, %36, %37, %38, %39, %40, %41, %42, %43, %44, %45, %46, %47, "
      "%48, %49, %50, %51, %52, %53, %54, %55, %56, %57, %58, %59, %60, %61, %62, %63, "
      "%64, %65, %66, %67, %68, %69, %70, %71, %72, %73, %74, %75, %76, %77, %78, %79, "
      "%80, %81, %82, %83, %84, %85, %86, %87, %88, %89, %90, %91, %92, %93, %94, %95"
      "}, a, b, t, 1, 1, 0, 1;\n"
    "wgmma.commit_group.sync.aligned;\n"
    "}\n"
      :
      "+f"(d[0]), "+f"(d[1]), "+f"(d[2]), "+f"(d[3]), "+f"(d[4]), "+f"(d[5]), "+f"(d[6]), "+f"(d[7]),
      "+f"(d[8]), "+f"(d[9]), "+f"(d[10]), "+f"(d[11]), "+f"(d[12]), "+f"(d[13]), "+f"(d[14]), "+f"(d[15]),
      "+f"(d[16]), "+f"(d[17]), "+f"(d[18]), "+f"(d[19]), "+f"(d[20]), "+f"(d[21]), "+f"(d[22]), "+f"(d[23]),
      "+f"(d[24]), "+f"(d[25]), "+f"(d[26]), "+f"(d[27]), "+f"(d[28]), "+f"(d[29]), "+f"(d[30]), "+f"(d[31]),
      "+f"(d[32]), "+f"(d[33]), "+f"(d[34]), "+f"(d[35]), "+f"(d[36]), "+f"(d[37]), "+f"(d[38]), "+f"(d[39]),
      "+f"(d[40]), "+f"(d[41]), "+f"(d[42]), "+f"(d[43]), "+f"(d[44]), "+f"(d[45]), "+f"(d[46]), "+f"(d[47]),
      "+f"(d[48]), "+f"(d[49]), "+f"(d[50]), "+f"(d[51]), "+f"(d[52]), "+f"(d[53]), "+f"(d[54]), "+f"(d[55]),
      "+f"(d[56]), "+f"(d[57]), "+f"(d[58]), "+f"(d[59]), "+f"(d[60]), "+f"(d[61]), "+f"(d[62]), "+f"(d[63]),
      "+f"(d[64]), "+f"(d[65]), "+f"(d[66]), "+f"(d[67]), "+f"(d[68]), "+f"(d[69]), "+f"(d[70]), "+f"(d[71]),
      "+f"(d[72]), "+f"(d[73]), "+f"(d[74]), "+f"(d[75]), "+f"(d[76]), "+f"(d[77]), "+f"(d[78]), "+f"(d[79]),
      "+f"(d[80]), "+f"(d[81]), "+f"(d[82]), "+f"(d[83]), "+f"(d[84]), "+f"(d[85]), "+f"(d[86]), "+f"(d[87]),
      "+f"(d[88]), "+f"(d[89]), "+f"(d[90]), "+f"(d[91]), "+f"(d[92]), "+f"(d[93]), "+f"(d[94]), "+f"(d[95])
      : "l"(da), "l"(db), "r"(rel), "r"(doR), "r"(fa), "r"(pa), "r"(fb), "r"(pb), "n"(BSTEP), "r"(acc), "r"(rela) : "memory");
    else if constexpr (W == 1 && RC == 2 && RA == 2) asm volatile(
    "{\n.reg .pred p, q, r, t;\n.reg .b64 a, b;\n.reg .u32 n;\nsetp.ne.b32 t, 1, 0;\nsetp.ne.b32 r, %105, 0;\n"
    "wgmma.mma_async.sync.aligned.m64n192k16.f32.bf16.bf16 {"
      "%0, %1, %2, %3, %4, %5, %6, %7, %8, %9, %10, %11, %12, %13, %14, %15, "
      "%16, %17, %18, %19, %20, %21, %22, %23, %24, %25, %26, %27, %28, %29, %30, %31, "
      "%32, %33, %34, %35, %36, %37, %38, %39, %40, %41, %42, %43, %44, %45, %46, %47, "
      "%48, %49, %50, %51, %52, %53, %54, %55, %56, %57, %58, %59, %60, %61, %62, %63, "
      "%64, %65, %66, %67, %68, %69, %70, %71, %72, %73, %74, %75, %76, %77, %78, %79, "
      "%80, %81, %82, %83, %84, %85, %86, %87, %88, %89, %90, %91, %92, %93, %94, %95"
      "}, %96, %97, r, 1, 1, 0, 1;\n"
    "add.u64 a, %96, 2;\nadd.u64 b, %97, %104;\n"
    "wgmma.mma_async.sync.aligned.m64n192k16.f32.bf16.bf16 {"
      "%0, %1, %2, %3, %4, %5, %6, %7, %8, %9, %10, %11, %12, %13, %14, %15, "
      "%16, %17, %18, %19, %20, %21, %22, %23, %24, %25, %26, %27, %28, %29, %30, %31, "
      "%32, %33, %34, %35, %36, %37, %38, %39, %40, %41, %42, %43, %44, %45, %46, %47, "
      "%48, %49, %50, %51, %52, %53, %54, %55, %56, %57, %58, %59, %60, %61, %62, %63, "
      "%64, %65, %66, %67, %68, %69, %70, %71, %72, %73, %74, %75, %76, %77, %78, %79, "
      "%80, %81, %82, %83, %84, %85, %86, %87, %88, %89, %90, %91, %92, %93, %94, %95"
      "}, a, b, t, 1, 1, 0, 1;\n"
    "wgmma.commit_group.sync.aligned;\nwgmma.wait_group.sync.aligned 1;\n"
    "add.u64 a, %96, 4;\nadd.u64 b, %97, 2*%104;\n"
    "wgmma.mma_async.sync.aligned.m64n192k16.f32.bf16.bf16 {"
      "%0, %1, %2, %3, %4, %5, %6, %7, %8, %9, %10, %11, %12, %13, %14, %15, "
      "%16, %17, %18, %19, %20, %21, %22, %23, %24, %25, %26, %27, %28, %29, %30, %31, "
      "%32, %33, %34, %35, %36, %37, %38, %39, %40, %41, %42, %43, %44, %45, %46, %47, "
      "%48, %49, %50, %51, %52, %53, %54, %55, %56, %57, %58, %59, %60, %61, %62, %63, "
      "%64, %65, %66, %67, %68, %69, %70, %71, %72, %73, %74, %75, %76, %77, %78, %79, "
      "%80, %81, %82, %83, %84, %85, %86, %87, %88, %89, %90, %91, %92, %93, %94, %95"
      "}, a, b, t, 1, 1, 0, 1;\n"
    "setp.ne.u32 q, %99, 0;\n@q mbarrier.arrive.shared::cta.b64 _, [%98];\n@q mbarrier.arrive.shared::cta.b64 _, [%98];\n@q mbarrier.arrive.shared::cta.b64 _, [%106];\n@q mbarrier.arrive.shared::cta.b64 _, [%106];\n"
    "mbarrier.test_wait.parity.shared::cta.b64 p, [%102], %103;\n"
    "add.u64 a, %96, 6;\nadd.u64 b, %97, 3*%104;\n"
    "wgmma.mma_async.sync.aligned.m64n192k16.f32.bf16.bf16 {"
      "%0, %1, %2, %3, %4, %5, %6, %7, %8, %9, %10, %11, %12, %13, %14, %15, "
      "%16, %17, %18, %19, %20, %21, %22, %23, %24, %25, %26, %27, %28, %29, %30, %31, "
      "%32, %33, %34, %35, %36, %37, %38, %39, %40, %41, %42, %43, %44, %45, %46, %47, "
      "%48, %49, %50, %51, %52, %53, %54, %55, %56, %57, %58, %59, %60, %61, %62, %63, "
      "%64, %65, %66, %67, %68, %69, %70, %71, %72, %73, %74, %75, %76, %77, %78, %79, "
      "%80, %81, %82, %83, %84, %85, %86, %87, %88, %89, %90, %91, %92, %93, %94, %95"
      "}, a, b, t, 1, 1, 0, 1;\n"
    "wgmma.commit_group.sync.aligned;\n"
    "@p bra.uni DN;\nmov.u32 n, 0;\nWT: mbarrier.try_wait.parity.shared::cta.b64 p, [%102], %103;\n@p bra.uni DN;\nadd.u32 n, n, 1;\nsetp.lt.u32 p, n, 0x100000;\n@p bra.uni WT;\nDN:\n"
    "}\n"
      :
      "+f"(d[0]), "+f"(d[1]), "+f"(d[2]), "+f"(d[3]), "+f"(d[4]), "+f"(d[5]), "+f"(d[6]), "+f"(d[7]),
      "+f"(d[8]), "+f"(d[9]), "+f"(d[10]), "+f"(d[11]), "+f"(d[12]), "+f"(d[13]), "+f"(d[14]), "+f"(d[15]),
      "+f"(d[16]), "+f"(d[17]), "+f"(d[18]), "+f"(d[19]), "+f"(d[20]), "+f"(d[21]), "+f"(d[22]), "+f"(d[23]),
      "+f"(d[24]), "+f"(d[25]), "+f"(d[26]), "+f"(d[27]), "+f"(d[28]), "+f"(d[29]), "+f"(d[30]), "+f"(d[31]),
      "+f"(d[32]), "+f"(d[33]), "+f"(d[34]), "+f"(d[35]), "+f"(d[36]), "+f"(d[37]), "+f"(d[38]), "+f"(d[39]),
      "+f"(d[40]), "+f"(d[41]), "+f"(d[42]), "+f"(d[43]), "+f"(d[44]), "+f"(d[45]), "+f"(d[46]), "+f"(d[47]),
      "+f"(d[48]), "+f"(d[49]), "+f"(d[50]), "+f"(d[51]), "+f"(d[52]), "+f"(d[53]), "+f"(d[54]), "+f"(d[55]),
      "+f"(d[56]), "+f"(d[57]), "+f"(d[58]), "+f"(d[59]), "+f"(d[60]), "+f"(d[61]), "+f"(d[62]), "+f"(d[63]),
      "+f"(d[64]), "+f"(d[65]), "+f"(d[66]), "+f"(d[67]), "+f"(d[68]), "+f"(d[69]), "+f"(d[70]), "+f"(d[71]),
      "+f"(d[72]), "+f"(d[73]), "+f"(d[74]), "+f"(d[75]), "+f"(d[76]), "+f"(d[77]), "+f"(d[78]), "+f"(d[79]),
      "+f"(d[80]), "+f"(d[81]), "+f"(d[82]), "+f"(d[83]), "+f"(d[84]), "+f"(d[85]), "+f"(d[86]), "+f"(d[87]),
      "+f"(d[88]), "+f"(d[89]), "+f"(d[90]), "+f"(d[91]), "+f"(d[92]), "+f"(d[93]), "+f"(d[94]), "+f"(d[95])
      : "l"(da), "l"(db), "r"(rel), "r"(doR), "r"(fa), "r"(pa), "r"(fb), "r"(pb), "n"(BSTEP), "r"(acc), "r"(rela) : "memory");
    else if constexpr (W == 2 && RC == 2 && RA == 0) asm volatile(
    "{\n.reg .pred p, q, r, t;\n.reg .b64 a, b;\n.reg .u32 n;\nsetp.ne.b32 t, 1, 0;\nsetp.ne.b32 r, %105, 0;\n"
    "wgmma.mma_async.sync.aligned.m64n192k16.f32.bf16.bf16 {"
      "%0, %1, %2, %3, %4, %5, %6, %7, %8, %9, %10, %11, %12, %13, %14, %15, "
      "%16, %17, %18, %19, %20, %21, %22, %23, %24, %25, %26, %27, %28, %29, %30, %31, "
      "%32, %33, %34, %35, %36, %37, %38, %39, %40, %41, %42, %43, %44, %45, %46, %47, "
      "%48, %49, %50, %51, %52, %53, %54, %55, %56, %57, %58, %59, %60, %61, %62, %63, "
      "%64, %65, %66, %67, %68, %69, %70, %71, %72, %73, %74, %75, %76, %77, %78, %79, "
      "%80, %81, %82, %83, %84, %85, %86, %87, %88, %89, %90, %91, %92, %93, %94, %95"
      "}, %96, %97, r, 1, 1, 0, 1;\n"
    "add.u64 a, %96, 2;\nadd.u64 b, %97, %104;\n"
    "wgmma.mma_async.sync.aligned.m64n192k16.f32.bf16.bf16 {"
      "%0, %1, %2, %3, %4, %5, %6, %7, %8, %9, %10, %11, %12, %13, %14, %15, "
      "%16, %17, %18, %19, %20, %21, %22, %23, %24, %25, %26, %27, %28, %29, %30, %31, "
      "%32, %33, %34, %35, %36, %37, %38, %39, %40, %41, %42, %43, %44, %45, %46, %47, "
      "%48, %49, %50, %51, %52, %53, %54, %55, %56, %57, %58, %59, %60, %61, %62, %63, "
      "%64, %65, %66, %67, %68, %69, %70, %71, %72, %73, %74, %75, %76, %77, %78, %79, "
      "%80, %81, %82, %83, %84, %85, %86, %87, %88, %89, %90, %91, %92, %93, %94, %95"
      "}, a, b, t, 1, 1, 0, 1;\n"
    "wgmma.commit_group.sync.aligned;\nwgmma.wait_group.sync.aligned 1;\n"
    "add.u64 a, %96, 4;\nadd.u64 b, %97, 2*%104;\n"
    "wgmma.mma_async.sync.aligned.m64n192k16.f32.bf16.bf16 {"
      "%0, %1, %2, %3, %4, %5, %6, %7, %8, %9, %10, %11, %12, %13, %14, %15, "
      "%16, %17, %18, %19, %20, %21, %22, %23, %24, %25, %26, %27, %28, %29, %30, %31, "
      "%32, %33, %34, %35, %36, %37, %38, %39, %40, %41, %42, %43, %44, %45, %46, %47, "
      "%48, %49, %50, %51, %52, %53, %54, %55, %56, %57, %58, %59, %60, %61, %62, %63, "
      "%64, %65, %66, %67, %68, %69, %70, %71, %72, %73, %74, %75, %76, %77, %78, %79, "
      "%80, %81, %82, %83, %84, %85, %86, %87, %88, %89, %90, %91, %92, %93, %94, %95"
      "}, a, b, t, 1, 1, 0, 1;\n"
    "setp.ne.u32 q, %99, 0;\n@q mbarrier.arrive.shared::cta.b64 _, [%98];\n@q mbarrier.arrive.shared::cta.b64 _, [%98];\n"
    "mbarrier.test_wait.parity.shared::cta.b64 p, [%102], %103;\n"
    "mbarrier.test_wait.parity.shared::cta.b64 r, [%100], %101;\nand.pred p, p, r;\n"
    "add.u64 a, %96, 6;\nadd.u64 b, %97, 3*%104;\n"
    "wgmma.mma_async.sync.aligned.m64n192k16.f32.bf16.bf16 {"
      "%0, %1, %2, %3, %4, %5, %6, %7, %8, %9, %10, %11, %12, %13, %14, %15, "
      "%16, %17, %18, %19, %20, %21, %22, %23, %24, %25, %26, %27, %28, %29, %30, %31, "
      "%32, %33, %34, %35, %36, %37, %38, %39, %40, %41, %42, %43, %44, %45, %46, %47, "
      "%48, %49, %50, %51, %52, %53, %54, %55, %56, %57, %58, %59, %60, %61, %62, %63, "
      "%64, %65, %66, %67, %68, %69, %70, %71, %72, %73, %74, %75, %76, %77, %78, %79, "
      "%80, %81, %82, %83, %84, %85, %86, %87, %88, %89, %90, %91, %92, %93, %94, %95"
      "}, a, b, t, 1, 1, 0, 1;\n"
    "wgmma.commit_group.sync.aligned;\n"
    "@p bra.uni DN;\nmov.u32 n, 0;\nWT: mbarrier.try_wait.parity.shared::cta.b64 p, [%102], %103;\nmbarrier.try_wait.parity.shared::cta.b64 r, [%100], %101;\nand.pred p, p, r;\n@p bra.uni DN;\nadd.u32 n, n, 1;\nsetp.lt.u32 p, n, 0x100000;\n@p bra.uni WT;\nDN:\n"
    "}\n"
      :
      "+f"(d[0]), "+f"(d[1]), "+f"(d[2]), "+f"(d[3]), "+f"(d[4]), "+f"(d[5]), "+f"(d[6]), "+f"(d[7]),
      "+f"(d[8]), "+f"(d[9]), "+f"(d[10]), "+f"(d[11]), "+f"(d[12]), "+f"(d[13]), "+f"(d[14]), "+f"(d[15]),
      "+f"(d[16]), "+f"(d[17]), "+f"(d[18]), "+f"(d[19]), "+f"(d[20]), "+f"(d[21]), "+f"(d[22]), "+f"(d[23]),
      "+f"(d[24]), "+f"(d[25]), "+f"(d[26]), "+f"(d[27]), "+f"(d[28]), "+f"(d[29]), "+f"(d[30]), "+f"(d[31]),
      "+f"(d[32]), "+f"(d[33]), "+f"(d[34]), "+f"(d[35]), "+f"(d[36]), "+f"(d[37]), "+f"(d[38]), "+f"(d[39]),
      "+f"(d[40]), "+f"(d[41]), "+f"(d[42]), "+f"(d[43]), "+f"(d[44]), "+f"(d[45]), "+f"(d[46]), "+f"(d[47]),
      "+f"(d[48]), "+f"(d[49]), "+f"(d[50]), "+f"(d[51]), "+f"(d[52]), "+f"(d[53]), "+f"(d[54]), "+f"(d[55]),
      "+f"(d[56]), "+f"(d[57]), "+f"(d[58]), "+f"(d[59]), "+f"(d[60]), "+f"(d[61]), "+f"(d[62]), "+f"(d[63]),
      "+f"(d[64]), "+f"(d[65]), "+f"(d[66]), "+f"(d[67]), "+f"(d[68]), "+f"(d[69]), "+f"(d[70]), "+f"(d[71]),
      "+f"(d[72]), "+f"(d[73]), "+f"(d[74]), "+f"(d[75]), "+f"(d[76]), "+f"(d[77]), "+f"(d[78]), "+f"(d[79]),
      "+f"(d[80]), "+f"(d[81]), "+f"(d[82]), "+f"(d[83]), "+f"(d[84]), "+f"(d[85]), "+f"(d[86]), "+f"(d[87]),
      "+f"(d[88]), "+f"(d[89]), "+f"(d[90]), "+f"(d[91]), "+f"(d[92]), "+f"(d[93]), "+f"(d[94]), "+f"(d[95])
      : "l"(da), "l"(db), "r"(rel), "r"(doR), "r"(fa), "r"(pa), "r"(fb), "r"(pb), "n"(BSTEP), "r"(acc), "r"(rela) : "memory");
    else if constexpr (W == 2 && RC == 2 && RA == 2) asm volatile(
    "{\n.reg .pred p, q, r, t;\n.reg .b64 a, b;\n.reg .u32 n;\nsetp.ne.b32 t, 1, 0;\nsetp.ne.b32 r, %105, 0;\n"
    "wgmma.mma_async.sync.aligned.m64n192k16.f32.bf16.bf16 {"
      "%0, %1, %2, %3, %4, %5, %6, %7, %8, %9, %10, %11, %12, %13, %14, %15, "
      "%16, %17, %18, %19, %20, %21, %22, %23, %24, %25, %26, %27, %28, %29, %30, %31, "
      "%32, %33, %34, %35, %36, %37, %38, %39, %40, %41, %42, %43, %44, %45, %46, %47, "
      "%48, %49, %50, %51, %52, %53, %54, %55, %56, %57, %58, %59, %60, %61, %62, %63, "
      "%64, %65, %66, %67, %68, %69, %70, %71, %72, %73, %74, %75, %76, %77, %78, %79, "
      "%80, %81, %82, %83, %84, %85, %86, %87, %88, %89, %90, %91, %92, %93, %94, %95"
      "}, %96, %97, r, 1, 1, 0, 1;\n"
    "add.u64 a, %96, 2;\nadd.u64 b, %97, %104;\n"
    "wgmma.mma_async.sync.aligned.m64n192k16.f32.bf16.bf16 {"
      "%0, %1, %2, %3, %4, %5, %6, %7, %8, %9, %10, %11, %12, %13, %14, %15, "
      "%16, %17, %18, %19, %20, %21, %22, %23, %24, %25, %26, %27, %28, %29, %30, %31, "
      "%32, %33, %34, %35, %36, %37, %38, %39, %40, %41, %42, %43, %44, %45, %46, %47, "
      "%48, %49, %50, %51, %52, %53, %54, %55, %56, %57, %58, %59, %60, %61, %62, %63, "
      "%64, %65, %66, %67, %68, %69, %70, %71, %72, %73, %74, %75, %76, %77, %78, %79, "
      "%80, %81, %82, %83, %84, %85, %86, %87, %88, %89, %90, %91, %92, %93, %94, %95"
      "}, a, b, t, 1, 1, 0, 1;\n"
    "wgmma.commit_group.sync.aligned;\nwgmma.wait_group.sync.aligned 1;\n"
    "add.u64 a, %96, 4;\nadd.u64 b, %97, 2*%104;\n"
    "wgmma.mma_async.sync.aligned.m64n192k16.f32.bf16.bf16 {"
      "%0, %1, %2, %3, %4, %5, %6, %7, %8, %9, %10, %11, %12, %13, %14, %15, "
      "%16, %17, %18, %19, %20, %21, %22, %23, %24, %25, %26, %27, %28, %29, %30, %31, "
      "%32, %33, %34, %35, %36, %37, %38, %39, %40, %41, %42, %43, %44, %45, %46, %47, "
      "%48, %49, %50, %51, %52, %53, %54, %55, %56, %57, %58, %59, %60, %61, %62, %63, "
      "%64, %65, %66, %67, %68, %69, %70, %71, %72, %73, %74, %75, %76, %77, %78, %79, "
      "%80, %81, %82, %83, %84, %85, %86, %87, %88, %89, %90, %91, %92, %93, %94, %95"
      "}, a, b, t, 1, 1, 0, 1;\n"
    "setp.ne.u32 q, %99, 0;\n@q mbarrier.arrive.shared::cta.b64 _, [%98];\n@q mbarrier.arrive.shared::cta.b64 _, [%98];\n@q mbarrier.arrive.shared::cta.b64 _, [%106];\n@q mbarrier.arrive.shared::cta.b64 _, [%106];\n"
    "mbarrier.test_wait.parity.shared::cta.b64 p, [%102], %103;\n"
    "mbarrier.test_wait.parity.shared::cta.b64 r, [%100], %101;\nand.pred p, p, r;\n"
    "add.u64 a, %96, 6;\nadd.u64 b, %97, 3*%104;\n"
    "wgmma.mma_async.sync.aligned.m64n192k16.f32.bf16.bf16 {"
      "%0, %1, %2, %3, %4, %5, %6, %7, %8, %9, %10, %11, %12, %13, %14, %15, "
      "%16, %17, %18, %19, %20, %21, %22, %23, %24, %25, %26, %27, %28, %29, %30, %31, "
      "%32, %33, %34, %35, %36, %37, %38, %39, %40, %41, %42, %43, %44, %45, %46, %47, "
      "%48, %49, %50, %51, %52, %53, %54, %55, %56, %57, %58, %59, %60, %61, %62, %63, "
      "%64, %65, %66, %67, %68, %69, %70, %71, %72, %73, %74, %75, %76, %77, %78, %79, "
      "%80, %81, %82, %83, %84, %85, %86, %87, %88, %89, %90, %91, %92, %93, %94, %95"
      "}, a, b, t, 1, 1, 0, 1;\n"
    "wgmma.commit_group.sync.aligned;\n"
    "@p bra.uni DN;\nmov.u32 n, 0;\nWT: mbarrier.try_wait.parity.shared::cta.b64 p, [%102], %103;\nmbarrier.try_wait.parity.shared::cta.b64 r, [%100], %101;\nand.pred p, p, r;\n@p bra.uni DN;\nadd.u32 n, n, 1;\nsetp.lt.u32 p, n, 0x100000;\n@p bra.uni WT;\nDN:\n"
    "}\n"
      :
      "+f"(d[0]), "+f"(d[1]), "+f"(d[2]), "+f"(d[3]), "+f"(d[4]), "+f"(d[5]), "+f"(d[6]), "+f"(d[7]),
      "+f"(d[8]), "+f"(d[9]), "+f"(d[10]), "+f"(d[11]), "+f"(d[12]), "+f"(d[13]), "+f"(d[14]), "+f"(d[15]),
      "+f"(d[16]), "+f"(d[17]), "+f"(d[18]), "+f"(d[19]), "+f"(d[20]), "+f"(d[21]), "+f"(d[22]), "+f"(d[23]),
      "+f"(d[24]), "+f"(d[25]), "+f"(d[26]), "+f"(d[27]), "+f"(d[28]), "+f"(d[29]), "+f"(d[30]), "+f"(d[31]),
      "+f"(d[32]), "+f"(d[33]), "+f"(d[34]), "+f"(d[35]), "+f"(d[36]), "+f"(d[37]), "+f"(d[38]), "+f"(d[39]),
      "+f"(d[40]), "+f"(d[41]), "+f"(d[42]), "+f"(d[43]), "+f"(d[44]), "+f"(d[45]), "+f"(d[46]), "+f"(d[47]),
      "+f"(d[48]), "+f"(d[49]), "+f"(d[50]), "+f"(d[51]), "+f"(d[52]), "+f"(d[53]), "+f"(d[54]), "+f"(d[55]),
      "+f"(d[56]), "+f"(d[57]), "+f"(d[58]), "+f"(d[59]), "+f"(d[60]), "+f"(d[61]), "+f"(d[62]), "+f"(d[63]),
      "+f"(d[64]), "+f"(d[65]), "+f"(d[66]), "+f"(d[67]), "+f"(d[68]), "+f"(d[69]), "+f"(d[70]), "+f"(d[71]),
      "+f"(d[72]), "+f"(d[73]), "+f"(d[74]), "+f"(d[75]), "+f"(d[76]), "+f"(d[77]), "+f"(d[78]), "+f"(d[79]),
      "+f"(d[80]), "+f"(d[81]), "+f"(d[82]), "+f"(d[83]), "+f"(d[84]), "+f"(d[85]), "+f"(d[86]), "+f"(d[87]),
      "+f"(d[88]), "+f"(d[89]), "+f"(d[90]), "+f"(d[91]), "+f"(d[92]), "+f"(d[93]), "+f"(d[94]), "+f"(d[95])
      : "l"(da), "l"(db), "r"(rel), "r"(doR), "r"(fa), "r"(pa), "r"(fb), "r"(pb), "n"(BSTEP), "r"(acc), "r"(rela) : "memory");
    else static_assert(W < 0, "variant not generated");
  }
};

#define NPRE 2
#define KV_T0 4000
#define KV2T 2000
#define XSD 400
#define CSD 600
#define ZW 300
#define TP_T 5000
#define PF2_D 200
#define PF_D 600
#define LKI 14
#define LEAD 4
#define HOLDA 30
#define HOLDB 28
#define CLK 1
#define HD 50
#define YD 600
#define HP0 3500
#define HPD 450
#define NSLEEP 100
#define MAP 4
#define EARLY 0

namespace {

constexpr int kS = 2048, kD = 640, kF = 1536;
constexpr int A_SLOT = 8192, B_SLOT = 24576, W_SLOT = 20480;
constexpr int OFF_A = 0;
constexpr int OFF_B = OFF_A + 10 * A_SLOT;
constexpr int XB_PL = 2112;
constexpr int CV_KE = 4224, CV_KO = CV_KE + 4160;
constexpr int CV_SZ = CV_KO + 4160;
constexpr int OFF_CV = OFF_B + 5 * B_SLOT;
constexpr int OFF_CS = OFF_CV + 2 * CV_SZ;
constexpr int OFF_XS = OFF_CS + 1536;
constexpr int OFF_BAR = OFF_XS + 512;
constexpr int SMEM_BYTES = OFF_BAR + 512;
static_assert(SMEM_BYTES <= 232448, "smem");
constexpr int OFF_RT = OFF_CS + 768;
constexpr int BAR_AF = OFF_BAR, BAR_BF = OFF_BAR + 8 * 10, BAR_WF = OFF_BAR + 8 * 15, BAR_ST = OFF_BAR + 8 * 21, BAR_XF = OFF_BAR + 8 * 23;
constexpr int BAR_ZP = OFF_BAR + 8 * 25, BAR_DUMMY = OFF_BAR + 8 * 27, BAR_PART = OFF_BAR + 8 * 28, BAR_WO = OFF_BAR + 8 * 29;
constexpr int BAR_YT = OFF_BAR + 8 * 30, BAR_KV2 = OFF_BAR + 8 * 31, BAR_XS = OFF_BAR + 8 * 32, BAR_HOLD = OFF_BAR + 8 * 33, BAR_ZG = OFF_BAR + 8 * 34;
constexpr int OFF_TAG = OFF_BAR + 8 * 35;
constexpr int BAR_HV = OFF_BAR + 8 * 36;
constexpr int BAR_HR = BAR_HV + 64, BAR_B2 = OFF_BAR + 8 * 26;
constexpr int BAR_XL = OFF_CS - 16;
constexpr int BAR_AE = OFF_BAR + 8 * 45, BAR_BE = OFF_BAR + 8 * 53, BAR_WE = OFF_BAR + 8 * 58;
constexpr int NB_WG = 1, NB_G1 = 3, NB_WO = 4, NB_CD = 5, NB_Z = 6, NB_C = 7, NB_KU = 8, NB_SV = 9, NB_KF = 12, NB_G1D = 13, NB_KU2 = 14, NB_KL = 15;

#define NB_SV2(h) ((h) ? NB_KU2 : NB_KU)

constexpr int CNT_KV = 0, CNT_WO = 4, CNT_Z = 8;
struct Scratch {
  uint8_t kvx[kD * 4096];
  uint8_t z2[4 * 32 * 24576];
  uint8_t h[32 * 12 * 8192];
  uint8_t wo[4 * 12 * 20480];
  uint8_t y[kD * 4096];
  uint4 zstat[32 * 128];
  uint2 xstat[kS];
  uint32_t colsum[kF];
  uint32_t cnt[32];
  uint32_t hflag[32 * 32];
  uint32_t epoch[136];

};
__device__ __align__(1024) Scratch g_scr;
#define TSP
#define TSA
#define TR(i)
#define STAMP(i)
#define STAMPE(i)
#define STAMP2(i)
#define STAMPW(i)

struct Params {
  Scratch* scr;
  int by_smid;
  const __nv_bfloat16 *x, *k, *v, *shift, *ssmk, *ssmD, *wsp, *bsp, *wout;
  __nv_bfloat16* out;
  CUtensorMap tmX, tmW, tmWsp, tmY, tmKV;
  uint16_t job[132];
};

__device__ __forceinline__ uint64_t mkdesc(uint32_t addr, uint32_t lbo, uint32_t sbo, uint32_t swz) {
  return (uint64_t)((addr & 0x3FFFF) >> 4) | ((uint64_t)(lbo >> 4) << 16) | ((uint64_t)(sbo >> 4) << 32) | ((uint64_t)swz << 62);
}
#define WG_FENCE() asm volatile("wgmma.fence.sync.aligned;" ::: "memory")
#define WG_COMMIT() asm volatile("wgmma.commit_group.sync.aligned;" ::: "memory")
#define WG_WAIT(n) asm volatile("wgmma.wait_group.sync.aligned %0;" ::"n"(n) : "memory")
template <int N> __device__ __forceinline__ void acc_fence(float* d) {
#pragma unroll
  for (int i = 0; i < N; i++) asm volatile("" : "+f"(d[i])::"memory");
}
__device__ __forceinline__ void mbar_init(uint32_t bar, int cnt) { asm volatile("mbarrier.init.shared::cta.b64 [%0], %1;" ::"r"(bar), "r"(cnt) : "memory"); }
__device__ __forceinline__ void mbar_expect(uint32_t bar, uint32_t bytes) { asm volatile("mbarrier.arrive.expect_tx.shared::cta.b64 _, [%0], %1;" ::"r"(bar), "r"(bytes) : "memory"); }
__device__ __forceinline__ void mbar_arrive(uint32_t bar) { asm volatile("mbarrier.arrive.shared::cta.b64 _, [%0];" ::"r"(bar) : "memory"); }
__device__ __forceinline__ void mbar_arrive_if(uint32_t bar, bool c) {
  asm volatile("{\n.reg .pred p;\nsetp.ne.u32 p, %1, 0;\n@p mbarrier.arrive.shared::cta.b64 _, [%0];\n}\n" ::"r"(bar), "r"((uint32_t)c) : "memory");
}
__device__ __forceinline__ bool mbar_try(uint32_t bar, uint32_t parity) {
  uint32_t ok;
  asm volatile("{\n.reg .pred p;\nmbarrier.try_wait.parity.shared::cta.b64 p, [%1], %2;\nselp.u32 %0, 1, 0, p;\n}\n" : "=r"(ok) : "r"(bar), "r"(parity) : "memory");
  return ok;
}
__device__ __forceinline__ void die() { asm volatile("st.volatile.global.u32 [%0], %1;" ::"l"(0ull), "r"(0) : "memory"); }
template <bool G = false> __device__ __forceinline__ void spin_guard(uint32_t& n, uint32_t = 0) { if (G && ++n == (1u << 20)) die(); }
template <bool G = false> __device__ __forceinline__ void mbar_wait(uint32_t bar, uint32_t parity) {
  uint32_t t0 = 0;
#pragma unroll 1
  while (!mbar_try(bar, parity)) spin_guard<G>(t0, bar);
}
__device__ __forceinline__ void mbar_wait2(uint32_t b0, uint32_t p0, uint32_t b1, uint32_t p1) { mbar_wait(b0, p0); mbar_wait(b1, p1); }
__device__ __forceinline__ int tid_now() { int v; asm volatile("mov.u32 %0, %%tid.x;" : "=r"(v)); return v & 127; }
__device__ __forceinline__ bool elect_one() {
  uint32_t p;
  asm volatile("{\n.reg .pred P;\nelect.sync _|P, 0xffffffff;\nselp.u32 %0, 1, 0, P;\n}\n" : "=r"(p));
  return p;
}
__device__ __forceinline__ void bar_sync(int id, int n) { asm volatile("bar.sync %0, %1;" ::"r"(id), "r"(n) : "memory"); }
__device__ __forceinline__ void bar_arrive(int id, int n) { asm volatile("bar.arrive %0, %1;" ::"r"(id), "r"(n) : "memory"); }
__device__ __forceinline__ void fence_async_smem() { asm volatile("fence.proxy.async.shared::cta;" ::: "memory"); }
__device__ __forceinline__ void bulk_g2s(uint32_t dst, const void* src, uint32_t bytes, uint32_t bar) {
  asm volatile("cp.async.bulk.shared::cluster.global.mbarrier::complete_tx::bytes [%0], [%1], %2, [%3];" ::"r"(dst), "l"(src), "r"(bytes), "r"(bar) : "memory");
}
__device__ __forceinline__ void bulk_s2g(void* dst, uint32_t src, uint32_t bytes) {
  asm volatile("cp.async.bulk.global.shared::cta.bulk_group [%0], [%1], %2;" ::"l"(dst), "r"(src), "r"(bytes) : "memory");
}
__device__ __forceinline__ void tma2d(uint32_t dst, const CUtensorMap* m, int c0, int c1, uint32_t bar) {
  asm volatile("cp.async.bulk.tensor.2d.shared::cluster.global.mbarrier::complete_tx::bytes [%0], [%1, {%3, %4}], [%2];" ::"r"(dst), "l"(m), "r"(bar), "r"(c0), "r"(c1) : "memory");
}
__device__ __forceinline__ void tma3d(uint32_t dst, const CUtensorMap* m, int c0, int c1, int c2, uint32_t bar) {
  asm volatile("cp.async.bulk.tensor.3d.shared::cluster.global.mbarrier::complete_tx::bytes [%0], [%1, {%3, %4, %5}], [%2];" ::"r"(dst), "l"(m), "r"(bar), "r"(c0), "r"(c1), "r"(c2) : "memory");
}
__device__ __forceinline__ uint4 ld_ll4(const void* p) {
  uint64_t a, b;
  asm volatile("ld.relaxed.gpu.global.v2.u64 {%0,%1}, [%2];" : "=l"(a), "=l"(b) : "l"(p) : "memory");
  return make_uint4((uint32_t)a, (uint32_t)(a >> 32), (uint32_t)b, (uint32_t)(b >> 32));
}
__device__ __forceinline__ void st_ll4(void* p, uint32_t a, uint32_t b, uint32_t c, uint32_t d) {
  asm volatile("st.relaxed.gpu.global.v2.u64 [%0], {%1,%2};" ::"l"(p), "l"(a | ((uint64_t)b << 32)), "l"(c | ((uint64_t)d << 32)) : "memory");
}
__device__ __forceinline__ void st_ll2(void* p, uint32_t a, uint32_t b) { asm volatile("st.relaxed.gpu.global.u64 [%0], %1;" ::"l"(p), "l"(a | ((uint64_t)b << 32)) : "memory"); }
__device__ __forceinline__ void wgmma_colsum(float* d, uint64_t da, uint64_t db) {
  asm volatile("{\n.reg .pred p;\nsetp.ne.b32 p, 1, 0;\nwgmma.mma_async.sync.aligned.m64n8k16.f32.bf16.bf16 {%0, %1, %2, %3}, %4, %5, p, 1, 1, 1, 0;\n}\n"
               : "+f"(d[0]), "+f"(d[1]), "+f"(d[2]), "+f"(d[3]) : "l"(da), "l"(db));
}
__device__ __forceinline__ void prefetch_l2(const void* p) { asm volatile("prefetch.global.L2 [%0];" ::"l"(p)); }
template <bool SLEEP = true> __device__ __forceinline__ void pace(uint32_t& t, uint32_t dt) {
  t += dt;
  while ((int32_t)((uint32_t)clock() - t) < 0) { if (SLEEP) __nanosleep(NSLEEP); }
}
__device__ __forceinline__ void red_release(uint32_t* p) { asm volatile("red.release.gpu.global.add.u32 [%0], 1;" ::"l"(p) : "memory"); }
__device__ __forceinline__ uint4 ldg4(const void* p) { uint4 v; asm volatile("ld.global.v4.u32 {%0,%1,%2,%3}, [%4];" : "=r"(v.x), "=r"(v.y), "=r"(v.z), "=r"(v.w) : "l"(p) : "memory"); return v; }
__device__ __forceinline__ uint32_t ldg1(const void* p) { uint32_t v; asm volatile("ld.global.u32 %0, [%1];" : "=r"(v) : "l"(p) : "memory"); return v; }
__device__ __forceinline__ void stg4_if(void* p, uint32_t a, uint32_t b, uint32_t c, uint32_t d, bool on) {
  asm volatile("{\n.reg .pred p;\nsetp.ne.u32 p, %5, 0;\n@p st.global.v4.u32 [%0], {%1,%2,%3,%4};\n}\n" ::"l"(p), "r"(a), "r"(b), "r"(c), "r"(d), "r"((uint32_t)on) : "memory");
}
template <int OFF> __device__ __forceinline__ uint32_t lds32(uint32_t a) { uint32_t v; asm volatile("ld.shared.u32 %0, [%1+%2];" : "=r"(v) : "r"(a), "n"(OFF)); return v; }
__device__ __forceinline__ uint4 lds128(uint32_t a) { uint4 v; asm volatile("ld.shared.v4.u32 {%0,%1,%2,%3}, [%4];" : "=r"(v.x), "=r"(v.y), "=r"(v.z), "=r"(v.w) : "r"(a) : "memory"); return v; }
__device__ __forceinline__ float2 lds64f(uint32_t a) { float2 v; asm volatile("ld.shared.v2.f32 {%0,%1}, [%2];" : "=f"(v.x), "=f"(v.y) : "r"(a) : "memory"); return v; }
__device__ __forceinline__ void sts64f(uint32_t a, float x, float y) { asm volatile("st.shared.v2.f32 [%0], {%1,%2};" ::"r"(a), "f"(x), "f"(y) : "memory"); }
__device__ __forceinline__ void sts32(uint32_t a, uint32_t x) { asm volatile("st.shared.u32 [%0], %1;" ::"r"(a), "r"(x) : "memory"); }
__device__ __forceinline__ void sts128(uint32_t a, uint32_t x, uint32_t y, uint32_t z, uint32_t w) { asm volatile("st.shared.v4.u32 [%0], {%1,%2,%3,%4};" ::"r"(a), "r"(x), "r"(y), "r"(z), "r"(w) : "memory"); }
__device__ __forceinline__ void stsm4(uint32_t a, uint32_t r0, uint32_t r1, uint32_t r2, uint32_t r3) {
  asm volatile("stmatrix.sync.aligned.m8n8.x4.shared.b16 [%0], {%1,%2,%3,%4};" ::"r"(a), "r"(r0), "r"(r1), "r"(r2), "r"(r3) : "memory");
}
__device__ __forceinline__ void stsm4t(uint32_t a, uint32_t r0, uint32_t r1, uint32_t r2, uint32_t r3) {
  asm volatile("stmatrix.sync.aligned.m8n8.x4.trans.shared.b16 [%0], {%1,%2,%3,%4};" ::"r"(a), "r"(r0), "r"(r1), "r"(r2), "r"(r3) : "memory");
}
__device__ __forceinline__ void ldsm4t(uint32_t* r, uint32_t a) {
  asm volatile("ldmatrix.sync.aligned.m8n8.x4.trans.shared.b16 {%0,%1,%2,%3}, [%4];" : "=r"(r[0]), "=r"(r[1]), "=r"(r[2]), "=r"(r[3]) : "r"(a) : "memory");
}
__device__ __forceinline__ uint32_t pack2(float lo, float hi) { uint32_t r; asm("cvt.rn.bf16x2.f32 %0, %1, %2;" : "=r"(r) : "f"(hi), "f"(lo)); return r; }
__device__ __forceinline__ float bf_lo(uint32_t u) { return __uint_as_float(u << 16); }
__device__ __forceinline__ float bf_hi(uint32_t u) { return __uint_as_float(u & 0xffff0000u); }
__device__ __forceinline__ uint32_t hmul2(uint32_t a, uint32_t b) { uint32_t r; asm("mul.rn.bf16x2 %0, %1, %2;" : "=r"(r) : "r"(a), "r"(b)); return r; }
__device__ __forceinline__ uint32_t hfma2(uint32_t a, uint32_t b, uint32_t c) { uint32_t r; asm("fma.rn.bf16x2 %0, %1, %2, %3;" : "=r"(r) : "r"(a), "r"(b), "r"(c)); return r; }
__device__ __forceinline__ uint32_t prmt(uint32_t a, uint32_t b, uint32_t s) { return __byte_perm(a, b, s); }

__device__ __forceinline__ uint32_t ld_relaxed(const uint32_t* p) { uint32_t v; asm volatile("ld.relaxed.gpu.global.u32 %0, [%1];" : "=r"(v) : "l"(p) : "memory"); return v; }
__device__ __forceinline__ void acquire_fence() { asm volatile("fence.acquire.gpu;\nfence.proxy.async.global;" ::: "memory"); }
__device__ __forceinline__ uint32_t load_epoch(const Params& p, int idx, int lane) { return ld_relaxed(&p.scr->epoch[idx + (((lane * lane) & 3) == 2 ? 1 : 0)]); }
template <bool G, class L, class C>
__device__ __forceinline__ auto poll(L load, C ok) {
  uint32_t t0 = 0;
  auto a = load();
#pragma unroll 1
  while (!__all_sync(0xffffffff, ok(a))) { spin_guard<G>(t0); a = load(); }
  return a;
}
__device__ __forceinline__ void poll_flags4(const uint32_t* flags, uint32_t tag, int lane) {
  poll<false>([&]() { return ld_relaxed(flags + (lane & 3) * 8); }, [&](uint32_t v) { return v == tag; });
  acquire_fence();
}
__device__ __forceinline__ void st_relaxed(uint32_t* p, uint32_t v) { asm volatile("st.relaxed.gpu.global.u32 [%0], %1;" ::"l"(p), "r"(v) : "memory"); }
__device__ __forceinline__ uint32_t tag8(uint32_t tag) { return (tag & 127) | 128; }
__device__ __forceinline__ uint32_t tagged(float v, uint32_t t8) { return (__float_as_uint(v) & ~255u) | t8; }
__device__ __forceinline__ void reset_sector(uint32_t* f) { st_ll4(f, 0, 0, 0, 0); st_ll4(f + 4, 0, 0, 0, 0); }
template <bool G = false> __device__ __forceinline__ void poll_counter(const uint32_t* cnt, uint32_t target) {
  poll<G>([&]() { return ld_relaxed(cnt); }, [&](uint32_t v) { return v == target; });
  acquire_fence();
}

__device__ __forceinline__ uint32_t hadd2(uint32_t a, uint32_t b) { uint32_t r; asm("add.rn.bf16x2 %0, %1, %2;" : "=r"(r) : "r"(a), "r"(b)); return r; }
__device__ __forceinline__ uint32_t htanh2(uint32_t a) { uint32_t r; asm("tanh.approx.bf16x2 %0, %1;" : "=r"(r) : "r"(a)); return r; }
__device__ __forceinline__ void red_relaxed(uint32_t* p) { asm volatile("red.relaxed.gpu.global.add.u32 [%0], 1;" ::"l"(p) : "memory"); }
__device__ __forceinline__ void bulk_commit_wait() { asm volatile("cp.async.bulk.commit_group;\ncp.async.bulk.wait_group 0;" ::: "memory"); }

__host__ __device__ constexpr uint32_t w_pos(int j) { j -= j >= 6 ? 6 : 0; return OFF_B + (j >= 3 ? j - 3 : j + 3) * W_SLOT; }
__host__ __device__ constexpr uint32_t w_full(int j) { return BAR_WF + 8 * (j >= 6 ? j - 6 : j); }
__host__ __device__ constexpr uint32_t h_pos(int i) { return (i >= 9 ? i - 9 : i) * A_SLOT; }
__device__ __forceinline__ int g3_block(int cb, int it) { return it < 3 ? cb * 3 + it : (it - 3 < cb * 3 ? it - 3 : it); }

#define GSTAMP(m, i)
struct NoHook { __device__ __forceinline__ void operator()() const {} };
template <int MODE, class F = NoHook>
__device__ __forceinline__ void gemm192(float* d, uint32_t sb, uint32_t doR TSP, F hook = F()) {
  constexpr int NKB = MODE == 1 ? 32 : 10, W = MODE == 3 ? 1 : 2, RA = MODE == 0 ? 0 : 2;
  const uint64_t da0 = mkdesc(sb + OFF_A, 16, 1024, 1), db0 = mkdesc(sb + OFF_B, 8192, 1024, 1);
  auto sa = [](int i) { return MODE == 1 ? (i + 3) & 7 : i; };
  auto pa = [](int i) { return MODE == 1 ? ((i >> 3) & 1) ^ 1 : 0; };
  const uint32_t dummy = sb + BAR_DUMMY;
  auto ea = [&](int i) { return MODE == 3 && i >= 8 ? dummy : sb + BAR_AE + 8 * sa(i); };
  uint32_t rel = dummy, rela = dummy;
  uint32_t pb = 0, acc = MODE == 1;
  int s = 0;
  acc_fence<96>(d);
  if (W == 2) mbar_wait(sb + BAR_AF + 8 * sa(0), pa(0));
  mbar_wait(sb + BAR_BF, 0);
  WG_FENCE();
#pragma unroll 1
  for (int i = 0; i < NKB - 1; i++) {
    GSTAMP(MODE, i);
    const int n = s == 4 ? 0 : s + 1;
    if (n == 0) pb ^= 1;
    KB<192>::run<W, 2, RA, 128>(d, da0 + sa(i) * (A_SLOT >> 4), db0 + s * (B_SLOT >> 4), rel, rela, doR, sb + BAR_AF + 8 * sa(i + 1), pa(i + 1), sb + BAR_BF + 8 * n, pb, acc);
    rel = sb + BAR_BE + 8 * s;
    rela = ea(i);
    s = n;
    acc = 1;
  }
  hook();
  GSTAMP(MODE, NKB - 1);
  KB<192>::run<0, 2, RA, 128>(d, da0 + sa(NKB - 1) * (A_SLOT >> 4), db0 + s * (B_SLOT >> 4), rel, rela, doR, 0, 0, 0, 0, 1);
  WG_WAIT(0);
  GSTAMP(MODE, NKB);
  acc_fence<96>(d);
  mbar_arrive_if(sb + BAR_BE + 8 * s, doR);
  mbar_arrive_if(sb + BAR_BE + 8 * s, doR);
  if (RA) { mbar_arrive_if(ea(NKB - 1), doR); mbar_arrive_if(ea(NKB - 1), doR); }
}
template <int I, int I1, bool OWN>
__device__ __forceinline__ void gemm3(float* d, uint32_t sb, uint64_t da0, uint64_t db0, uint32_t doR, uint32_t doR3 TSP) {
  if constexpr (I < I1) {
    GSTAMP(2, I);
    constexpr int W = (I == 11 || (OWN && I == 2)) ? 0 : (I < 2 ? 1 : 2), RC = I >= 1 && I <= 6;
    KB<80>::run<W, RC, I == 3, 320>(d, da0 + (h_pos(I) >> 4), db0 + (w_pos(I) >> 4), sb + (BAR_WE - 8 + 8 * I), sb + BAR_B2, I == 3 ? doR3 : doR,
                                    sb + (BAR_HV - 16 + 8 * I), I + 1 >= 9, sb + w_full(I + 1), I + 1 >= 6, I > 0);
    gemm3<I + 1, I1, OWN>(d, sb, da0, db0, doR, doR3 TSA);
  }
}

__device__ __forceinline__ uint32_t val_off(int lane) { return lane * 32 + ((lane >> 2) & 1) * 16 + (lane >> 3) * 4; }
template <int NK, int PAD = 0, class F>
__device__ __forceinline__ void validate(uint32_t a, uint32_t par, uint32_t rt, F reload) {
  uint32_t t0 = 0;
#pragma unroll 1
  while (true) {
    uint32_t v[NK], any = 0;
#pragma unroll
    for (int i = 0; i < NK; i++) asm volatile("ld.shared.u32 %0, [%1];" : "=r"(v[i]) : "r"(a + i * 1024 + (i >> 1) * PAD) : "memory");
#pragma unroll
    for (int i = 0; i < NK; i++) any |= v[i] ^ par;
    if (!__any_sync(0xffffffff, any & 1)) break;
    spin_guard(t0);
    fence_async_smem();
    __syncwarp();
    if (elect_one()) { mbar_init(rt, 1); fence_async_smem(); mbar_expect(rt, NK * 1024); reload(); }
    __syncwarp();
    mbar_wait(rt, 0);
    __syncwarp();
    if (elect_one()) asm volatile("mbarrier.inval.shared::cta.b64 [%0];" ::"r"(rt) : "memory");
  }
}
__device__ __forceinline__ uint32_t part_addr(uint32_t sb, int j, int t) { const int q = j * 128 + t; return sb + OFF_B + 5 * W_SLOT + (q / 80) * 2560 + (q % 80) * 16; }
__device__ __forceinline__ uint32_t swz_base(uint32_t img, int w, int lane) { return img + (w * 16 + (lane & 15)) * 128 + (((lane >> 4) ^ lane) & 7) * 16; }

template <bool STATS>
__device__ __forceinline__ void gelu_tile(const float* d, uint32_t* z, float* st, uint32_t cs0, float2 s0, float2 s1, uint32_t done) {
  const float kA = 0.7978845608028654f, kB = 0.7978845608028654f * 0.044715f;
  const float ra = s0.y, rb = s1.y;
  const float a1 = kA * ra, a3 = kB * ra * ra * ra, b1 = kA * rb, b3 = kB * rb * rb * rb;
  const uint32_t c1[2] = {pack2(a1, a1), pack2(b1, b1)}, c3[2] = {pack2(a3, a3), pack2(b3, b3)};
  const float m[2] = {-s0.x, -s1.x};
  uint32_t S[2][2], Q[2][2];
#pragma unroll
  for (int j = 0; j < 24; j++) {
    if (!STATS && j && j % 6 == 0) mbar_wait(done, 0);
    const float2 cs = lds64f(cs0 + j * 32);
#pragma unroll
    for (int r = 0; r < 2; r++) {
      const uint32_t v = pack2(fmaf(m[r], cs.x, d[4 * j + 2 * r]), fmaf(m[r], cs.y, d[4 * j + 2 * r + 1]));
      uint32_t y = hfma2(v, htanh2(hmul2(v, hfma2(hmul2(v, v), c3[r], c1[r]))), v);
      asm volatile("" : "+r"(y));
      z[2 * j + r] = y;
      if (STATS) {
        S[r][j & 1] = j < 2 ? y : hadd2(S[r][j & 1], y);
        Q[r][j & 1] = j < 2 ? hmul2(y, y) : hfma2(y, y, Q[r][j & 1]);
      }
    }
  }
  if (STATS) {
#pragma unroll
    for (int r = 0; r < 2; r++) {
      st[2 * r] = (bf_lo(S[r][0]) + bf_hi(S[r][0])) + (bf_lo(S[r][1]) + bf_hi(S[r][1]));
      st[2 * r + 1] = (bf_lo(Q[r][0]) + bf_hi(Q[r][0])) + (bf_lo(Q[r][1]) + bf_hi(Q[r][1]));
    }
  }
}

__device__ __forceinline__ float2 quad_sum(const float* st, int t) {
  const bool o = t & 1;
  float s = (o ? st[2] : st[0]) + __shfl_xor_sync(0xffffffff, o ? st[0] : st[2], 1);
  float q = (o ? st[3] : st[1]) + __shfl_xor_sync(0xffffffff, o ? st[1] : st[3], 1);
  s += __shfl_xor_sync(0xffffffff, s, 2);
  q += __shfl_xor_sync(0xffffffff, q, 2);
  return make_float2(s, q);
}
template <int Q> __device__ __forceinline__ void conv_load(uint32_t* a, uint32_t ab) {
  a[0] = lds32<512 * Q>(ab);       a[1] = lds32<512 * Q + 256>(ab);  a[2] = lds32<512 * Q + 16>(ab);   a[3] = lds32<512 * Q + 272>(ab);
  a[4] = lds32<512 * Q + 32>(ab);  a[5] = lds32<512 * Q + 288>(ab);  a[6] = lds32<512 * Q + 48>(ab);   a[7] = lds32<512 * Q + 304>(ab);
  a[8] = lds32<512 * Q + 64>(ab);  a[9] = lds32<512 * Q + 320>(ab);  a[10] = lds32<512 * Q + 80>(ab);  a[11] = lds32<512 * Q + 336>(ab);
  a[12] = lds32<512 * Q + 96>(ab); a[13] = lds32<512 * Q + 352>(ab); a[14] = lds32<512 * Q + 112>(ab); a[15] = lds32<512 * Q + 368>(ab);
}
template <int Q, int S> __device__ __forceinline__ void conv_load4(uint32_t* a, uint32_t ab) {
  a[4 * S] = lds32<512 * Q + 32 * S>(ab);          a[4 * S + 1] = lds32<512 * Q + 32 * S + 256>(ab);
  a[4 * S + 2] = lds32<512 * Q + 32 * S + 16>(ab); a[4 * S + 3] = lds32<512 * Q + 32 * S + 272>(ab);
}
template <int Q, int L> __device__ __forceinline__ void conv_step2(float* d, uint32_t (*a)[16], uint32_t ab, uint64_t db) {
  constexpr int LL = L >= 0 ? L : 0;
  WG_FENCE();
  WG<128 - 16 * Q>::rs(d, a[Q], db + 16 * Q);
  if (L >= 0) conv_load4<LL, 0>(a[LL], ab);
  WG<128 - 16 * Q>::rs(d, a[Q] + 4, db + 1 + 16 * Q);
  if (L >= 0) conv_load4<LL, 1>(a[LL], ab);
  WG<128 - 16 * Q>::rs(d, a[Q] + 8, db + 2 + 16 * Q);
  if (L >= 0) conv_load4<LL, 2>(a[LL], ab);
  WG<128 - 16 * Q>::rs(d, a[Q] + 12, db + 3 + 16 * Q);
  WG_COMMIT();
  if (L >= 0) conv_load4<LL, 3>(a[LL], ab);
  if (Q == 0) WG_WAIT(0); else WG_WAIT(1);
}
template <int Q, int L> __device__ __forceinline__ void conv_step(float* d, uint32_t (*a)[16], uint32_t ab, uint64_t db) {
  WG_FENCE();
#pragma unroll
  for (int s = 0; s < 4; s++) WG<128 - 16 * Q>::rs(d, a[Q] + 4 * s, db + s + 16 * Q);
  WG_COMMIT();
  WG_WAIT(1);
  if (L >= 0) conv_load<(L >= 0 ? L : 0)>(a[L >= 0 ? L : 0], ab);
  if (Q == 0) WG_WAIT(0);
}

__device__ __forceinline__ void final_load_x(uint32_t (*xw)[10], const __nv_bfloat16* x0, int t) {
#pragma unroll
  for (int r = 0; r < 2; r++) {
    const __nv_bfloat16* q = x0 + r * 8 * kD;
    const uint4 u = ldg4(q + t * 8), v = ldg4(q + 32 + t * 8);
    asm volatile("ld.global.v2.u32 {%0,%1}, [%2];" : "=r"(xw[r][8]), "=r"(xw[r][9]) : "l"(q + 64 + t * 4) : "memory");
    xw[r][0] = u.x; xw[r][1] = u.y; xw[r][2] = u.z; xw[r][3] = u.w;
    xw[r][4] = v.x; xw[r][5] = v.y; xw[r][6] = v.z; xw[r][7] = v.w;
  }
}
template <class F>
__device__ __forceinline__ void final_out(const float* d, const uint32_t (*xw)[10], const uint32_t* rn, const float* c, uint32_t yt, __nv_bfloat16* o0, int w, int lane, F wait_y) {
  const int r8 = lane & 7, mi = lane >> 3, t = lane & 3;
  const uint32_t ya = yt + ((mi >> 1) * 8 + r8) * 128 + (((2 * w + (mi & 1)) ^ r8) << 4);
#pragma unroll
  for (int q = 0; q < 3; q++) {
    const int n = q < 2 ? 8 : 4;
    uint32_t gt[8], y[8];
#pragma unroll
    for (int e = 0; e < n; e++) {
      const int i = q * 8 + e;
      const uint32_t h = pack2(d[2 * i] * c[i & 1], d[2 * i + 1] * c[i & 1]);
      gt[e] = hmul2(hfma2(h, htanh2(h), h), hfma2(xw[i & 1][i >> 1], rn[i & 1], rn[2 + (i & 1)]));
      if (q == 0) asm volatile("" : "+r"(gt[e]));
    }
    if (q == 0) wait_y();
    ldsm4t(y, ya + q * 4096);
    if (q < 2) ldsm4t(y + 4, ya + q * 4096 + 2048);
#pragma unroll
    for (int e = 0; e < n; e++) y[e] = hfma2(gt[e], y[e], xw[e & 1][q * 4 + (e >> 1)]);
#pragma unroll
    for (int r = 0; r < 2; r++) {
      __nv_bfloat16* o = o0 + r * 8 * kD;
      if (q < 2) stg4_if(o + q * 32 + t * 8, y[r], y[2 + r], y[4 + r], y[6 + r], true);
      else asm volatile("st.global.v2.u32 [%0], {%1,%2};" ::"l"(o + 64 + t * 4), "r"(y[r]), "r"(y[2 + r]) : "memory");
    }
  }
}

struct Taps { uint4 r0, r1; uint32_t n0, n1, dd; };
__device__ __forceinline__ void load_taps(Taps& k, const Params& p, int ch, int tid) {
  const uint4* kp = (const uint4*)(p.ssmk + (size_t)ch * kS);
  k.r0 = ldg4(kp + tid); k.r1 = ldg4(kp + 128 + tid);
  k.n0 = ldg1(kp + tid + 1); k.n1 = tid < 127 ? ldg1(kp + 129 + tid) : 0u;
  k.dd = __bfloat16_as_ushort(p.ssmD[ch]);
}
__device__ __forceinline__ void convx_copy(const Params& p, uint32_t cv, uint32_t bar, int ch) {
  bulk_g2s(cv, p.scr->kvx + (size_t)ch * 4096, 2048, bar);
  bulk_g2s(cv + XB_PL, p.scr->kvx + (size_t)ch * 4096 + 2048, 2048, bar);
}
__device__ __forceinline__ void convx_issue(const Params& p, uint32_t sb, int h, int ch) {
  if (elect_one()) { mbar_expect(sb + BAR_XL + 8 * h, 4096); convx_copy(p, sb + OFF_CV + (1 - h) * CV_SZ, sb + BAR_XL + 8 * h, ch); }
}
__device__ __forceinline__ void convx_finish(const Params& p, uint32_t sb, int h, int ch, int i, uint32_t par, int lane) {
  const uint32_t cv = sb + OFF_CV + (1 - h) * CV_SZ, rt = sb + BAR_XL - 16 + 8 * h;
  mbar_wait(sb + BAR_XL + 8 * h, i & 1);
  validate<4, XB_PL - 2048>(cv + lane * 32, par, rt, [&]() { convx_copy(p, cv, rt, ch); });
  if (elect_one()) mbar_arrive(sb + BAR_XF + 8 * h);
}
__device__ __forceinline__ void zero_pads(uint32_t cv, int lane) {
  if (lane < 8) sts128(cv + (lane >> 2) * XB_PL + 2048 + (lane & 3) * 16, 0, 0, 0, 0);
  else if (lane < 12) sts128(cv + ((lane & 2) ? CV_KO : CV_KE) + (lane & 1) * 16, 0, 0, 0, 0);
  fence_async_smem();
  __syncwarp();
}
__device__ __forceinline__ int y_row(int c) {
  const int cc = c % 80;
  return c - cc + (cc & 1) + (cc < 64 ? (cc & 32) + ((cc >> 1) & 3) * 8 + ((cc >> 3) & 3) * 2 : 64 + ((cc >> 1) & 1) * 8 + ((cc >> 2) & 3) * 2);
}
struct KvRegs { uint32_t k[11], v[8]; uint4 sh; };
__device__ __forceinline__ void kv_load(KvRegs& q, const __nv_bfloat16* kp, const __nv_bfloat16* vp, const __nv_bfloat16* sp, bool halo) {
#pragma unroll
  for (int i = 0; i < 11; i++) q.k[i] = (i >= 3 || halo) ? ldg1(kp + i * kD) : 0u;
#pragma unroll
  for (int i = 0; i < 8; i++) q.v[i] = ldg1(vp + i * kD);
  q.sh = ldg4(sp);
}
__device__ __forceinline__ void kv_calc(const KvRegs& q, uint32_t* o) {
  const uint32_t w0 = prmt(q.sh.x, q.sh.z, 0x5410), w1 = prmt(q.sh.x, q.sh.z, 0x7632), w2 = prmt(q.sh.y, q.sh.w, 0x5410), w3 = prmt(q.sh.y, q.sh.w, 0x7632);
  uint32_t r[8];
#pragma unroll
  for (int i = 0; i < 8; i++) r[i] = hmul2(hfma2(q.k[i + 3], w0, hfma2(q.k[i + 2], w1, hfma2(q.k[i + 1], w2, hmul2(q.k[i], w3)))), q.v[i]);
#pragma unroll
  for (int i = 0; i < 4; i++) { o[i] = prmt(r[7 - 2 * i], r[6 - 2 * i], 0x5410); o[4 + i] = prmt(r[7 - 2 * i], r[6 - 2 * i], 0x7632); }
}
__device__ __forceinline__ void kv_put(const uint32_t* o, uint32_t oa, uint32_t tm, uint32_t tb) {
  sts128(oa, (o[0] & tm) | tb, o[1], o[2], o[3]);
  sts128(oa + 2048, (o[4] & tm) | tb, o[5], o[6], o[7]);
}

__device__ __forceinline__ void kv_store(const Params& p, uint32_t src, int tb, int unit) {
  asm volatile("cp.async.bulk.tensor.3d.global.shared::cta.bulk_group [%0, {%2, %3, %4}], [%1];" ::"l"(&p.tmKV), "r"(src), "r"((63 - tb) * 16), "r"(unit * 32), "r"(0) : "memory");
}
__device__ __forceinline__ uint32_t kv_stage_addr(int w, int lane) { return ((3 - w) & 1) * 1024 + lane * 32 + ((((3 - w) >> 1) ^ (lane >> 2)) & 1) * 16; }

template <class F>
__device__ __forceinline__ void conv_service(const Params& p, uint32_t sb, int h, int ch, uint32_t par, int lane, F mid) {
#pragma unroll 1
  for (int i = 0; i < 2 + h; i++, ch += 128) {
    bar_sync(NB_SV + h, 160);
    if (i < h) convx_issue(p, sb, h, ch + 128);
    uint8_t* dst = p.scr->y + (size_t)y_row(ch) * 4096;
    bar_sync(NB_SV2(h), 160);
    if (elect_one()) {
      bulk_s2g(dst, sb + OFF_A + 9 * A_SLOT + h * 4096, 4096);
      bulk_commit_wait();
    }
    __syncwarp();
    if (i > h) break;
    if (i == h) { mid(); mbar_wait(sb + BAR_KV2, 0); convx_issue(p, sb, h, ch + 128); }
    convx_finish(p, sb, h, ch + 128, i + 1, par, lane);
  }
}
__device__ __forceinline__ void conv_worker(const Params& p, Taps& k, uint32_t sb, int h, int ch0, int w, int lane, int tid, int rb, int cb TSP) {
  const uint32_t cv = sb + OFF_CV + (1 - h) * CV_SZ, yb0 = sb + OFF_A + 9 * A_SLOT + h * 4096, xbar = sb + BAR_XF + 8 * h;
  const int n = 2 + h, nbar = NB_WG + h;
  const int g = lane >> 2, t = lane & 3, w0 = w & 1, w1 = w >> 1;
  const uint32_t ab = cv + ((g & 1) ? CV_KE : CV_KO) + 32 + 2 * (64 * w0 + 8 * w1 + ((g - 15) & ~1) + 2 * t);
  const uint32_t scA = cv + (w1 ? CV_KO : CV_KE) + 32, scB = scA + 2048;
  const int dl = (t >> 1) ^ 1, col = lane & 7, mi = lane >> 3;
  if (h == 0) mbar_wait(xbar, 0);
  TR(26);
#pragma unroll 1
  for (int i = 0; i < n; i++) {
    if (tid == 0) {
      k.r0.x = (k.r0.x & 0xffff0000u) | (pack2(bf_lo(k.r0.x) + bf_lo(k.dd), 0.f) & 0xffffu);
      sts32(cv + CV_KO + 28, k.r0.x << 16);
    }
    sts128(cv + CV_KE + 32 + tid * 16, k.r0.x, k.r0.y, k.r0.z, k.r0.w);
    sts128(cv + CV_KO + 32 + tid * 16, prmt(k.r0.x, k.r0.y, 0x5432), prmt(k.r0.y, k.r0.z, 0x5432), prmt(k.r0.z, k.r0.w, 0x5432), prmt(k.r0.w, k.n0, 0x5432));
    sts128(cv + CV_KE + 2080 + tid * 16, k.r1.x, k.r1.y, k.r1.z, k.r1.w);
    sts128(cv + CV_KO + 2080 + tid * 16, prmt(k.r1.x, k.r1.y, 0x5432), prmt(k.r1.y, k.r1.z, 0x5432), prmt(k.r1.z, k.r1.w, 0x5432), prmt(k.r1.w, k.n1, 0x5432));
    TR(30 + i * 10);
    if (i + 1 < n) load_taps(k, p, ch0 + (i + 1) * 128, tid);
    bar_sync(nbar, 128);
    TR(31 + i * 10);
    const uint64_t db = mkdesc(cv + (i & 0x1000), XB_PL, 128, 0);
    float d[64];
    uint32_t a[8][16];
    conv_load<7>(a[7], ab);
    conv_load<6>(a[6], ab);
    conv_load<5>(a[5], ab);
    conv_load<4>(a[4], ab);
    if (CLK == 1) conv_load<3>(a[3], ab);
#pragma unroll
    for (int j = 0; j < 64; j++) d[j] = 0.f;
    if (i == 0) STAMPW(h ? 43 : 8);
    TR(32 + i * 10);
    mbar_wait2(xbar, i & 1, sb + (i + 1 < n ? BAR_ZG : (h ? BAR_HOLD : BAR_ST)), i + 1 == n && !h);
    if (i == 0) STAMPW(h ? 51 : 7);
    TR(33 + i * 10);
    if (CLK == 1) {
      conv_step2<7, -1>(d, a, ab, db); conv_step2<6, -1>(d, a, ab, db); conv_step2<5, 2>(d, a, ab, db); conv_step2<4, 1>(d, a, ab, db);
      conv_step2<3, 0>(d, a, ab, db); conv_step2<2, -1>(d, a, ab, db); conv_step2<1, -1>(d, a, ab, db); conv_step2<0, -1>(d, a, ab, db);
    } else if (CLK == 2) {
      conv_step2<7, -1>(d, a, ab, db); conv_step2<6, -1>(d, a, ab, db); conv_step2<5, 3>(d, a, ab, db); conv_step2<4, 2>(d, a, ab, db);
      conv_step2<3, 1>(d, a, ab, db); conv_step2<2, 0>(d, a, ab, db); conv_step2<1, -1>(d, a, ab, db); conv_step2<0, -1>(d, a, ab, db);
    } else {
    conv_step<7, -1>(d, a, ab, db); conv_step<6, -1>(d, a, ab, db); conv_step<5, -1>(d, a, ab, db); conv_step<4, 3>(d, a, ab, db);
    conv_step<3, 2>(d, a, ab, db); conv_step<2, 1>(d, a, ab, db); conv_step<1, 0>(d, a, ab, db); conv_step<0, -1>(d, a, ab, db);
    }
    acc_fence<64>(d);
    TR(34 + i * 10);
    bar_arrive(NB_SV + h, 160);
    if (i == 0) mbar_wait(sb + BAR_YT, 0);
    const uint32_t par = lds32<0>(sb + OFF_TAG);
    TR(35 + i * 10);
    float E[16][2];
#pragma unroll
    for (int j = 0; j < 15; j++) { E[j][0] = d[4 * j] + d[4 * j + 6]; E[j][1] = d[4 * j + 1] + d[4 * j + 7]; }
    E[15][0] = d[60]; E[15][1] = d[61];
    if (w0 == 0) {
#pragma unroll
      for (int j = 8; j < 16; j++) sts64f(scA + (j - 8) * 256 + lane * 8, E[j][0], E[j][1]);
    } else {
      const uint32_t a = scB - dl * 256 + (lane ^ 2) * 8;
#pragma unroll
      for (int j = 1; j < 8; j++) sts64f(a + j * 256, E[j][0], E[j][1]);
      sts64f(scB + (dl ? 7 * 256 : 0) + (lane ^ 2) * 8, dl ? E[8][0] : E[0][0], dl ? E[8][1] : E[0][1]);
    }
    TR(36 + i * 10);
    bar_sync(nbar, 128);
    uint32_t pk[8];
    const bool tg = w1 == 0 && g == 0;
    const uint32_t tm = tg ? ~0x10001u : ~0u, tb = tg && (par & 1) ? 0x10001u : 0;
    if (w0 == 0) {
#pragma unroll
      for (int j = 0; j < 8; j++) { const float2 v = lds64f(scB + j * 256 + lane * 8); pk[j] = (pack2(E[j][0] + v.x, E[j][1] + v.y) & tm) | tb; }
      const uint32_t ya = yb0 + 32 * (127 - (8 * mi + col)) + 16 * w1;
      stsm4t(ya, pk[0], pk[1], pk[2], pk[3]);
      stsm4t(ya - 1024, pk[4], pk[5], pk[6], pk[7]);
    } else {
      const uint32_t a0 = scA - dl * 256 + (lane ^ 2) * 8;
#pragma unroll
      for (int j = 9; j < 16; j++) { const float2 v = lds64f(a0 + (j - 8) * 256); pk[j - 8] = (pack2(E[j][0] + v.x, E[j][1] + v.y) & tm) | tb; }
      const float2 v = lds64f(scA + (dl ? 7 * 256 : 0) + (lane ^ 2) * 8);
      pk[0] = (pack2((dl ? 0.f : E[8][0]) + v.x, (dl ? 0.f : E[8][1]) + v.y) & tm) | tb;
      const uint32_t yb = yb0 + 32 * (127 - (92 + 8 * mi + col)) + 16 * w1;
      const uint32_t ya = (mi == 0 && col < 4) ? yb0 + 32 * (3 - col) + 16 * w1 : yb + 1024;
      stsm4t(ya, pk[0], pk[1], pk[2], pk[3]);
      stsm4t(yb, pk[4], pk[5], pk[6], pk[7]);
    }
    TR(37 + i * 10);
    fence_async_smem();
    bar_arrive(NB_SV2(h), 160);
    if (i + 1 < n) bar_sync(nbar, 128);
    TR(38 + i * 10);
    STAMPW((h ? 40 : 5) + i);
    if (i == 0 && h == 0) {
      const int tn = tid_now();
      {
        const int ln = tn & 31, t0 = (rb * 2 + (cb & 1)) * 32 + w * 8, c0 = (cb >> 1) * 320 + 192 + ln * 2;
        KvRegs q0, q1;
        uint32_t o[8];
        kv_load(q0, p.k + (size_t)(t0 - 3) * kD + c0, p.v + (size_t)t0 * kD + c0, p.shift + c0 * 4, t0 > 0);
        kv_load(q1, p.k + (size_t)(t0 - 3) * kD + c0 + 64, p.v + (size_t)t0 * kD + c0 + 64, p.shift + c0 * 4 + 256, t0 > 0);
        const uint32_t oa = sb + OFF_A + 8 * A_SLOT + kv_stage_addr(w, ln), km = w >= 2 ? ~1u : ~0u, kb = w >= 2 ? lds32<0>(sb + OFF_TAG) & 1 : 0;
        kv_calc(q0, o);
        kv_put(o, oa, km, kb);
        kv_calc(q1, o);
        kv_put(o, oa + 4096, km, kb);
        fence_async_smem();
        bar_arrive(NB_KL, 160);
      }
      STAMPW(56);
      const int u = (tn >> 3) % 5, kg = rb * 3 + (tn < 120 ? (tn >> 3) / 5 : 0), c = u < 4 ? (u >> 1) * 10 + (u & 1) * 4 : 8, o2 = u < 4 ? 2 : 10;
      const uint4* wp = (const uint4*)(p.wout + (size_t)(kg * 8 + (tn & 7)) * kD + cb * 160) + c;
      const uint4 w0 = ldg4(wp), w1 = ldg4(wp + 1), w2 = ldg4(wp + o2), w3 = ldg4(wp + o2 + 1);
      uint8_t* dst = p.scr->wo + (size_t)cb * (12 * W_SLOT) + kg * 2560 + c * 128 + (tn & 7) * 16;
      const bool f = u < 4, on = tn < 120;
      stg4_if(dst, w0.x, f ? w1.x : w0.z, f ? w2.x : w1.x, f ? w3.x : w1.z, on);
      stg4_if(dst + 128, w0.y, f ? w1.y : w0.w, f ? w2.y : w1.y, f ? w3.y : w1.w, on);
      stg4_if(dst + o2 * 128, f ? w0.z : w2.x, f ? w1.z : w2.z, f ? w2.z : w3.x, w3.z, on);
      stg4_if(dst + o2 * 128 + 128, f ? w0.w : w2.y, f ? w1.w : w2.w, f ? w2.w : w3.y, w3.w, on);
      bar_arrive(NB_WO, 160);
    }
  }
}

__device__ __forceinline__ void release_held(uint32_t sb, int done, int lane) {
  mbar_arrive_if(sb + BAR_HOLD, done == HOLDB && lane == 0);
  mbar_arrive_if(sb + BAR_ST, done == HOLDA && lane == 0);
}
struct U6 { uint64_t a, b, c; };
__device__ __forceinline__ uint64_t ld_ll2(const void* p) { uint64_t a; asm volatile("ld.relaxed.gpu.global.u64 %0, [%1];" : "=l"(a) : "l"(p) : "memory"); return a; }
__device__ __forceinline__ void gather_colsum(const Params& p, uint32_t sb, int part, int cb, uint32_t tag8, int lane) {
  const uint32_t* src = p.scr->colsum + (uint32_t)((part ? 0 : 768) + cb * 192 + lane * 2);
  const uint64_t t2 = tag8 * 0x100000001ull;
  const U6 v = poll<false>([&]() { return U6{ld_ll2(src), ld_ll2(src + 64), ld_ll2(src + 128)}; },
                                    [&](const U6& u) { return (((u.a ^ t2) | (u.b ^ t2) | (u.c ^ t2)) & 0xff000000ffull) == 0; });
  const uint32_t dst = sb + OFF_CS + (part ? 0 : 768) + lane * 8;
  asm volatile("st.shared.u64 [%0], %1;\nst.shared.u64 [%0+256], %2;\nst.shared.u64 [%0+512], %3;" ::"r"(dst), "l"(v.a), "l"(v.b), "l"(v.c) : "memory");
  __syncwarp();
  mbar_arrive_if(sb + BAR_ST + 8 * part, lane == 0);
}

__device__ __forceinline__ void helper_cta(const Params& p, uint32_t sb, int cb, int warp, int lane TSP) {
  constexpr int NS = 9, ONES = NS * B_SLOT, BF = ONES + 256, BE = BF + 8 * NS;
  if (warp < NS && elect_one()) {
    mbar_init(sb + BF + 8 * warp, 1); mbar_init(sb + BE + 8 * warp, 1);
    fence_async_smem();
    if (warp == 0) { mbar_expect(sb + BF, B_SLOT); tma3d(sb, &p.tmW, 0, 0, 12 + cb * 3, sb + BF); }
  }
  if (warp == 15) { sts32(sb + ONES + lane * 4, 0x3f803f80u); sts32(sb + ONES + 128 + lane * 4, 0x3f803f80u); fence_async_smem(); }
  __syncthreads();
  if (warp == 4) {
    int s = 1, ph = 1;
    uint32_t tp = clock() + HP0;
#pragma unroll 1
    for (int it = 1; it < 20; it++) {
      if (it >= 10) pace(tp, HPD);
      mbar_wait(sb + BE + 8 * s, ph);
      if (elect_one()) { mbar_expect(sb + BF + 8 * s, B_SLOT); tma3d(sb + s * B_SLOT, &p.tmW, 0, (it < 10 ? it : it - 10) * 64, (it < 10 ? 12 : 0) + cb * 3, sb + BF + 8 * s); }
      if (++s == NS) { s = 0; ph ^= 1; }
    }
  } else if (warp < 4) {
    const uint32_t tag = load_epoch(p, 128 + cb, lane) + 1;
    const uint64_t db = mkdesc(sb + ONES, 128, 128, 0);
    uint32_t* dst = p.scr->colsum + cb * 192 + warp * 16 + (lane >> 2);
    if ((lane & 3) == 0) {
#pragma unroll 1
      for (int j = 0; j < 12; j++) st_relaxed(dst + (j < 6 ? 768 : 0) + ((j % 6) >> 1) * 64 + (j & 1) * 8, 0);
    }
    int s = 0, ph = 0;
#pragma unroll 1
    for (int part = 0; part < 2; part++) {
      float d[12];
#pragma unroll
      for (int i = 0; i < 12; i++) d[i] = 0.f;
#pragma unroll 1
      for (int it = 0; it < 10; it++) {
        mbar_wait(sb + BF + 8 * s, ph);
        const uint64_t da = mkdesc(sb + s * B_SLOT, 8192, 1024, 1);
        WG_FENCE();
#pragma unroll
        for (int j = 0; j < 12; j++) wgmma_colsum(d + 4 * (j % 3), da + (j % 3) * 512 + (j / 3) * 128, db);
        WG_COMMIT();
        WG_WAIT(1);
        mbar_arrive_if(sb + BE + 8 * (s == 0 ? NS - 1 : s - 1), threadIdx.x == 0 && (it | part) != 0);
        if (++s == NS) { s = 0; ph ^= 1; }
      }
      WG_WAIT(0);
      acc_fence<12>(d);
      if ((lane & 3) == 0) {
#pragma unroll
        for (int j = 0; j < 6; j++) st_relaxed(dst + (part ? 0 : 768) + (j >> 1) * 64 + (j & 1) * 8, tagged(d[2 * j], tag8(tag)));
      }
      STAMPW(1 + part);
    }
    if (threadIdx.x == 0) *(volatile uint32_t*)&p.scr->epoch[128 + cb] = tag;
  }
}

__global__ void __launch_bounds__(512, 1) fused_kernel(const __grid_constant__ Params p) {
  extern __shared__ __align__(1024) uint8_t smem[];
  const int warp = __shfl_sync(0xffffffff, (int)(threadIdx.x >> 5), 0);
  const int lane = threadIdx.x & 31;
  const uint32_t sb = __shfl_sync(0xffffffff, (uint32_t)__cvta_generic_to_shared(smem), 0);
  const uint32_t tstart = clock();
  int b = blockIdx.x;
  if (p.by_smid) asm volatile("mov.u32 %0, %%smid;" : "=r"(b));
  b = __shfl_sync(0xffffffff, b, 0);
  const int job = p.job[b], lin = job & 255, cb = job >> 8 & 3, rb = job >> 10;
  if (elect_one()) {
    mbar_init(sb + OFF_BAR + 8 * warp, 1);
    if (lin < 128) {
      if (warp < NPRE) { fence_async_smem(); mbar_expect(sb + BAR_AF + 8 * warp, A_SLOT); tma2d(sb + OFF_A + warp * A_SLOT, &p.tmX, warp * 64, rb * 64, sb + BAR_AF + 8 * warp); }
      if (warp >= 10 && warp < 10 + NPRE) { fence_async_smem(); mbar_expect(sb + OFF_BAR + 8 * warp, B_SLOT); tma3d(sb + OFF_B + (warp - 10) * B_SLOT, &p.tmW, 0, (warp - 10) * 64, 12 + cb * 3, sb + OFF_BAR + 8 * warp); }
    }
    if (warp >= 2 && warp < 5) asm volatile("prefetch.tensormap [%0];" ::"l"(&p.tmX + warp) : "memory");
    mbar_init(sb + OFF_BAR + 128 + 8 * warp, 1);
    if (warp != 3) mbar_init(sb + OFF_BAR + 256 + 8 * warp, (0x2224444444441111ull >> (4 * warp)) & 15);
    mbar_init(sb + OFF_BAR + 384 + 8 * warp, 2);
    if (warp < 2) mbar_init(sb + BAR_XL + 8 * warp, 1);
    asm volatile("fence.mbarrier_init.release.cluster;" ::: "memory");
  }
  if (lin >= 128) { helper_cta(p, sb, cb, warp, lane TSA); return; }
  const int chb = (cb >> 1) * 320 + rb * 2 + (cb & 1);
  if (sb & 1023) die();
  __syncthreads();

  if (warp >= 12) {
    asm volatile("setmaxnreg.dec.sync.aligned.u32 32;");
    const uint8_t* z2s = p.scr->z2 + (size_t)cb * 32 * B_SLOT;
    const char* wq = (const char*)p.wsp + (rb * 64 + cb * 16 + (lane >> 1)) * (kS * 2) + (lane & 1) * 128;
    if (warp == 12) {
      int s = NPRE, ph = 1;
#pragma unroll 1
      for (int it = NPRE; it < 20; it++) {
        if (it >= 5) mbar_wait<true>(sb + BAR_BE + 8 * s, ph);
        if (it < 5 && elect_one()) { mbar_expect(sb + BAR_AF + 8 * it, A_SLOT); tma2d(sb + OFF_A + it * A_SLOT, &p.tmX, it * 64, rb * 64, sb + BAR_AF + 8 * it); }
        if (elect_one()) {
          mbar_expect(sb + BAR_BF + 8 * s, B_SLOT);
          tma3d(sb + OFF_B + s * B_SLOT, &p.tmW, 0, (it < 10 ? it : it - 10) * 64, (it < 10 ? 12 : 0) + cb * 3, sb + BAR_BF + 8 * s);
        }
        if (it == 4) {
#pragma unroll 1
          for (int i = 5; i < 10; i++)
            if (elect_one()) { mbar_expect(sb + BAR_AF + 8 * i, A_SLOT); tma2d(sb + OFF_A + i * A_SLOT, &p.tmX, i * 64, rb * 64, sb + BAR_AF + 8 * i); }
          bar_arrive(NB_KF, 160);
        }
        STAMP2(32 + it);
        if (++s == 5) { s = 0; ph ^= 1; }
      }
      const uint32_t ztarget = (load_epoch(p, lin, lane) + 1) * 128;
#pragma unroll 1
      for (int i = 0; i < LEAD; i++) {
        mbar_wait<true>(sb + BAR_AE + 8 * (3 + i), 0);
        if (elect_one()) { mbar_expect(sb + BAR_AF + 8 * (3 + i), A_SLOT); tma2d(sb + OFF_A + (3 + i) * A_SLOT, &p.tmWsp, i * 64, rb * 64, sb + BAR_AF + 8 * (3 + i)); }
      }
      mbar_wait<true>(sb + BAR_ZP, 0);
      poll_counter<true>(p.scr->cnt + CNT_Z, ztarget);
      STAMP(24);
#pragma unroll 1
      for (int it = 0; it < 32; it++) {
        mbar_wait<true>(sb + BAR_BE + 8 * s, ph);
        if (elect_one()) {
          mbar_expect(sb + BAR_BF + 8 * s, B_SLOT);
          bulk_g2s(sb + OFF_B + s * B_SLOT, z2s + it * B_SLOT, B_SLOT, sb + BAR_BF + 8 * s);
        }
        if (it == 0) STAMP(22);
        const int ia = it + LEAD - 1, sa = (ia + 3) & 7;
        if (it >= 1 && ia < 32) {
          mbar_wait<true>(sb + BAR_AE + 8 * sa, (ia >> 3) & 1);
          if (elect_one()) { mbar_expect(sb + BAR_AF + 8 * sa, A_SLOT); tma2d(sb + OFF_A + sa * A_SLOT, &p.tmWsp, ia * 64, rb * 64, sb + BAR_AF + 8 * sa); }
        }
        if (HOLDA < 27 || HOLDB < 27) release_held(sb, it - 5, lane);
        STAMP2(52 + it);
        if (++s == 5) { s = 0; ph ^= 1; }
      }
      mbar_wait<true>(sb + BAR_WO, 0);
      acquire_fence();
#pragma unroll 1
      for (int it = 0; it < 12; it++) {
        if (it < 6) mbar_wait<true>(sb + BAR_BE + 8 * ((0x110443 >> (4 * it)) & 7), it < 3 ? 1 : 0);
        else mbar_wait<true>(sb + BAR_WE + 8 * (it - 6), 0);
        if (it < 5 && it != 2) release_held(sb, it < 2 ? 28 + it : 27 + it, lane);
        if (elect_one()) {
          mbar_expect(sb + w_full(it), W_SLOT);
          bulk_g2s(sb + w_pos(it), p.scr->wo + (size_t)(cb * 12 + g3_block(cb, it)) * W_SLOT, W_SLOT, sb + w_full(it));
        }
        STAMP2(84 + it);
      }
      mbar_wait<true>(sb + BAR_WE, 1);
    } else if (warp == 13) {
      const uint32_t tag = load_epoch(p, lin, lane) + 1;
      if (elect_one()) reset_sector(&p.scr->hflag[rb * 32 + cb * 8]);
      if (lane == 0) sts32(sb + OFF_TAG, tag8(tag));
      mbar_wait(sb + BAR_AF + 72, 0);
      { uint32_t tp = clock(); pace(tp, CSD); }
      gather_colsum(p, sb, 0, cb, tag8(tag), lane);
      STAMP(27);
      bar_sync(NB_Z, 160);
      if (elect_one()) {
        mbar_arrive(sb + BAR_ZG);
        bulk_s2g((void*)(z2s + rb * B_SLOT), sb + OFF_A, B_SLOT);
        bulk_commit_wait();
        mbar_arrive(sb + BAR_ZP);
        STAMPE(58);
        red_release(p.scr->cnt + CNT_Z);
      }
      __syncwarp();
      STAMP(28);
      {
        uint32_t tp = clock();
#pragma unroll 1
        for (int i = 1; i < 16; i++) {
          pace(tp, PF_D);
          prefetch_l2(wq + i * 256);
          if (i == LKI) bar_sync(NB_KL, 160);
          if ((i == LKI || i == LKI + 1) && elect_one()) {
            kv_store(p, sb + OFF_A + 8 * A_SLOT + (i - LKI) * 4096, rb * 2 + (cb & 1), (cb >> 1) * 5 + 3 + i - LKI);
            bulk_commit_wait();
            if (i > LKI) red_relaxed(p.scr->cnt + CNT_KV + 2 + (cb >> 1));
          }
          __syncwarp();
          if (i == LKI + 1) STAMP(59);
        }
      }
      if (!EARLY) poll_counter(p.scr->cnt + CNT_KV + 2 + (cb >> 1), tag * 64);
      if (elect_one()) mbar_arrive(sb + BAR_KV2);
      STAMP(34);
      const uint8_t* hs = p.scr->h + (size_t)rb * 12 * A_SLOT;
#pragma unroll 1
      for (int i = 0; i < 3; i++) {
        mbar_wait(sb + BAR_HR - 16 + 8 * i, 0);
        if (elect_one()) bulk_s2g((void*)(hs + (cb * 3 + i) * A_SLOT), sb + OFF_A + i * A_SLOT, A_SLOT);
      }
      if (elect_one()) {
        st_relaxed(&p.scr->hflag[rb * 32 + cb * 8], tag);
        bulk_commit_wait();
      }
      __syncwarp();
      STAMP(20);
      if (!EARLY) poll_flags4(p.scr->hflag + rb * 32, tag, lane);
      { uint32_t tp = clock(); pace<false>(tp, HD); }
      STAMP(37);
#pragma unroll 1
      for (int it = 3; it < 12; it++) {
        const uint32_t land = sb + BAR_AF + 8 * (it < 9 ? it : it - 9);
        if (it == 9) mbar_wait2(sb + BAR_PART, 0, sb + BAR_B2, 0);
        if (elect_one()) { mbar_expect(land, A_SLOT); bulk_g2s(sb + h_pos(it), hs + g3_block(cb, it) * A_SLOT, A_SLOT, land); }
      }
      STAMP(21);
    } else if (warp == 14) {
      const uint32_t tag = load_epoch(p, lin, lane) + 1;
      const int tb = rb * 2 + (cb & 1), u0 = (cb >> 1) * 5;
      const uint32_t ks = sb + OFF_CV + CV_SZ, par = __shfl_sync(0xffffffff, tag, 0);
      {
        uint32_t tp = tstart;
        pace(tp, TP_T);
        const char* q = (const char*)p.ssmk + chb * 4096 + lane * 128;
        prefetch_l2(q); prefetch_l2(q + 64 * 4096);
      }
      mbar_wait2(sb + BAR_XS, 0, sb + BAR_ST, 0);
      bar_sync(NB_KU, 160);
      if (elect_one()) { kv_store(p, ks, tb, u0); kv_store(p, ks + 4096, tb, u0 + 1); bulk_commit_wait(); red_relaxed(p.scr->cnt + CNT_KV + (cb >> 1)); }
      __syncwarp();
      STAMP(35);
      bar_sync(NB_KU2, 160);
      if (elect_one()) { kv_store(p, ks + 8192, tb, u0 + 2); bulk_commit_wait(); }
      __syncwarp();
      zero_pads(ks, lane);
      bar_arrive(NB_G1D, 64);
      STAMP(30);
      {
        uint32_t tp = clock();
        const size_t o = (size_t)(tb * 32 + lane) * (kD * 2) + (u0 + 3) * 128;
        const char* r = (const char*)p.wout + (rb * 24 + min(lane, 23)) * (kD * 2) + cb * 320;
        const char* q = (const char*)p.ssmk + (chb + 128) * 4096 + lane * 128;
#pragma unroll 1
        for (int i = 0; i < 10; i++) {
          pace(tp, PF2_D);
          prefetch_l2(i < 3 ? q + i * 64 * 4096 : (i < 7 ? (const char*)((i & 1) ? p.k : p.v) + o + ((i - 3) >> 1) * 128 : r + (i - 7) * 128));
        }
      }
      conv_service(p, sb, 0, chb + 64, par, lane, NoHook());
      bar_sync(NB_CD, 64);
      STAMP(47);
      if (!EARLY) mbar_wait(sb + BAR_WE + 40, 0);
      { uint32_t tp = clock(); pace<false>(tp, YD); }
      if (elect_one()) {
        mbar_expect(sb + BAR_YT, 20480);
#pragma unroll 1
        for (int i = 0; i < 4; i++) tma2d(sb + OFF_CV + i * 5120, &p.tmY, rb * 64, cb * 160 + i * 40, sb + BAR_YT);
      }
      if (lane == 0) *(volatile uint32_t*)&p.scr->epoch[lin] = tag;
      STAMP(23);
    } else {
      const uint32_t tag = load_epoch(p, lin, lane) + 1;
      mbar_wait(sb + BAR_AF + 72, 0);
      { uint32_t tp = clock(); pace(tp, XSD); }
      {
        const uint32_t t8 = tag8(tag);
        const uint4 u = poll<false>([&]() { return ld_ll4(&p.scr->xstat[rb * 64 + lane * 2]); },
                                                [&](const uint4& v) { return (((v.x ^ t8) | (v.y ^ t8) | (v.z ^ t8) | (v.w ^ t8)) & 255u) == 0; });
        sts128(sb + OFF_XS + lane * 16, u.x, u.y, u.z, u.w);
      }
      __syncwarp();
      if (lane == 0) mbar_arrive(sb + BAR_XS);
      STAMP(25);
      const uint32_t par = __shfl_sync(0xffffffff, tag, 0);
      bar_sync(NB_G1D, 64);
      if (!EARLY) poll_counter(p.scr->cnt + CNT_KV + (cb >> 1), tag * 64);
      convx_issue(p, sb, 1, chb);
      convx_issue(p, sb, 0, chb + 64);
#pragma unroll 1
      for (int h = 1; h >= 0; h--) convx_finish(p, sb, h, chb + 64 - 64 * h, 0, par, lane);
      STAMP(48);
      gather_colsum(p, sb, 1, cb, tag8(tag), lane);
      STAMP(38);
      conv_service(p, sb, 1, chb, par, lane, [&]() {
        bar_sync(NB_WO, 160);
        if (elect_one()) red_release(p.scr->cnt + CNT_WO + cb);
        STAMP(49);
        poll_counter(p.scr->cnt + CNT_WO + cb, tag * 32);
        if (elect_one()) mbar_arrive(sb + BAR_WO);
        STAMP(46);
      });
      bar_arrive(NB_CD, 64);
    }
  } else if (warp >= 8) {
    const int w = warp & 3;
    {
      const int tid = tid_now();
      uint2* xs = &p.scr->xstat[rb * 64 + cb * 16 + (tid >> 3)];
      if ((tid & 7) == 0) st_ll2(xs, 0, 0);
      const uint32_t epoch = load_epoch(p, lin, lane);
      float sa[4] = {0.f, 0.f, 0.f, 0.f}, qa[4] = {0.f, 0.f, 0.f, 0.f};
#pragma unroll 1
      for (int i = 0; i < 10; i++) {
        mbar_wait(sb + BAR_AF + 8 * i, 0);
        const uint4 x4 = lds128(sb + OFF_A + i * A_SLOT + cb * 2048 + tid * 16);
        const uint32_t u[4] = {x4.x, x4.y, x4.z, x4.w};
#pragma unroll
        for (int e = 0; e < 4; e++) { const float a = bf_lo(u[e]), c = bf_hi(u[e]); sa[e] += a + c; qa[e] = fmaf(a, a, fmaf(c, c, qa[e])); }
      }
      float s = (sa[0] + sa[1]) + (sa[2] + sa[3]), q = (qa[0] + qa[1]) + (qa[2] + qa[3]);
#pragma unroll
      for (int o = 1; o <= 4; o <<= 1) { s += __shfl_xor_sync(0xffffffff, s, o); q += __shfl_xor_sync(0xffffffff, q, o); }
      const float m = s * (1.f / kD);
      const float r = rsqrtf(fmaxf(fmaf(-m, m, q * (1.f / kD)), 0.f) + 1e-5f);
      if ((tid & 7) == 0) st_ll2(xs, tagged(m, tag8(epoch + 1)), tagged(r, tag8(epoch + 1)));
      STAMPW(12); TR(70);
      fence_async_smem();
    }
    asm volatile("setmaxnreg.inc.sync.aligned.u32 160;");
    const unsigned short* bp = (const unsigned short*)p.bsp + rb * 64 + w * 16 + (lane >> 2);
    const uint32_t bias = bp[0] | ((uint32_t)bp[8] << 16);
    float d[96];
    uint32_t z[48];
    {
#pragma unroll
      for (int i = 0; i < 96; i++) d[i] = 0.f;
      bar_sync(NB_G1, 256);
      TR(71);
      gemm192<3>(d, sb, tid_now() == 0 TSA);
      mbar_arrive_if(sb + BAR_YT, tid_now() == 0);
      STAMPW(14); TR(74);
      mbar_wait2(sb + BAR_XS, 0, sb + BAR_ST + 8, 0);
      const uint32_t xa1 = sb + OFF_XS + (w * 16 + (lane >> 2)) * 8;
      gelu_tile<false>(d, z, nullptr, sb + OFF_CS + (lane & 3) * 8, lds64f(xa1), lds64f(xa1 + 64), sb + BAR_XS);
    }
#pragma unroll
    for (int j = 0; j < 96; j++) d[j] = (j & 2) ? bf_hi(bias) : bf_lo(bias);
    STAMPW(15); TR(76);
    gemm192<1>(d, sb, tid_now() == 0 TSA);
    STAMPW(16); TR(77);
    {
      const int l2 = tid_now() & 31;
      const uint32_t ha = swz_base(sb + OFF_A, w, l2);
      const bool tg = (l2 & 3) == (l2 >> 3);
      const uint32_t tm = tg ? ~1u : ~0u, tb = tg ? lds32<0>(sb + OFF_TAG) & 1 : 0;
#pragma unroll
      for (int j = 0; j < 24; j += 2) {
#pragma unroll
        for (int e = 0; e < 4; e++) z[2 * j + e] = hmul2(z[2 * j + e], pack2(d[4 * j + 2 * e], d[4 * j + 2 * e + 1]));
        stsm4((ha ^ ((j & 7) * 16)) + (j >> 3) * A_SLOT, (z[2 * j] & tm) | tb, (z[2 * j + 1] & tm) | tb, z[2 * j + 2], z[2 * j + 3]);
        if ((j & 7) == 6) {
          fence_async_smem();
          __syncwarp();
          mbar_arrive_if(sb + BAR_HR - 16 + (j >> 3) * 8, l2 == 0);
        }
      }
    }
    STAMPW(17); TR(78);
    const int t3 = tid_now();
    {
      acc_fence<40>(d);
      mbar_wait2(sb + BAR_HR, 0, sb + BAR_WF, 0);
      WG_FENCE();
      gemm3<0, 3, true>(d, sb, mkdesc(sb, 16, 1024, 1), mkdesc(sb, 2560, 128, 0), t3 == 0, 0 TSA);
      WG_WAIT(0);
      acc_fence<40>(d);
      TR(79);
#pragma unroll
      for (int j = 0; j < 5; j++)
        sts128(part_addr(sb, j, t3), pack2(d[8 * j], d[8 * j + 1]), pack2(d[8 * j + 2], d[8 * j + 3]), pack2(d[8 * j + 4], d[8 * j + 5]), pack2(d[8 * j + 6], d[8 * j + 7]));
      bar_sync(NB_C, 128);
      mbar_arrive_if(sb + BAR_PART, t3 == 0);
      STAMPW(45); TR(80);
    }
    {
      const uint32_t par = __shfl_sync(0xffffffff, lds32<0>(sb + OFF_TAG), 0), a = sb + w * 2048 + val_off(t3 & 31);
      const uint8_t* hs = p.scr->h + (size_t)rb * 12 * A_SLOT + w * 2048;
      const uint32_t rt = sb + OFF_RT + 8 * w;
#pragma unroll 1
      for (int it = 3; it < 12; it++) {
        mbar_wait(sb + BAR_AF + 8 * (it < 9 ? it : it - 9), 1);
        validate<2>(a + h_pos(it), par, rt, [&]() { bulk_g2s(sb + h_pos(it) + w * 2048, hs + g3_block(cb, it) * A_SLOT, 2048, rt); });
        if (elect_one()) mbar_arrive(sb + BAR_HV + 8 * (it - 3));
        if (it == 3) STAMPW(26);
      }
      {
        const int l = t3 & 31;
        mbar_wait(sb + BAR_YT, 1);
        validate<5>(sb + OFF_CV + w * 5120 + (l >> 2) * 128 + ((2 * (l & 3)) ^ (l >> 2)) * 16, par, rt, [&]() { tma2d(sb + OFF_CV + w * 5120, &p.tmY, rb * 64, cb * 160 + w * 40, rt); });
        bar_sync(NB_C, 128);
        mbar_arrive_if(sb + BAR_PART, t3 == 0);
        STAMPW(57);
      }
    }
  } else {
    const int h = warp >> 2, w = warp & 3;
    Taps k;
    asm volatile("setmaxnreg.inc.sync.aligned.u32 160;");
    if (h == 0) {
      uint4* zs = &p.scr->zstat[rb * 128 + w * 8 + (lane >> 2)];
      if ((lane & 3) == 0) st_ll4(zs + cb * 32, 0, 0, 0, 0);
      float d[96];
      uint32_t z[48];
#pragma unroll
      for (int i = 0; i < 96; i++) d[i] = 0.f;
      gemm192<0>(d, sb, tid_now() == 0 TSA, [&]() { bar_arrive(NB_G1, 256); });
      STAMPW(1); TR(0);
      const int tid = tid_now(), lane = tid & 31, g = lane >> 2, t = lane & 3;
      mbar_wait2(sb + BAR_XS, 0, sb + BAR_ST, 0);
      STAMPW(52); TR(1);
      const uint32_t xa1 = sb + OFF_XS + (w * 16 + g) * 8;
      const uint32_t tag = lds32<0>(sb + OFF_TAG);
      const float2 s0 = lds64f(xa1), s1 = lds64f(xa1 + 64);
      float st[4];
      gelu_tile<true>(d, z, st, sb + OFF_CS + 768 + t * 8, s0, s1, 0);
      TR(2);
      float2 sq = quad_sum(st, t);
      if (t < 2) st_ll2((uint2*)(zs + cb * 32) + t, tagged(sq.x, tag), __float_as_uint(sq.y));
      STAMPW(2); TR(3);
      { uint32_t tp = clock(); pace<false>(tp, ZW); }
      const uint4 u = poll<false>([&]() { return ld_ll4(zs + t * 32); }, [&](const uint4& v) { return (((v.x ^ tag) | (v.z ^ tag)) & 255u) == 0; });
      STAMPW(3); TR(10);
      st[0] = __uint_as_float(u.x); st[1] = __uint_as_float(u.y); st[2] = __uint_as_float(u.z); st[3] = __uint_as_float(u.w);
      sq = quad_sum(st, t);
      const float ca = 0.5f * ((t & 1) ? s1.y : s0.y), ma = sq.x * (1.f / 768.f);
      const float ra = ca * rsqrtf(fmaf(fmaxf(fmaf(-ma, ma, sq.y * (1.f / 768.f)), 0.f), ca * ca, 1e-5f));
      const uint32_t r2 = pack2(ra, ra);
      const float na = -ma * bf_lo(r2);
      const uint32_t n2 = pack2(na, na), r2o = __shfl_xor_sync(0xffffffff, r2, 1), n2o = __shfl_xor_sync(0xffffffff, n2, 1);
      const uint32_t fr[2] = {(t & 1) ? r2o : r2, (t & 1) ? r2 : r2o}, fn[2] = {(t & 1) ? n2o : n2, (t & 1) ? n2 : n2o};
      const uint32_t za = swz_base(sb + OFF_A, w, lane);
      TR(11);
      mbar_wait(sb + BAR_AE + 16, 0);
      TR(12);
#pragma unroll
      for (int j = 0; j < 24; j += 2)
        stsm4((za ^ ((j & 7) * 16)) + (j >> 3) * A_SLOT, hfma2(z[2 * j], fr[0], fn[0]), hfma2(z[2 * j + 1], fr[1], fn[1]), hfma2(z[2 * j + 2], fr[0], fn[0]), hfma2(z[2 * j + 3], fr[1], fn[1]));
      TR(14);
      fence_async_smem();
      bar_arrive(NB_Z, 160);
      STAMPW(4); TR(15);
      load_taps(k, p, chb + 64, tid);
    } else {
      if (w == 0) zero_pads(sb + OFF_CV, lane);
      const uint32_t epoch = load_epoch(p, lin, lane);
      const int t0 = (rb * 2 + (cb & 1)) * 32 + w * 8, c0 = (cb >> 1) * 320 + lane * 2;
      const __nv_bfloat16* kp = p.k + (size_t)(t0 - 3) * kD + c0;
      const __nv_bfloat16* vp = p.v + (size_t)t0 * kD + c0;
      const __nv_bfloat16* sp = p.shift + c0 * 4;
      const uint32_t oa = sb + OFF_CV + CV_SZ + kv_stage_addr(w, lane);
      bar_sync(NB_KF, 160);
      uint32_t tp = tstart;
      pace(tp, KV_T0);
      KvRegs n0, n1;
      uint32_t o[8];
      kv_load(n0, kp, vp, sp, t0 > 0);
      kv_load(n1, kp + 64, vp + 64, sp + 256, t0 > 0);
      const uint32_t tm = w >= 2 ? ~1u : ~0u, tb = w >= 2 ? (epoch + 1) & 1 : 0;
      kv_calc(n0, o);
      kv_put(o, oa, tm, tb);
      kv_calc(n1, o);
      kv_put(o, oa + 4096, tm, tb);
      fence_async_smem();
      bar_arrive(NB_KU, 160);
      TR(0);
      pace(tp, KV2T);
      kv_load(n0, kp + 128, vp + 128, sp + 512, t0 > 0);
      load_taps(k, p, chb, tid_now());
      kv_calc(n0, o);
      kv_put(o, oa + 8192, tm, tb);
      fence_async_smem();
      bar_arrive(NB_KU2, 160);
      STAMPW(13); TR(1);
    }
    uint32_t xw[2][10];
    {
      const int tid = tid_now();
      final_load_x(xw, p.x + (rb * 64 + w * 16 + ((tid & 31) >> 2)) * kD + cb * 160 + h * 80, tid & 3);
      conv_worker(p, k, sb, h, chb + 64 - 64 * h, w, tid & 31, tid, rb, cb TSA);
    }
    float d[40];
    const int t3 = tid_now();
    const uint32_t o0 = (rb * 64 + w * 16 + ((t3 & 31) >> 2)) * kD + cb * 160 + h * 80;
    float cf[2];
    uint32_t rn[4];
    const uint32_t xs_addr = sb + OFF_XS + (w * 16 + ((t3 & 31) >> 2)) * 8;
    TR(60);
    {
      const float2 s0 = lds64f(xs_addr), s1 = lds64f(xs_addr + 64);
      cf[0] = 0.25f * s0.y; cf[1] = 0.25f * s1.y;
      rn[0] = pack2(s0.y, s0.y); rn[1] = pack2(s1.y, s1.y);
      rn[2] = pack2(-s0.x * bf_lo(rn[0]), -s0.x * bf_lo(rn[0])); rn[3] = pack2(-s1.x * bf_lo(rn[1]), -s1.x * bf_lo(rn[1]));
    }
    const uint64_t da3 = mkdesc(sb, 16, 1024, 1), db3 = mkdesc(sb + h * 1280, 2560, 128, 0);
    if (h == 0) {
      mbar_wait(sb + BAR_PART, 0);
      TR(61);
#pragma unroll
      for (int j = 0; j < 5; j++) {
        const uint4 v = lds128(part_addr(sb, j, t3));
        d[8 * j] = bf_lo(v.x); d[8 * j + 1] = bf_hi(v.x); d[8 * j + 2] = bf_lo(v.y); d[8 * j + 3] = bf_hi(v.y);
        d[8 * j + 4] = bf_lo(v.z); d[8 * j + 5] = bf_hi(v.z); d[8 * j + 6] = bf_lo(v.w); d[8 * j + 7] = bf_hi(v.w);
      }
      fence_async_smem();
      bar_sync(NB_WG, 128);
      mbar_arrive_if(sb + BAR_WE + 16, t3 == 0);
      acc_fence<40>(d);
      mbar_wait2(sb + BAR_HV, 0, sb + w_full(3), 0);
    } else {
#pragma unroll
      for (int j = 0; j < 40; j++) d[j] = 0.f;
      acc_fence<40>(d);
      mbar_wait2(sb + BAR_HR, 0, sb + BAR_WF, 0);
      WG_FENCE();
      gemm3<0, 3, false>(d, sb, da3, db3, t3 == 0, 0 TSA);
    }
    TR(62);
    if (h == 0) STAMPW(36);
    WG_FENCE();
    gemm3<3, 12, false>(d, sb, da3, db3, t3 == 0, h && t3 == 0 TSA);
    WG_WAIT(0);
    GSTAMP(2, 12);
    acc_fence<40>(d);
    STAMPW(h ? 18 : 10);
    TR(63);
    const int l3 = tid_now() & 31;
    final_out(d, xw, rn, cf, sb + OFF_CV + h * 10240, p.out + o0, w, l3, [&]() {
      STAMPW(h ? 44 : 9);
      TR(64);
      mbar_wait(sb + BAR_PART, 1);
      TR(65);
    });
    TR(66);
    mbar_arrive_if(sb + BAR_WE, t3 == 0);
  }
}

typedef CUresult (*EncodeFn)(CUtensorMap*, CUtensorMapDataType, cuuint32_t, void*, const cuuint64_t*, const cuuint64_t*, const cuuint32_t*,
                             const cuuint32_t*, CUtensorMapInterleave, CUtensorMapSwizzle, CUtensorMapL2promotion, CUtensorMapFloatOOBfill);

void encode(EncodeFn fn, CUtensorMap* m, const void* ptr, int rank, const cuuint64_t* dims, const cuuint64_t* strides, const cuuint32_t* box,
            CUtensorMapSwizzle swz = CU_TENSOR_MAP_SWIZZLE_128B) {
  const cuuint32_t es[3] = {1, 1, 1};
  fn(m, CU_TENSOR_MAP_DATA_TYPE_BFLOAT16, rank, const_cast<void*>(ptr), dims, strides, box, es, CU_TENSOR_MAP_INTERLEAVE_NONE,
     swz, CU_TENSOR_MAP_L2_PROMOTION_L2_128B, CU_TENSOR_MAP_FLOAT_OOB_FILL_NONE);
}

}

extern "C" void kernel_launch(void* const* d_in, const int* in_sizes, int n_in, void* d_out, int out_size) {
  (void)in_sizes; (void)n_in; (void)out_size;
  static EncodeFn enc = nullptr;
  static Scratch* scr = nullptr;
  static int sms = 0;
  if (!enc) {
    void* fn = nullptr;
    cudaDriverEntryPointQueryResult qr;
    cudaGetDriverEntryPoint("cuTensorMapEncodeTiled", &fn, cudaEnableDefault, &qr);
    enc = (EncodeFn)fn;
    cudaFuncSetAttribute(fused_kernel, cudaFuncAttributeMaxDynamicSharedMemorySize, SMEM_BYTES);
    cudaGetSymbolAddress((void**)&scr, g_scr);
    int dev = 0;
    cudaGetDevice(&dev);
    cudaDeviceGetAttribute(&sms, cudaDevAttrMultiProcessorCount, dev);
  }
  Params p;
  p.scr = scr;
  p.by_smid = sms == 132;
  for (int b = 0; b < 132; b++) {
    const int tp = b >> 1, t7 = (tp - 32) / 7;
    const int lin = tp < 32 ? ((tp & 7) ? (tp & 7) * 16 : 8) + (tp >> 3) * 2 + (b & 1)
                            : (tp < 60 ? (tp - 31 - t7 * 7) * 16 + 8 + t7 * 2 + (b & 1) : (tp < 62 ? 128 + (b & 3) : b - 124));
    const int cb = ((lin >> 4) & 1) * 2 + (lin & 1), rb = (lin >> 5) * 8 + ((lin >> 1) & 7);
    p.job[b] = lin < 128 ? lin | cb << 8 | rb << 10 : lin | (lin & 3) << 8;
  }
  p.x = (const __nv_bfloat16*)d_in[0];
  p.k = (const __nv_bfloat16*)d_in[1];
  p.v = (const __nv_bfloat16*)d_in[2];
  p.shift = (const __nv_bfloat16*)d_in[3];
  p.ssmk = (const __nv_bfloat16*)d_in[4];
  p.ssmD = (const __nv_bfloat16*)d_in[5];
  p.wsp = (const __nv_bfloat16*)d_in[8];
  p.bsp = (const __nv_bfloat16*)d_in[9];
  p.wout = (const __nv_bfloat16*)d_in[10];
  p.out = (__nv_bfloat16*)d_out;
  {
    const cuuint64_t dims[2] = {kD, kS}, st[1] = {kD * 2};
    const cuuint32_t box[2] = {64, 64};
    encode(enc, &p.tmX, d_in[0], 2, dims, st, box);
  }
  {
    const cuuint64_t dims[3] = {64, kD, kF / 64}, st[2] = {kF * 2, 128};
    const cuuint32_t box[3] = {64, 64, 3};
    encode(enc, &p.tmW, d_in[7], 3, dims, st, box);
  }
  {
    const cuuint64_t dims[2] = {kS, kS}, st[1] = {kS * 2};
    const cuuint32_t box[2] = {64, 64};
    encode(enc, &p.tmWsp, d_in[8], 2, dims, st, box);
  }
  {
    const cuuint64_t dims[2] = {kS, kD}, st[1] = {kS * 2};
    const cuuint32_t box[2] = {64, 40};
    encode(enc, &p.tmY, scr->y, 2, dims, st, box);
  }
  {
    const cuuint64_t dims[3] = {1024, kD / 2, 4}, st[2] = {8192, 2048};
    const cuuint32_t box[3] = {16, 32, 4};
    encode(enc, &p.tmKV, scr->kvx, 3, dims, st, box, CU_TENSOR_MAP_SWIZZLE_32B);
  }
  fused_kernel<<<132, 512, SMEM_BYTES, cudaStreamPerThread>>>(p);
}
```
